```python
import torch

def _softmax(x, axis=-1):
    return torch.softmax(x, dim=axis)
def _gelu(x):
    return torch.nn.functional.gelu(x, approximate="tanh")
def _silu(x):
    return torch.nn.functional.silu(x)
def _sigmoid(x):
    return torch.sigmoid(x)
def _layernorm(x, axis=-1, eps=1e-5):
    m = x.mean(dim=axis, keepdim=True)
    v = x.var(dim=axis, keepdim=True, unbiased=False)
    return (x - m) / torch.sqrt(v + eps)
def _scatter_add(tgt, idx, src, axis=0):
    return tgt.clone().index_add_(axis, idx, src)
def _segment_sum(src, seg, n):
    out = torch.zeros((n,) + src.shape[1:], dtype=src.dtype)
    return out.index_add_(0, seg, src)
def _pad(x, pw):
    flat = tuple(v for pair in reversed(pw) for v in pair)
    return torch.nn.functional.pad(x, flat)

kernel_name = 'gated_mix__ssm_conv_s5__ssm_conv_h3__prompt'

def setup_inputs():

    _w = (lambda a: (lambda t: t.to(torch.bfloat16) if t.is_floating_point() else t)(torch.as_tensor(a)))
    def _A_setup():
        B, S, D = 1, 2048, 1024
        P = D
        Lambda_re = -0.5 * (lambda _x: torch.exp(torch.as_tensor(_x)))((lambda *s: torch.randn(*s, dtype=torch.bfloat16) * 0.2)(P))
        Lambda_im = (lambda *s: torch.randn(*s, dtype=torch.bfloat16) * 0.4)(P) * 1.0
        B_re = (lambda *s: torch.randn(*s, dtype=torch.bfloat16) * 0.2)(P, D) * (D ** -0.5)
        B_im = (lambda *s: torch.randn(*s, dtype=torch.bfloat16) * 0.2)(P, D) * (D ** -0.5)
        C_re = (lambda *s: torch.randn(*s, dtype=torch.bfloat16) * 0.2)(D, P) * (P ** -0.5)
        C_im = (lambda *s: torch.randn(*s, dtype=torch.bfloat16) * 0.2)(D, P) * (P ** -0.5)
        log_dt = (lambda *s: torch.randn(*s, dtype=torch.bfloat16) * 0.2)(P) * 0.3 - 2.0
        Dskip = (lambda *s: torch.randn(*s, dtype=torch.bfloat16) * 0.05)(D)
        return {
            "x": _w((lambda *s: torch.randn(*s, dtype=torch.bfloat16) * 0.05)(B, S, D)),
            "Lambda_re": _w(Lambda_re),
            "Lambda_im": _w(Lambda_im),
            "B_re": _w(B_re),
            "B_im": _w(B_im),
            "C_re": _w(C_re),
            "C_im": _w(C_im),
            "log_dt": _w(log_dt),
            "Dskip": _w(Dskip),
        }
    _A_in = _A_setup()

    def _B_setup():
        B, S, D = 1, 2048, 1024
        ks = 4
        return {
            "q": _w((lambda *s: torch.randn(*s, dtype=torch.bfloat16) * 0.05)(B, S, D)),
            "k": _w((lambda *s: torch.randn(*s, dtype=torch.bfloat16) * 0.4)(B, S, D)),
            "v": _w((lambda *s: torch.randn(*s, dtype=torch.bfloat16) * 0.2)(B, S, D)),
            "shift_k": _w((lambda *s: torch.randn(*s, dtype=torch.bfloat16) * 0.4)(D, ks) * 0.5),
            "ssm_k": _w((lambda *s: torch.randn(*s, dtype=torch.bfloat16) * 0.4)(D, S) * (1.0 / S ** 0.5)),
            "ssm_D": _w((lambda *s: torch.randn(*s, dtype=torch.bfloat16) * 0.2)(D)),
        }
    _B_in = _B_setup()

    return {
        "A_x": _A_in["x"],
        "A_Lambda_re": _A_in["Lambda_re"],
        "A_Lambda_im": _A_in["Lambda_im"],
        "A_B_re": _A_in["B_re"],
        "A_B_im": _A_in["B_im"],
        "A_C_re": _A_in["C_re"],
        "A_C_im": _A_in["C_im"],
        "A_log_dt": _A_in["log_dt"],
        "A_Dskip": _A_in["Dskip"],
        "B_q": _B_in["q"],
        "B_k": _B_in["k"],
        "B_v": _B_in["v"],
        "B_shift_k": _B_in["shift_k"],
        "B_ssm_k": _B_in["ssm_k"],
        "B_ssm_D": _B_in["ssm_D"],
        "gate_w": _w((lambda *s: torch.randn(*s, dtype=torch.bfloat16) * 0.05)(1024) * 16.0),
    }

def reference(A_x, A_Lambda_re, A_Lambda_im, A_B_re, A_B_im, A_C_re, A_C_im, A_log_dt, A_Dskip, B_q, B_k, B_v, B_shift_k, B_ssm_k, B_ssm_D, gate_w):
    def _A_ref(x, Lambda_re, Lambda_im, B_re, B_im, C_re, C_im, log_dt, Dskip):
        Bsz, L, H = x.shape
        Lam = Lambda_re + 1j * Lambda_im
        Bmat = B_re + 1j * B_im
        Cmat = C_re + 1j * C_im
        dt = torch.exp(log_dt)
        Lam_bar = torch.exp(dt * Lam)
        B_bar = ((Lam_bar - 1.0) / Lam)[:, None] * Bmat
        Bu = torch.einsum("bld,pd->blp", x + 0j, B_bar)
        h = torch.zeros_like(Bu[:, 0, :])
        hs = []
        for t in range(L):
            h = Lam_bar[None, :] * h + Bu[:, t, :]
            hs.append(h)
        hseq = torch.stack(hs, 1)
        y = 2.0 * torch.einsum("blp,dp->bld", hseq, Cmat).real + x * Dskip[None, None, :]
        return y

    def _B_ref(q, k, v, shift_k, ssm_k, ssm_D):
        B, S, D = q.shape
        ks = shift_k.shape[-1]
        k_pad = _pad(k, ((0, 0), (ks - 1, 0), (0, 0)))
        k_shift = torch.zeros_like(k)
        for t in range(ks):
            k_shift = k_shift + k_pad[:, t:t + S, :] * shift_k[:, ks - 1 - t][None, None, :]
        kv = k_shift * v
        L = 2 * S
        kv_pad = _pad(kv, ((0, 0), (0, S), (0, 0)))
        kf_pad = _pad(ssm_k, ((0, 0), (0, S)))
        kv_f = (lambda x, axes=(-2,-1): torch.fft.rfft2(x.float(), dim=axes))(kv_pad[:, None, :, :], axes=(1, 2))
        kf_f = (lambda x, axes=(-2,-1): torch.fft.rfft2(x.float(), dim=axes))(kf_pad[:, None, :], axes=(1, 2))
        kf_f = (lambda x, *d: x.permute(*d))(kf_f, 1, 2, 0)
        y_f = kv_f * kf_f[None, :, :, :]
        y = (lambda x, s, axes=(-2,-1): torch.fft.irfft2(x, s=s, dim=axes).to(torch.bfloat16))(y_f, (1, L), axes=(1, 2))[:, 0, :S, :]
        y = y + kv * ssm_D[None, None, :]
        return q * y

    x = A_x
    g = _sigmoid((x * gate_w).sum(-1, keepdims=True))
    a = _A_ref(x, A_Lambda_re, A_Lambda_im, A_B_re, A_B_im, A_C_re, A_C_im, A_log_dt, A_Dskip)
    b = _B_ref(x, B_k, B_v, B_shift_k, B_ssm_k, B_ssm_D)
    return g * a + (1 - g) * b
```

```cpp
#include <cuda_runtime.h>
#include <cuda_bf16.h>
#include <cuda.h>
#include <stdint.h>

namespace {
__device__ __forceinline__ uint32_t smem_u32(const void* p) { return (uint32_t)__cvta_generic_to_shared(p); }
__device__ __forceinline__ void mbar_init(uint32_t bar, uint32_t count) {
    asm volatile("mbarrier.init.shared::cta.b64 [%0], %1;" ::"r"(bar), "r"(count) : "memory");
}
__device__ __forceinline__ void mbar_expect_tx(uint32_t bar, uint32_t bytes) {
    asm volatile("mbarrier.arrive.expect_tx.shared::cta.b64 _, [%0], %1;" ::"r"(bar), "r"(bytes) : "memory");
}
__device__ __forceinline__ void mbar_arrive(uint32_t bar) {
    asm volatile("mbarrier.arrive.shared::cta.b64 _, [%0];" ::"r"(bar) : "memory");
}
__device__ __forceinline__ void mbar_wait(uint32_t bar, uint32_t parity) {
    asm volatile(
        "{\n"
        ".reg .pred p;\n"
        ".reg .u32 n;\n"
        "mov.u32 n, 0;\n"
        "LAB_WAIT:\n"
        "mbarrier.try_wait.parity.shared::cta.b64 p, [%0], %1;\n"
        "@p bra LAB_DONE;\n"
        "add.u32 n, n, 1;\n"
        "setp.lt.u32 p, n, 0x400000;\n"
        "@p bra LAB_WAIT;\n"
        "trap;\n"
        "LAB_DONE:\n"
        "}\n" ::"r"(bar), "r"(parity) : "memory");
}
__device__ __forceinline__ void tma_load_2d(uint32_t dst, const CUtensorMap* map, uint32_t bar, int c0, int c1) {
    asm volatile(
        "cp.async.bulk.tensor.2d.shared::cluster.global.mbarrier::complete_tx::bytes [%0], [%1, {%3, %4}], [%2];"
        ::"r"(dst), "l"((uint64_t)map), "r"(bar), "r"(c0), "r"(c1) : "memory");
}
__device__ __forceinline__ void tma_load_4d(uint32_t dst, const CUtensorMap* map, uint32_t bar, int c0, int c1, int c2, int c3) {
    asm volatile(
        "cp.async.bulk.tensor.4d.shared::cluster.global.mbarrier::complete_tx::bytes [%0], [%1, {%3, %4, %5, %6}], [%2];"
        ::"r"(dst), "l"((uint64_t)map), "r"(bar), "r"(c0), "r"(c1), "r"(c2), "r"(c3) : "memory");
}
__device__ __forceinline__ void tma_load_5d(uint32_t dst, const CUtensorMap* map, uint32_t bar, int c0, int c1, int c2, int c3, int c4) {
    asm volatile(
        "cp.async.bulk.tensor.5d.shared::cluster.global.mbarrier::complete_tx::bytes [%0], [%1, {%3, %4, %5, %6, %7}], [%2];"
        ::"r"(dst), "l"((uint64_t)map), "r"(bar), "r"(c0), "r"(c1), "r"(c2), "r"(c3), "r"(c4) : "memory");
}
__device__ __forceinline__ void bulk_load(uint32_t dst, const void* src, uint32_t bytes, uint32_t bar) {
    asm volatile("cp.async.bulk.shared::cluster.global.mbarrier::complete_tx::bytes [%0], [%1], %2, [%3];"
                 ::"r"(dst), "l"(src), "r"(bytes), "r"(bar) : "memory");
}
__device__ __forceinline__ void tma_store_3d(const CUtensorMap* map, uint32_t src, int c0, int c1, int c2) {
    asm volatile("cp.async.bulk.tensor.3d.global.shared::cta.bulk_group [%0, {%2, %3, %4}], [%1];"
                 ::"l"((uint64_t)map), "r"(src), "r"(c0), "r"(c1), "r"(c2) : "memory");
}
__device__ __forceinline__ void bulk_commit() { asm volatile("cp.async.bulk.commit_group;" ::: "memory"); }
__device__ __forceinline__ void bulk_wait0() { asm volatile("cp.async.bulk.wait_group 0;" ::: "memory"); }
__device__ __forceinline__ void bulk_wait_read0() { asm volatile("cp.async.bulk.wait_group.read 0;" ::: "memory"); }
__device__ __forceinline__ void fence_async_smem() { asm volatile("fence.proxy.async.shared::cta;" ::: "memory"); }
__device__ __forceinline__ void named_bar(int id, int n) { asm volatile("bar.sync %0, %1;" ::"r"(id), "r"(n) : "memory"); }
__device__ __forceinline__ void sts128(uint32_t addr, uint32_t a, uint32_t b, uint32_t c, uint32_t d) {
    asm volatile("st.shared.v4.b32 [%0], {%1, %2, %3, %4};" ::"r"(addr), "r"(a), "r"(b), "r"(c), "r"(d) : "memory");
}
__device__ __forceinline__ void prefetch_map(const CUtensorMap* m) {
    asm volatile("prefetch.tensormap [%0];" ::"l"((uint64_t)m) : "memory");
}
__device__ __forceinline__ void wgmma_fence() { asm volatile("wgmma.fence.sync.aligned;" ::: "memory"); }
__device__ __forceinline__ void wgmma_commit() { asm volatile("wgmma.commit_group.sync.aligned;" ::: "memory"); }
template <int N>
__device__ __forceinline__ void wgmma_wait() { asm volatile("wgmma.wait_group.sync.aligned %0;" ::"n"(N) : "memory"); }
template <int N>
__device__ __forceinline__ void fence_regs(float (&a)[N]) {
#pragma unroll
    for (int i = 0; i < N; ++i) asm volatile("" : "+f"(a[i])::"memory");
}
template <int N>
__device__ __forceinline__ void fence_regs(uint32_t (&a)[N]) {
#pragma unroll
    for (int i = 0; i < N; ++i) asm volatile("" : "+r"(a[i])::"memory");
}
#define R8(a, i) "+f"(a[i + 0]), "+f"(a[i + 1]), "+f"(a[i + 2]), "+f"(a[i + 3]), "+f"(a[i + 4]), "+f"(a[i + 5]), "+f"(a[i + 6]), "+f"(a[i + 7])
#define REGS32 "{%0, %1, %2, %3, %4, %5, %6, %7, %8, %9, %10, %11, %12, %13, %14, %15, %16, %17, %18, %19, %20, %21, %22, %23, %24, %25, %26, %27, %28, %29, %30, %31}"
#define REGS16 "{%0, %1, %2, %3, %4, %5, %6, %7, %8, %9, %10, %11, %12, %13, %14, %15}"

__host__ __device__ constexpr uint32_t desc_hi(uint32_t sbo, uint32_t mode) { return (sbo >> 4) | (mode << 30); }
__device__ __forceinline__ uint32_t desc_lo(uint32_t saddr, uint32_t lbo) { return ((saddr & 0x3FFFF) >> 4) | ((lbo >> 4) << 16); }
constexpr uint32_t HI128 = desc_hi(1024, 1), HI64 = desc_hi(512, 2);
#define W8(a, i) "=f"(a[i + 0]), "=f"(a[i + 1]), "=f"(a[i + 2]), "=f"(a[i + 3]), "=f"(a[i + 4]), "=f"(a[i + 5]), "=f"(a[i + 6]), "=f"(a[i + 7])
template <int TA, int TB, int ACC, uint32_t AHI, uint32_t BHI>
__device__ __forceinline__ void wgmma_n64_ss(float (&d)[32], uint32_t alo, uint32_t blo) {
#define N64_TEXT "{\n.reg .pred p;\n.reg .b64 da, db;\nsetp.ne.b32 p, %36, 0;\nmov.b64 da, {%32, %37};\nmov.b64 db, {%33, %38};\n" \
        "wgmma.mma_async.sync.aligned.m64n64k16.f32.bf16.bf16 " REGS32 ", da, db, p, 1, 1, %34, %35;\n}\n"
    if (ACC) asm volatile(N64_TEXT : R8(d, 0), R8(d, 8), R8(d, 16), R8(d, 24) : "r"(alo), "r"(blo), "n"(TA), "n"(TB), "n"(ACC), "n"(AHI), "n"(BHI));
    else asm volatile(N64_TEXT : W8(d, 0), W8(d, 8), W8(d, 16), W8(d, 24) : "r"(alo), "r"(blo), "n"(TA), "n"(TB), "n"(ACC), "n"(AHI), "n"(BHI));
}
template <int ACC, int SA>
__device__ __forceinline__ void wgmma_n32_tt(float (&d)[16], uint32_t alo, uint32_t blo) {
#define N32T_TEXT "{\n.reg .pred p;\n.reg .b64 da, db;\nsetp.ne.b32 p, %18, 0;\nmov.b64 da, {%16, %19};\nmov.b64 db, {%17, %20};\n" \
        "wgmma.mma_async.sync.aligned.m64n32k16.f32.bf16.bf16 " REGS16 ", da, db, p, %21, 1, 1, 1;\n}\n"
    if (ACC) asm volatile(N32T_TEXT : R8(d, 0), R8(d, 8) : "r"(alo), "r"(blo), "n"(ACC), "n"(HI64), "n"(HI128), "n"(SA));
    else asm volatile(N32T_TEXT : W8(d, 0), W8(d, 8) : "r"(alo), "r"(blo), "n"(ACC), "n"(HI64), "n"(HI128), "n"(SA));
}
template <int TB, int ACC, uint32_t BHI>
__device__ __forceinline__ void wgmma_n32_rs(float (&d)[16], uint32_t a0, uint32_t a1, uint32_t a2, uint32_t a3, uint32_t blo) {
#define N32_TEXT "{\n.reg .pred p;\n.reg .b64 db;\nsetp.ne.b32 p, %22, 0;\nmov.b64 db, {%20, %23};\n" \
        "wgmma.mma_async.sync.aligned.m64n32k16.f32.bf16.bf16 " REGS16 ", {%16, %17, %18, %19}, db, p, 1, 1, %21;\n}\n"
    if (ACC) asm volatile(N32_TEXT : R8(d, 0), R8(d, 8) : "r"(a0), "r"(a1), "r"(a2), "r"(a3), "r"(blo), "n"(TB), "n"(ACC), "n"(BHI));
    else asm volatile(N32_TEXT : W8(d, 0), W8(d, 8) : "r"(a0), "r"(a1), "r"(a2), "r"(a3), "r"(blo), "n"(TB), "n"(ACC), "n"(BHI));
}

__device__ __forceinline__ float bf16r(float x) { return __bfloat162float(__float2bfloat16_rn(x)); }
__device__ __forceinline__ uint32_t pack_bf16(float lo, float hi) {
    __nv_bfloat162 v = __floats2bfloat162_rn(lo, hi);
    return *reinterpret_cast<uint32_t*>(&v);
}
__device__ __forceinline__ __nv_bfloat162 as_bf2(uint32_t w) { return *reinterpret_cast<__nv_bfloat162*>(&w); }
__device__ __forceinline__ uint32_t as_u32(__nv_bfloat162 v) { return *reinterpret_cast<uint32_t*>(&v); }
__device__ __forceinline__ float bf_lo(uint32_t w) { return __uint_as_float(w << 16); }
__device__ __forceinline__ float bf_hi(uint32_t w) { return __uint_as_float(w & 0xFFFF0000u); }
__device__ __forceinline__ void ldsm_x4_t(uint32_t& r0, uint32_t& r1, uint32_t& r2, uint32_t& r3, uint32_t addr) {
    asm volatile("ldmatrix.sync.aligned.m8n8.x4.trans.shared.b16 {%0,%1,%2,%3}, [%4];"
                 : "=r"(r0), "=r"(r1), "=r"(r2), "=r"(r3) : "r"(addr) : "memory");
}
__device__ __forceinline__ void stsm_x4(uint32_t addr, uint32_t r0, uint32_t r1, uint32_t r2, uint32_t r3) {
    asm volatile("stmatrix.sync.aligned.m8n8.x4.shared.b16 [%0], {%1,%2,%3,%4};"
                 ::"r"(addr), "r"(r0), "r"(r1), "r"(r2), "r"(r3) : "memory");
}
__device__ __forceinline__ void stsm_x4_t(uint32_t addr, uint32_t r0, uint32_t r1, uint32_t r2, uint32_t r3) {
    asm volatile("stmatrix.sync.aligned.m8n8.x4.trans.shared.b16 [%0], {%1,%2,%3,%4};"
                 ::"r"(addr), "r"(r0), "r"(r1), "r"(r2), "r"(r3) : "memory");
}
__device__ __forceinline__ uint32_t lds32(uint32_t addr) {
    uint32_t v;
    asm volatile("ld.shared.b32 %0, [%1];" : "=r"(v) : "r"(addr));
    return v;
}

typedef CUresult (*EncodeFn)(CUtensorMap*, CUtensorMapDataType, cuuint32_t, void*, const cuuint64_t*, const cuuint64_t*,
                             const cuuint32_t*, const cuuint32_t*, CUtensorMapInterleave, CUtensorMapSwizzle,
                             CUtensorMapL2promotion, CUtensorMapFloatOOBfill);
EncodeFn get_encode() {
    static EncodeFn fn = nullptr;
    if (!fn) {
        void* p = nullptr;
        cudaDriverEntryPointQueryResult qres;
        cudaGetDriverEntryPoint("cuTensorMapEncodeTiled", &p, cudaEnableDefault, &qres);
        fn = (EncodeFn)p;
    }
    return fn;
}
}
namespace {
constexpr double c_pi = 3.14159265358979323846;
constexpr double c_cos256(int i) {
    i &= 255;
    if (i > 128) i = 256 - i;
    double sgn = 1.0;
    if (i > 64) { i = 128 - i; sgn = -1.0; }
    if (i == 64) return 0.0;
    double x = 2.0 * c_pi * i / 256.0, x2 = x * x, term = 1.0, sum = 1.0;
    for (int k = 1; k < 20; ++k) { term *= -x2 / ((2 * k - 1) * (2 * k)); sum += term; }
    return sgn * sum;
}
constexpr uint32_t c_bf16(double v) {
    if (v == 0.0) return 0u;
    uint32_t s = v < 0 ? 0x8000u : 0u;
    double a = v < 0 ? -v : v;
    int e = 0;
    while (a >= 2.0) { a *= 0.5; ++e; }
    while (a < 1.0) { a *= 2.0; --e; }
    int r = (int)(a * 128.0 + 0.5);
    if (r == 256) { r = 128; ++e; }
    return s | (uint32_t)((e + 127) << 7) | (uint32_t)(r - 128);
}
__host__ __device__ constexpr int conv_k1(int r) { return (r & 8) ? 63 - (((r >> 4) << 3) | (r & 7)) : (((r >> 4) << 3) | (r & 7)); }
struct ConvTab { uint32_t w[2 * 2048]; };
constexpr ConvTab make_conv_tab() {
    ConvTab t{};
    uint32_t cs[256] = {};
    for (int i = 0; i < 256; ++i) cs[i] = c_bf16(c_cos256(i));
    for (int m = 0; m < 2; ++m)
        for (int r = 0; r < 64; ++r)
            for (int c = 0; c < 64; ++c) {
                int a = 0;
                if (m == 0) {
                    const int ro = (r >> 4) & 1, ri = r & 15, co = (c >> 4) & 1, ci = c & 15;
                    a = (c >= 32) ? 8 * ri * (2 * ci + 1) : (r >= 32) ? 8 * ci * (2 * ri + 1) : 16 * ri * ci;
                    a += (ro == co) ? 0 : (ro == 0) ? 192 : 64;
                } else {
                    const int n1 = 2 * (c & 31) + (c >> 5);
                    a = n1 * (2 * (((r >> 4) << 3) | (r & 7)) + 1) + ((r & 8) ? 64 : 0);
                }
                const int off = r * 128 + (((c >> 3) ^ (r & 7)) << 4) + (c & 7) * 2;
                t.w[m * 2048 + (off >> 2)] |= cs[a & 255] << ((off & 2) * 8);
            }
    return t;
}
__device__ __align__(128) constexpr ConvTab g_conv_tab = make_conv_tab();

struct Twiddle { uint32_t r[8], i[8], n[8]; };
constexpr double c_cospi(double x) {
    double sgn = 1.0;
    if (x > 0.5) { x = 1.0 - x; sgn = -1.0; }
    const double y = c_pi * x, y2 = y * y;
    double term = 1.0, sum = 1.0;
    for (int k = 1; k < 12; ++k) { term *= -y2 / ((2 * k - 1) * (2 * k)); sum += term; }
    return sgn * sum;
}
struct TwTab { uint32_t w[3072]; };
constexpr TwTab make_tw_tab() {
    TwTab t{};
    for (int th = 0; th < 128; ++th)
        for (int q = 0; q < 8; ++q)
            for (int e = 0; e < 2; ++e) {
                const int k1 = conv_k1(16 * (th >> 5) + 8 * (q & 1) + ((th & 31) >> 2)), n2 = 8 * (q >> 1) + 2 * (th & 3) + e;
                const double x = (double)(n2 * (2 * k1 + 1)) / 4096.0;
                const double cs = c_cospi(x), sn = n2 == 0 ? 0.0 : c_cospi(x > 0.5 ? x - 0.5 : 0.5 - x);
                t.w[((q >> 2) * 128 + th) * 4 + (q & 3)] |= c_bf16(cs * 0.0625) << (16 * e);
                t.w[((2 + (q >> 2)) * 128 + th) * 4 + (q & 3)] |= c_bf16(-sn * 0.0625) << (16 * e);
                t.w[((4 + (q >> 2)) * 128 + th) * 4 + (q & 3)] |= c_bf16(sn * 0.0625) << (16 * e);
            }
    return t;
}
__device__ __align__(128) constexpr TwTab g_tw_tab = make_tw_tab();
__device__ __forceinline__ void load_twiddle(Twiddle& tw, const uint4* p) {
#pragma unroll
    for (int q = 0; q < 2; ++q) {
        const uint4 a = __ldg(p + q * 128);
        const uint4 b = __ldg(p + (2 + q) * 128);
        tw.r[4 * q] = a.x; tw.r[4 * q + 1] = a.y; tw.r[4 * q + 2] = a.z; tw.r[4 * q + 3] = a.w;
        const uint4 n = __ldg(p + (4 + q) * 128);
        tw.n[4 * q] = n.x; tw.n[4 * q + 1] = n.y; tw.n[4 * q + 2] = n.z; tw.n[4 * q + 3] = n.w;
        tw.i[4 * q] = b.x; tw.i[4 * q + 1] = b.y; tw.i[4 * q + 2] = b.z; tw.i[4 * q + 3] = b.w;
    }
}

__device__ __forceinline__ int fresh_tid() { int v; asm volatile("mov.u32 %0, %tid.x;" : "=r"(v)); return v; }
__device__ __forceinline__ uint32_t hmul(uint32_t a, uint32_t b) { return as_u32(__hmul2_rn(as_bf2(a), as_bf2(b))); }
__device__ __forceinline__ uint32_t hadd(uint32_t a, uint32_t b) { return as_u32(__hadd2_rn(as_bf2(a), as_bf2(b))); }
__device__ __forceinline__ uint32_t hsub(uint32_t a, uint32_t b) { return as_u32(__hsub2_rn(as_bf2(a), as_bf2(b))); }
__device__ __forceinline__ uint32_t hfma(uint32_t a, uint32_t b, uint32_t c) { return as_u32(__hfma2(as_bf2(a), as_bf2(b), as_bf2(c))); }

__device__ __forceinline__ void conv_dft16(float (&x)[16], const uint32_t (&f)[8], uint32_t blo) {
    wgmma_n32_rs<0, 0, HI128>(x, f[0], f[1], f[2], f[3], blo);
    wgmma_n32_rs<0, 1, HI128>(x, f[4], f[5], f[6], f[7], blo + 2);
}
__device__ __forceinline__ void conv_s1(float (&dE)[32], float (&dO)[32], uint32_t tlo, uint32_t ulo) {
    wgmma_n64_ss<0, 1, 0, HI128, HI64>(dE, tlo + 512, ulo);
    wgmma_n64_ss<0, 1, 0, HI128, HI64>(dO, tlo + 512 + 4, ulo + 128);
    wgmma_n64_ss<0, 1, 1, HI128, HI64>(dE, tlo + 512 + 2, ulo + 64);
    wgmma_n64_ss<0, 1, 1, HI128, HI64>(dO, tlo + 512 + 6, ulo + 192);
}
template <int S>
__device__ __forceinline__ void conv_t1(const float (&dE)[32], const float (&dO)[32], const Twiddle& tw, float dsk, uint32_t (&fs)[8], uint32_t (&fd)[8]) {
    uint32_t ar[8], ai[8];
#pragma unroll
    for (int j = 0; j < 4; ++j) {
        const int i = 16 * S + 4 * j;
        const uint32_t e0 = pack_bf16(i == 16 ? dE[i] + dsk : dE[i], dE[i + 1]), e1 = pack_bf16(dE[i + 2], dE[i + 3]);
        const uint32_t o0 = pack_bf16(dO[i], dO[i + 1]), o1 = pack_bf16(dO[i + 2], dO[i + 3]);
        ar[2 * j] = hadd(e0, o0); ai[2 * j] = hadd(e1, o1);
        ar[2 * j + 1] = hsub(e0, o0); ai[2 * j + 1] = hsub(o1, e1);
    }
#pragma unroll
    for (int q = 0; q < 4; ++q) {
        const uint32_t pr = hfma(ar[q], tw.r[q], hmul(ai[q], tw.n[q])), pi = hfma(ar[q], tw.i[q], hmul(ai[q], tw.r[q]));
        fs[q] = hfma(ar[4 + q], tw.r[4 + q], hfma(ai[4 + q], tw.n[4 + q], pr));
        fs[4 + q] = hfma(ar[4 + q], tw.i[4 + q], hfma(ai[4 + q], tw.r[4 + q], pi));
        fd[q] = hfma(pr, 0xC000C000u, fs[q]);
        fd[4 + q] = hfma(pi, 0xC000C000u, fs[4 + q]);
    }
}
__device__ __forceinline__ void conv_prod(const float (&xu)[16], const float (&xk)[16], uint32_t (&f)[8]) {
#pragma unroll
    for (int q = 0; q < 4; ++q) {
        float pr[2], pi[2];
#pragma unroll
        for (int e = 0; e < 2; ++e) {
            const float ur = xu[2 * q + e], ui = xu[8 + 2 * q + e], kr = xk[2 * q + e], ki = xk[8 + 2 * q + e];
            pr[e] = fmaf(ur, kr, -ui * ki);
            pi[e] = fmaf(-ur, ki, -ui * kr);
        }
        f[q] = pack_bf16(pr[0], pr[1]);
        f[4 + q] = pack_bf16(pi[0], pi[1]);
    }
}
template <bool SYNC, bool NEXT, class G>
__device__ __forceinline__ void conv_channel(float (&dE)[32], float (&dO)[32], const Twiddle& tw, float dsk, uint32_t tlo, uint32_t nxt,
                                             uint32_t wre, uint32_t wim, int bar, G before_next) {
    float xuE[16], xuO[16], xkE[16], xkO[16];
    {
        uint32_t fs[8], fd[8], gs[8], gd[8];
        conv_t1<0>(dE, dO, tw, 0.f, fs, fd);
        wgmma_fence();
        conv_dft16(xuE, fs, tlo);
        conv_dft16(xuO, fd, tlo + 256);
        wgmma_commit();
        conv_t1<1>(dE, dO, tw, dsk, gs, gd);
        wgmma_fence();
        conv_dft16(xkE, gs, tlo);
        conv_dft16(xkO, gd, tlo + 256);
        wgmma_commit();
        before_next();
        wgmma_wait<0>();
        fence_regs(xuE); fence_regs(xuO); fence_regs(xkE); fence_regs(xkO);
        fence_regs(fs); fence_regs(fd); fence_regs(gs); fence_regs(gd);
    }
    uint32_t fe[8], fo[8];
    conv_prod(xuE, xkE, fe);
    conv_prod(xuO, xkO, fo);
    wgmma_fence();
    conv_dft16(xuE, fe, tlo);
    conv_dft16(xuO, fo, tlo + 4);
    wgmma_commit();
    if (NEXT) {
        conv_s1(dE, dO, tlo, nxt);
        wgmma_commit();
    }
    wgmma_wait<NEXT ? 1 : 0>();
    fence_regs(xuE); fence_regs(xuO);
    fence_regs(fe); fence_regs(fo);
    uint32_t zr[8], zi[8], wr[8], wi[8];
#pragma unroll
    for (int q = 0; q < 4; ++q) {
        const uint32_t er = pack_bf16(xuE[2 * q], xuE[2 * q + 1]), ei = pack_bf16(xuE[8 + 2 * q], xuE[9 + 2 * q]);
        const uint32_t or_ = pack_bf16(xuO[2 * q], xuO[2 * q + 1]), oi = pack_bf16(xuO[8 + 2 * q], xuO[9 + 2 * q]);
        zr[q] = hadd(er, or_); zi[q] = hadd(ei, oi); zr[4 + q] = hsub(er, or_); zi[4 + q] = hsub(ei, oi);
    }
#pragma unroll
    for (int q = 0; q < 8; ++q) {
        wr[q] = hfma(zr[q], tw.r[q], hmul(zi[q], tw.n[q]));
        wi[q] = hfma(zr[q], tw.i[q], hmul(zi[q], tw.r[q]));
    }
    if (SYNC) named_bar(bar, 128);
    stsm_x4(wre, hadd(wr[0], wr[1]), hadd(wr[2], wr[3]), hadd(wr[4], wr[5]), hadd(wr[6], wr[7]));
    stsm_x4(wre + 512, hsub(wi[1], wi[0]), hsub(wi[3], wi[2]), hsub(wi[5], wi[4]), hsub(wi[7], wi[6]));
    stsm_x4(wim, hsub(wr[1], wr[0]), hsub(wr[3], wr[2]), hsub(wr[5], wr[4]), hsub(wr[7], wr[6]));
    stsm_x4(wim + 512, hadd(wi[0], wi[1]), hadd(wi[2], wi[3]), hadd(wi[4], wi[5]), hadd(wi[6], wi[7]));
}
template <bool NEXT, class G>
__device__ __forceinline__ void conv_pair(float (&dE)[32], float (&dO)[32], const Twiddle& tw, uint32_t dd, uint32_t tlo, uint32_t u0, uint32_t un,
                                          uint32_t lo, int BAR, G before_next) {
    conv_channel<false, true>(dE, dO, tw, bf_lo(dd), tlo, desc_lo(u0 + 4096, 8192), u0 + lo, u0 + 8192 + lo, BAR, []() {});
    wgmma_wait<0>();
    fence_regs(dE); fence_regs(dO);
    conv_channel<true, NEXT>(dE, dO, tw, bf_hi(dd), tlo, desc_lo(un, 8192), u0 + 4096 + lo, u0 + 12288 + lo, BAR, before_next);
    fence_async_smem();
    named_bar(BAR, 128);
    float ye[16], yo[16];
    wgmma_fence();
    const uint32_t wlo = desc_lo(u0, 4096);
    wgmma_n32_tt<0, 1>(ye, wlo, tlo + 512);
    wgmma_n32_tt<0, -1>(yo, wlo + 512, tlo + 512 + 4);
#pragma unroll
    for (int k = 1; k < 4; ++k) {
        wgmma_n32_tt<1, 1>(ye, wlo + 64 * k, tlo + 512 + 128 * k);
        wgmma_n32_tt<1, -1>(yo, wlo + 512 + 64 * k, tlo + 512 + 4 + 128 * k);
    }
    wgmma_commit();
    wgmma_wait<0>();
    fence_regs(ye); fence_regs(yo);
    if (NEXT) { fence_regs(dE); fence_regs(dO); }
    named_bar(BAR, 128);
    const int t = fresh_tid();
    const uint32_t ya = u0 + (t & 64) * 64 + (t & 31) * 64 + (((((t >> 4) & 2) ^ (t >> 1)) & 3) << 4);
#pragma unroll
    for (int h = 0; h < 2; ++h) {
        stsm_x4_t(ya ^ (16 * h), pack_bf16(ye[2 * h], ye[2 * h + 1]), pack_bf16(ye[4 + 2 * h], ye[5 + 2 * h]),
                  pack_bf16(ye[8 + 2 * h], ye[9 + 2 * h]), pack_bf16(ye[12 + 2 * h], ye[13 + 2 * h]));
        stsm_x4_t((ya ^ (16 * h)) + 2048, pack_bf16(yo[2 * h], yo[2 * h + 1]), pack_bf16(yo[4 + 2 * h], yo[5 + 2 * h]),
                  pack_bf16(yo[8 + 2 * h], yo[9 + 2 * h]), pack_bf16(yo[12 + 2 * h], yo[13 + 2 * h]));
    }
    fence_async_smem();
    __syncwarp();
}
}

namespace {

constexpr int S_LEN = 2048;
constexpr int D_DIM = 1024;

#define REG_P 24
#define REG_AB 168
#define REG_C 152
#define SKEW1 4
#define TK_PF0 0
#define GAP_PF 300
#define TK_KV0 2
#define TK_KV1 4
#define GAP_KV 50
#define GAP_ST 50
#define GAP_HB 100
#define PFD 7
#define CWAIT 0
#define GAP_Y 100
#define GAP_X 150
#define SLOT4 20
#define SKEW2 4
#define KVFMA 0
#define G2SIG 0
#define GAP_CV 100
#define TK_C 8
#define GWAIT 1

__device__ __align__(1024) __nv_bfloat16 g_H[2 * D_DIM * S_LEN];
__device__ __align__(1024) __nv_bfloat16 g_y2[D_DIM * S_LEN];
__device__ __align__(1024) __nv_bfloat16 g_kvT[D_DIM * S_LEN];
__device__ __align__(128) float g_gate[S_LEN];
__device__ __align__(128) unsigned long long g_agg[8 * D_DIM];
__device__ __align__(128) unsigned int g_cnt[48 * 32];

#define STAMP(k, s) do { } while (0)
#define SAMPLE(i) do { } while (0)

__device__ __forceinline__ void tma_store_5d(const CUtensorMap* map, uint32_t src, int c0, int c1, int c2, int c3, int c4) {
    asm volatile("cp.async.bulk.tensor.5d.global.shared::cta.bulk_group [%0, {%2, %3, %4, %5, %6}], [%1];"
                 ::"l"((uint64_t)map), "r"(src), "r"(c0), "r"(c1), "r"(c2), "r"(c3), "r"(c4) : "memory");
}
#define ELECT "{\n.reg .pred p;\nelect.sync _|p, 0xffffffff;\n@p "
__device__ __forceinline__ void e_expect_tx(uint32_t bar, uint32_t bytes) {
    asm volatile(ELECT "mbarrier.arrive.expect_tx.shared::cta.b64 _, [%0], %1;\n}" ::"r"(bar), "r"(bytes) : "memory");
}
__device__ __forceinline__ void e_arrive(uint32_t bar) {
    asm volatile(ELECT "mbarrier.arrive.shared::cta.b64 _, [%0];\n}" ::"r"(bar) : "memory");
}
__device__ __forceinline__ void e_load_4d(uint32_t dst, const CUtensorMap* map, uint32_t bar, int c0, int c1, int c2, int c3) {
    asm volatile(ELECT "cp.async.bulk.tensor.4d.shared::cluster.global.mbarrier::complete_tx::bytes [%0], [%1, {%3, %4, %5, %6}], [%2];\n}"
        ::"r"(dst), "l"((uint64_t)map), "r"(bar), "r"(c0), "r"(c1), "r"(c2), "r"(c3) : "memory");
}
__device__ __forceinline__ void e_load_5d(uint32_t dst, const CUtensorMap* map, uint32_t bar, int c0, int c1, int c2, int c3, int c4) {
    asm volatile(ELECT "cp.async.bulk.tensor.5d.shared::cluster.global.mbarrier::complete_tx::bytes [%0], [%1, {%3, %4, %5, %6, %7}], [%2];\n}"
        ::"r"(dst), "l"((uint64_t)map), "r"(bar), "r"(c0), "r"(c1), "r"(c2), "r"(c3), "r"(c4) : "memory");
}
__device__ __forceinline__ void e_bulk_load(uint32_t dst, const void* src, uint32_t bytes, uint32_t bar) {
    asm volatile(ELECT "cp.async.bulk.shared::cluster.global.mbarrier::complete_tx::bytes [%0], [%1], %2, [%3];\n}"
                 ::"r"(dst), "l"(src), "r"(bytes), "r"(bar) : "memory");
}
__device__ __forceinline__ void l2_prefetch(const void* p, uint32_t bytes) {
    asm volatile("cp.async.bulk.prefetch.L2.global [%0], %1;" ::"l"(p), "r"(bytes) : "memory");
}
__device__ __forceinline__ void l2_prefetch_4d(const CUtensorMap* map, int c0, int c1, int c2, int c3) {
    asm volatile("cp.async.bulk.prefetch.tensor.4d.L2.global [%0, {%1, %2, %3, %4}];" ::"l"((uint64_t)map), "r"(c0), "r"(c1), "r"(c2), "r"(c3) : "memory");
}
__device__ __forceinline__ void l2_prefetch_5d(const CUtensorMap* map, int c0, int c1, int c2, int c3, int c4) {
    asm volatile("cp.async.bulk.prefetch.tensor.5d.L2.global [%0, {%1, %2, %3, %4, %5}];" ::"l"((uint64_t)map), "r"(c0), "r"(c1), "r"(c2), "r"(c3), "r"(c4) : "memory");
}
__device__ __forceinline__ unsigned int ld_relaxed(const unsigned int* p) {
    unsigned int v;
    asm volatile("ld.relaxed.gpu.global.u32 %0, [%1];" : "=r"(v) : "l"(p) : "memory");
    return v;
}
__device__ __forceinline__ void fence_async_global() { asm volatile("fence.proxy.async.global;" ::: "memory"); }
__device__ __forceinline__ void wait_counter(const unsigned int* p, unsigned int target) {
    unsigned int v;
    int it = 0;
    do { asm volatile("ld.acquire.gpu.global.u32 %0, [%1];" : "=r"(v) : "l"(p) : "memory"); } while (v != target && ++it < (1 << 22));
    fence_async_global();
}
__device__ __forceinline__ void red_release(unsigned int* p, unsigned int n) {
    asm volatile("red.release.gpu.global.add.u32 [%0], %1;" ::"l"(p), "r"(n) : "memory");
}
__device__ __forceinline__ uint4 ldg128(const void* p) {
    uint4 v;
    asm volatile("ld.global.nc.v4.u32 {%0,%1,%2,%3}, [%4];" : "=r"(v.x), "=r"(v.y), "=r"(v.z), "=r"(v.w) : "l"(p));
    return v;
}
__device__ __forceinline__ void stg128(void* p, uint32_t a, uint32_t b, uint32_t c, uint32_t d) {
    asm volatile("st.global.v4.b32 [%0], {%1, %2, %3, %4};" ::"l"(p), "r"(a), "r"(b), "r"(c), "r"(d) : "memory");
}

template <int TA>
__device__ __forceinline__ void wgmma_n128(float (&d)[64], uint32_t alo, uint32_t blo, int acc) {
    asm volatile(
        "{\n.reg .pred p;\n.reg .b64 da, db;\nsetp.ne.b32 p, %67, 0;\nmov.b64 da, {%64, %69};\nmov.b64 db, {%65, %66};\n"
        "wgmma.mma_async.sync.aligned.m64n128k16.f32.bf16.bf16 "
        "{%0, %1, %2, %3, %4, %5, %6, %7, %8, %9, %10, %11, %12, %13, %14, %15, "
        "%16, %17, %18, %19, %20, %21, %22, %23, %24, %25, %26, %27, %28, %29, %30, %31, "
        "%32, %33, %34, %35, %36, %37, %38, %39, %40, %41, %42, %43, %44, %45, %46, %47, "
        "%48, %49, %50, %51, %52, %53, %54, %55, %56, %57, %58, %59, %60, %61, %62, %63}, "
        "da, db, p, 1, 1, %68, 0;\n"
        "}\n"
        : R8(d, 0), R8(d, 8), R8(d, 16), R8(d, 24), R8(d, 32), R8(d, 40), R8(d, 48), R8(d, 56)
        : "r"(alo), "r"(blo), "n"(HI128), "r"(acc), "n"(TA), "n"(TA ? HI64 : HI128));
}

constexpr int NST = 5;
constexpr int OFF_BB = 4 * 32768;
constexpr int OFF_CT = 5 * 32768;
constexpr int OFF_CU = OFF_CT + 32768;
__host__ __device__ constexpr uint32_t conv_buf(int p) { return OFF_CT + 16384 + (p == 3 ? 0 : p) * 16384; }
constexpr int OFF_PAR = OFF_CU + 32768;
constexpr int OFF_BAR = OFF_PAR + 2048;
constexpr int SMEM_BYTES = OFF_BAR + 896;
static_assert(SMEM_BYTES <= 232448, "smem layout");

static_assert(SLOT4 % 4 == 0 && SLOT4 <= 24, "ring");
constexpr uint32_t PH4 = (SLOT4 / 4 - 1) & 1;
__host__ __device__ constexpr int ring_slot(int kb) { return (kb - SLOT4 + 4) % 5; }
__host__ __device__ constexpr uint32_t ring_par(int kb) { return ((SLOT4 / 4 - 1 + (kb - SLOT4 + 4) / 5) & 1) ^ (ring_slot(kb) == 4 ? PH4 : 0); }

struct Maps {
    CUtensorMap x5, b4, cre, cim, sk, yt, out, kvst, bre, bim;
};

__device__ __forceinline__ void cmul(float& r, float& i, float ar, float ai, float br, float bi) {
    const float a = ar * br - ai * bi, b = ar * bi + ai * br;
    r = a; i = b;
}
__device__ __forceinline__ void csqr(float& r, float& i) { const float a = r * r - i * i, b = 2.f * r * i; r = a; i = b; }
__device__ __forceinline__ float after(float v, float dep) { return __float_as_uint(dep) == 0x7fedcba9u ? dep : v; }

template <int BMODE>
__global__ void __launch_bounds__(512, 1)
fused_kernel(const __nv_bfloat16* __restrict__ x,
             const __nv_bfloat16* __restrict__ kin, const __nv_bfloat16* __restrict__ vin, const __nv_bfloat16* __restrict__ ssm_k,
             const __nv_bfloat16* __restrict__ shift_k, const __nv_bfloat16* __restrict__ ssm_D,
             const __nv_bfloat16* __restrict__ lam_re, const __nv_bfloat16* __restrict__ lam_im,
             const __nv_bfloat16* __restrict__ log_dt, const __nv_bfloat16* __restrict__ gate_w,
             const __nv_bfloat16* __restrict__ dskip,
             const __nv_bfloat16* __restrict__ c_re, const __nv_bfloat16* __restrict__ c_im,
             const __grid_constant__ Maps maps) {
    constexpr bool MERGED = BMODE != 0, SW = BMODE == 2;
    extern __shared__ __align__(1024) unsigned char smem_raw[];
    const uint32_t sbase = smem_u32(smem_raw);
    const uint32_t bar_full = sbase + OFF_BAR;
    const uint32_t bar_empty = bar_full + 32;
    const uint32_t bar_full2 = bar_empty + 32;
    const uint32_t bar_empty2 = bar_full2 + 40;
    const uint32_t bar_k = bar_empty2 + 40;
    const uint32_t bar_tab = bar_k + 32;
    const uint32_t bar_ab = bar_tab + 8;
    const uint32_t bar_adone = bar_ab + 8;
    const uint32_t bar_par = bar_adone + 8;
    const uint32_t bar_y = bar_par + 8;
    const uint32_t bar_rel = bar_y + 8;
    const uint32_t bar_kvrel = bar_rel + 8;
    const uint32_t bar_fh = bar_kvrel + 8;
    const uint32_t bar_tick = bar_fh + 24;
    const uint32_t bar_stg = bar_tick + 104;
    const uint32_t bar_bias = bar_stg + 112;
    const uint32_t bar_hw = bar_bias + 16;
    const uint32_t bar_gate = bar_hw + 32;
    const uint32_t bar_ascan = bar_gate + 8;
    const uint32_t bar_g2 = bar_hw;
    const uint32_t w_bid = bar_full + 600, w_dsk = bar_full + 608, w_ones = bar_full + 640;
    const int tid = threadIdx.x, warp = __shfl_sync(0xffffffffu, tid >> 5, 0), wg = warp >> 2, lane = tid & 31;
    int bid = blockIdx.x;
    {
        unsigned int sm, nsm;
        asm volatile("mov.u32 %0, %smid;" : "=r"(sm));
        asm volatile("mov.u32 %0, %nsmid;" : "=r"(nsm));
        if (gridDim.x == 132 && nsm == 132) {
            const int tpc = sm >> 1;
            int gp, ix;
            if (tpc < 32) { gp = tpc & 7; ix = tpc >> 3; }
            else if (tpc < 60) { ix = ((tpc - 32) * 37) >> 8; gp = tpc - 31 - 7 * ix; ix += 4; }
            else { gp = 0; ix = tpc - 58; }
            bid = (tpc | 1) == 61 ? 128 : (4 * (gp >> 1) + (ix >> 1)) * 8 + 4 * (gp & 1) + 2 * (ix & 1) + (sm & 1);
        }
    }
    if (bid >= 128) {
        if (tid == 0) {
            __nanosleep(2000);
            const unsigned int target = (ld_relaxed(&g_cnt[32 * 32]) & ~63u) + 64u;
            for (int i = 0; i < 8; ++i)
                for (int it = 0; ld_relaxed(&g_cnt[(40 + i) * 32]) != target && it < (1 << 12); ++it) __nanosleep(500);
        }
        return;
    }
    const int tt = bid >> 3, dt = bid & 7;
    const int ti = tt >> 1;
    const int cg = (dt >> 2) * 8 + (tt & 1) * 4 + (dt & 3);
    if (warp == 0) {
        if (lane == 0) {
            STAMP(1, 0);
#pragma unroll
            for (int s = 0; s < 4; ++s) mbar_init(bar_full + 8 * s, 1);
            asm volatile("fence.mbarrier_init.release.cluster;" ::: "memory");
        }
        __syncwarp();
        if (MERGED) {
#pragma unroll 1
            for (int it = 0; it < 4; ++it) {
                e_expect_tx(bar_full + 8 * it, 49152);
                e_load_4d(sbase + OFF_CU + it * 8192, &maps.b4, bar_full + 8 * it, it * 64, 0, 0, cg * 4);
                e_load_5d(sbase + it * 32768, &maps.x5, bar_full + 8 * it, it * 64, 0, 0, 0, ti);
                e_load_4d(sbase + OFF_BB + it * 8192, &maps.b4, bar_full + 8 * it, it * 64, 0, 0, 64 + cg * 4);
                if (it == 0) asm volatile("bar.arrive 4, 512;" ::: "memory");
            }
        }
        if (lane == 0) STAMP(1, 1);
    } else if (tid == 32) {
        if (sbase & 1023) __trap();
#pragma unroll
        for (int s = 0; s < 4; ++s) mbar_init(bar_empty + 8 * s, 2);
#pragma unroll
        for (int s = 0; s < NST; ++s) { mbar_init(bar_full2 + 8 * s, 1); mbar_init(bar_empty2 + 8 * s, 1); }
        mbar_init(bar_k, 1); mbar_init(bar_k + 8, 1); mbar_init(bar_k + 16, 1); mbar_init(bar_k + 24, 1);
        mbar_init(bar_tab, 1);
        mbar_init(bar_ab, 1);
        mbar_init(bar_adone, 4);
        mbar_init(bar_par, 2);
        asm volatile("fence.mbarrier_init.release.cluster;" ::: "memory");
    } else if (tid == 64) {
#pragma unroll
        for (int s = 0; s < 19; ++s) mbar_init(bar_y + 8 * s, 1);
    } else if (tid == 96) {
#pragma unroll
        for (int s = 0; s < 22; ++s) mbar_init(bar_stg + 8 * s, 4);
    } else if (tid == 128) {
        asm volatile("st.shared.b32 [%0], %1;" ::"r"(w_bid), "r"(bid) : "memory");
        SAMPLE(0);
    }
    if (MERGED) {
        if (warp == 0) asm volatile("bar.sync 5, 64;" ::: "memory");
        else {
            __syncwarp();
            asm volatile("bar.sync 4, 512;" ::: "memory");
            if (warp == 1) asm volatile("bar.arrive 5, 64;" ::: "memory");
        }
    } else {
        __syncthreads();
    }

    auto bias_half = [&](int b) {
        const int t = fresh_tid() & 127, lane = t & 31, w4 = t >> 5, g = lane >> 2, t4 = lane & 3;
        const int bid = lds32(w_bid), dt = bid & 7;
        const int trow = (bid >> 4) * 256 + 4 * (bid & 8) + 128 * (w4 & 1) + 16 * b + 8 * (w4 >> 1) + g;
        uint4 xv[8], xd[8];
        const __nv_bfloat16* xp = x + (size_t)trow * D_DIM + dt * 128 + 8 * t4;
#pragma unroll
        for (int i = 0; i < 8; ++i) {
            xv[i] = ldg128(xp + (size_t)(64 * (i >> 2)) * D_DIM + 32 * (i & 3));
            if (i & 1) __nanosleep(GAP_X);
        }
#pragma unroll
        for (int jq = 0; jq < 4; ++jq) {
            const uint4 dk = ldg128(dskip + dt * 128 + 32 * jq + 8 * t4);
#pragma unroll
            for (int c = 0; c < 8; ++c) (&xd[(c & 4) + jq].x)[c & 3] = hmul((&xv[(c & 4) + jq].x)[c & 3], (&dk.x)[c & 3]);
        }
        mbar_wait(bar_fh, 0);
        mbar_wait(bar_hw + 16, 0);
        uint32_t omg[2], g2[2];
#pragma unroll
        for (int h = 0; h < 2; ++h) {
            const float gt = __ldcg(g_gate + trow + 64 * h);
            if (t4 == 0) asm volatile("st.shared.f32 [%0], %1;" ::"r"(sbase + OFF_PAR + (64 * b + 16 * w4 + 8 * h + g) * 4), "f"(gt) : "memory");
            omg[h] = pack_bf16(2.f - 2.f * gt, 2.f - 2.f * gt); g2[h] = pack_bf16(gt, gt);
        }
        mbar_wait(bar_y, 0);
        if (t == 0) STAMP(0, 6 + 10 * b);
        uint32_t yw[8][4];
        const uint32_t ya = sbase + OFF_CT + (w4 & 1) * 16384 + lane * 128 + ((((2 * b + (w4 >> 1)) ^ ((bid >> 3 & 2) + (w4 & 1))) ^ (lane & 7)) << 4);
#pragma unroll
        for (int i = 0; i < 8; ++i) ldsm_x4_t(yw[i][0], yw[i][1], yw[i][2], yw[i][3], (ya ^ ((i & 4) << 4)) + (i & 3) * 4096);
        if (b == 0) asm volatile("bar.arrive 6, 256;" ::: "memory");
        else asm volatile("bar.sync 6, 256;" ::: "memory");
#pragma unroll
        for (int i = 0; i < 8; ++i) {
            uint32_t o[4];
#pragma unroll
            for (int c = 0; c < 4; ++c) o[c] = hfma(g2[i >> 2], (&xd[i].x)[c], hmul(omg[i >> 2], hmul((&xv[i].x)[c], yw[i][c])));
            sts128(sbase + (b ? OFF_CT : OFF_CU) + (i & 3) * 8192 + (w4 * 16 + g + (i & 4) * 2) * 128 + (((2 * t4) ^ g) << 4), o[0], o[1], o[2], o[3]);
        }
        __syncwarp();
        if (lane == 0) mbar_arrive(bar_bias + 8 * b);
        if (t == 0) STAMP(0, 7 + 10 * b);
    };

    if (wg == 0) {
        asm volatile("setmaxnreg.dec.sync.aligned.u32 %0;" ::"n"(REG_P));
        if (warp == 0) {
#pragma unroll 1
            for (int it = MERGED ? 4 : 0; it < 16; ++it) {
                const int st = it & 3;
                const uint32_t bf = bar_full + 8 * st;
                mbar_wait(bar_empty + 8 * st, ((it >> 2) & 1) ^ 1);
                e_expect_tx(bf, 49152);
                e_load_5d(sbase + st * 32768, &maps.x5, bf, it * 64, 0, 0, 0, ti);
                if (MERGED) {
                    e_load_4d(sbase + OFF_CU + st * 8192, &maps.b4, bf, it * 64, 0, 0, cg * 4);
                    e_load_4d(sbase + OFF_BB + st * 8192, &maps.b4, bf, it * 64, 0, 0, 64 + cg * 4);
                } else {
                    if (lane < 16)
                        tma_load_2d(sbase + ((lane & 8) ? OFF_BB : OFF_CU) + st * 8192 + (lane & 7) * 1024, (lane & 1) ? &maps.bim : &maps.bre, bf,
                                    it * 64, (lane >> 3) * 512 + cg * 32 + ((lane & 7) >> 1) * 8);
                    __syncwarp();
                }
                if (it >= 4) e_arrive(bar_tick + 8 * (it - 3));
                if (lane == 0) STAMP(1, 16 + it);
                if (lane == 0) SAMPLE(it - 3);
            }
            int st = 0;
            uint32_t ph = 0;
#pragma unroll 1
            for (int kb = 0; kb < 32; ++kb) {
                const uint32_t bf = bar_full2 + 8 * st;
                mbar_wait(bar_empty2 + 8 * st, st == 4 ? ph ^ PH4 : ph);
                e_expect_tx(bf, 32768);
                e_load_5d(sbase + st * 32768 + 16384, &maps.cre + ((kb >> 3) & 1), bf, ((kb >> 4) * 8 + (kb & 7)) * 64, 0, 0, 0, dt * 4);
                if (lane == 0) STAMP(2, 16 + kb);
                if (lane == 0 && (kb & 3) == 0) SAMPLE(13 + (kb >> 2));
                if (++st == (kb < SLOT4 - 1 ? 4 : 5)) { st = 0; ph ^= 1; }
            }
        } else if (warp == 1) {
            mbar_wait(bar_full, 0);
            e_arrive(bar_tick);
            if (MERGED && PFD && lane == 0) {
#pragma unroll 1
                for (int n = 0; n + PFD < 16; ++n) {
                    mbar_wait(bar_tick + 8 * n, 0);
                    if (cg >= 4 && max(cg - PFD, 0) == n) l2_prefetch_5d(&maps.x5, cg * 64, 0, 0, 0, ti);
                    if (ti >= 2 && max(2 * ti - PFD, 0) == n) {
#pragma unroll 1
                        for (int i = 0; i < 4; ++i) l2_prefetch_4d(&maps.b4, (2 * ti + (i >> 1)) * 64, 0, 0, (i & 1) * 64 + cg * 4);
                    }
                }
            }
            __syncwarp();
            const unsigned int target = (ld_relaxed(&g_cnt[(4 * ti) * 32]) & ~63u) + 64u;
            const char* hp = reinterpret_cast<const char*>(g_H) + (size_t)tt * 262144;
            mbar_wait(bar_rel, 0);
            int st = 0;
            uint32_t ph = 0;
#pragma unroll 1
            for (int q = 0; q < 4; ++q) {
                if (lane == 0) STAMP(0, 8 + 2 * q);
                if (q == 0) wait_counter(&g_cnt[(4 * ti) * 32], target);
                else { mbar_wait(bar_fh + 8 * q - 8, 0); fence_async_global(); }
                if (lane == 0) STAMP(0, 9 + 2 * q);
#pragma unroll 1
                for (int kb = 0; kb < 8; ++kb) {
                    mbar_wait(bar_empty2 + 8 * st, st == 4 ? ph ^ PH4 : ph);
                    e_bulk_load(sbase + st * 32768, hp + kb * 16384, 16384, bar_full2 + 8 * st);
                    if (++st == (8 * q + kb < SLOT4 - 1 ? 4 : 5)) { st = 0; ph ^= 1; }
                }
                hp += (q & 1) ? 4194304 - 131072 : 131072;
            }
        } else if (warp == 2) {
            if (lane == 0) {
                mbar_wait(bar_tick + 8, 0);
                const unsigned int target = (ld_relaxed(&g_cnt[(40 + dt) * 32]) & ~63u) + 64u;
                prefetch_map(&maps.kvst); prefetch_map(&maps.sk);
#pragma unroll 1
                for (int bt = 0; bt < 2; ++bt) {
                    mbar_wait(bar_stg + 8 * bt, 0);
#pragma unroll 1
                    for (int i = 0; i < 4; ++i) {
                        if (i) __nanosleep(GAP_ST);
                        tma_store_3d(&maps.kvst, sbase + OFF_CT + bt * 16384 + i * 4096, (tt & 1) * 1024 + ti * 128 + 64 * bt, dt * 16, 2 * i);
                    }
                    bulk_commit();
                }
                bulk_wait0();
                fence_async_global();
                red_release(&g_cnt[(40 + dt) * 32], 4);
                mbar_arrive(bar_kvrel);
                STAMP(0, 23);
                mbar_expect_tx(bar_tab, 16384);
                bulk_load(sbase + OFF_CT, &g_conv_tab, 16384, bar_tab);
                mbar_expect_tx(bar_k, 16384);
                tma_load_4d(sbase + conv_buf(0) + 8192, &maps.sk, bar_k, 0, 0, 0, bid * 8);
                tma_load_4d(sbase + conv_buf(0) + 12288, &maps.sk, bar_k, 0, 0, 0, bid * 8 + 1);
                wait_counter(&g_cnt[(40 + (bid >> 4)) * 32], target);
                STAMP(0, 19);
                bulk_load(sbase + conv_buf(0), g_kvT + (size_t)bid * 16384, 8192, bar_k);
                mbar_wait(bar_adone, 0);
                mbar_expect_tx(bar_k + 8, 16384);
                mbar_expect_tx(bar_k + 16, 16384);
#pragma unroll 1
                for (int c = 2; c < 6; ++c) {
                    const uint32_t u = sbase + conv_buf(0) + (c >> 1) * 16384 + (c & 1) * 4096;
                    __nanosleep(GAP_CV);
                    bulk_load(u, g_kvT + (size_t)(bid * 8 + c) * 2048, 4096, bar_k + 8 * (c >> 1));
                    __nanosleep(GAP_CV);
                    tma_load_4d(u + 8192, &maps.sk, bar_k + 8 * (c >> 1), 0, 0, 0, bid * 8 + c);
                }
                prefetch_map(&maps.out); prefetch_map(&maps.yt);
#pragma unroll 1
                for (int p = 0; p < 4; ++p) {
                    mbar_wait(bar_stg + 16 + 8 * p, 0);
                    if (p == 0) {
                        mbar_expect_tx(bar_k + 24, 16384);
                        tma_load_4d(sbase + conv_buf(3) + 8192, &maps.sk, bar_k + 24, 0, 0, 0, bid * 8 + 6);
                        mbar_wait(bar_g2, 0);
                        tma_load_4d(sbase + conv_buf(3) + 12288, &maps.sk, bar_k + 24, 0, 0, 0, bid * 8 + 7);
                    }
#pragma unroll 1
                    for (int i = 0; i < 2; ++i) {
                        if (i) __nanosleep(GAP_Y);
                        asm volatile("cp.async.bulk.global.shared::cta.bulk_group [%0], [%1], 4096;"
                                     ::"l"(g_y2 + (size_t)(bid * 8 + 2 * p + i) * 2048), "r"(sbase + conv_buf(p) + i * 4096) : "memory");
                    }
                    bulk_commit();
                    STAMP(0, 24 + p);
                    if (p == 0) {
                        bulk_wait_read0();
                        bulk_load(sbase + conv_buf(3), g_kvT + (size_t)(bid * 8 + 6) * 2048, 8192, bar_k + 24);
                    }
                }
                bulk_wait0();
                fence_async_global();
                red_release(&g_cnt[(32 + (bid >> 4)) * 32], 4);
                STAMP(0, 2);
                wait_counter(&g_cnt[(32 + dt) * 32], target);
                STAMP(0, 5);
                mbar_expect_tx(bar_y, 32768);
#pragma unroll 1
                for (int i = 0; i < 4; ++i) {
                    if (i) __nanosleep(GAP_Y);
                    tma_load_5d(sbase + OFF_CT + i * 8192, &maps.yt, bar_y, (tt & 1) * 1024 + ti * 128 + (i >> 1) * 64, 0, 0, 0, dt * 4 + (i & 1) * 2);
                }
#pragma unroll 1
                for (int i = 0; i < 8; ++i) {
                    mbar_wait(bar_stg + 48 + 8 * i, 0);
                    tma_store_5d(&maps.out, sbase + ((i & 4) ? OFF_CT : OFF_CU) + (i & 3) * 8192, dt * 128 + (i & 3) * 32, 0, 0, (tt & 1) * 4 + ((i & 4) >> 1), ti);
                    bulk_commit();
                }
                bulk_wait_read0();
                STAMP(2, 3);
                SAMPLE(21);
            }
        } else if (lane == 0) {
            mbar_wait(bar_tick + 8 * TK_PF0, 0);
#pragma unroll 1
            for (int i = 0; i < 8; ++i) {
                l2_prefetch(((i & 1) ? vin : kin) + (size_t)(ti * 256 + 32 * (i & 4) + (bid & 15) * 8 + 2 * (i & 2)) * D_DIM, 8192);
                __nanosleep(GAP_PF);
            }
            if (bid < 2) l2_prefetch(reinterpret_cast<const char*>(&g_conv_tab) + bid * 8192, 8192);
            prefetch_map(&maps.cre); prefetch_map(&maps.cim);
            mbar_wait(bar_tick + 8 * TK_C, 0);
#pragma unroll 1
            for (int i = 0; i < 8; ++i) {
                l2_prefetch((i & 1) ? ((i & 4) ? c_im : c_re) + (size_t)bid * 8192 + (i & 2) * 2048 : ssm_k + (size_t)bid * 16384 + (i >> 1) * 4096, 8192);
                __nanosleep(GAP_PF);
            }
            const unsigned int target = (ld_relaxed(&g_cnt[(4 * ti + 1) * 32]) & ~63u) + 64u;
            mbar_wait(bar_gate, 0);
#pragma unroll 1
            for (int q = 1; q < 4; ++q) {
                if (q < 3) mbar_wait(bar_hw + 8 * q, 0);
                if (q > 1) {
                    mbar_wait(bar_g2, 0);
                    char* hp = reinterpret_cast<char*>(g_H) + (size_t)((16 + 2 * ti) * 16 + (q & 1) * 8 + (cg >> 1)) * 16384 + (cg & 1) * 2048;
#pragma unroll 1
                    for (int i = 0; i < 8; ++i) {
                        asm volatile("cp.async.bulk.global.shared::cta.bulk_group [%0], [%1], 2048;"
                                     ::"l"(hp + (i & 3) * 4096 + (i >> 2) * 262144), "r"(sbase + OFF_BB + (q & 1) * 16384 + i * 2048) : "memory");
                        __nanosleep(GAP_HB);
                    }
                    bulk_commit();
                    bulk_wait0();
                    if (q == 3) mbar_arrive(bar_empty2 + 32);
                    fence_async_global();
                }
                red_release(&g_cnt[(4 * ti + q) * 32], 4);
                STAMP(0, 36 + q);
                wait_counter(&g_cnt[(4 * ti + q) * 32], target);
                mbar_arrive(bar_fh + 8 * q - 8);
            }
        }
    } else if (wg == 3) {
        asm volatile("setmaxnreg.inc.sync.aligned.u32 %0;" ::"n"(REG_C));
        const int t = tid & 127, w4 = t >> 5;
        mbar_wait(bar_tick, 0);
        if (t < 64) {
            const int ch = (t >> 5) * 512 + cg * 32 + (t & 31);
            unsigned long long oldagg;
            asm volatile("ld.relaxed.gpu.global.u64 %0, [%1];" : "=l"(oldagg) : "l"(&g_agg[ti * D_DIM + ch]) : "memory");
            const float Lr = __bfloat162float(lam_re[ch]), Li = __bfloat162float(lam_im[ch]);
            const float dtv = bf16r(expf(__bfloat162float(log_dt[ch])));
            const unsigned int tag = ((((unsigned int)oldagg & 1u) | ((unsigned int)(oldagg >> 31) & 2u)) + 1u) & 3u;
            const float er = expf(dtv * Lr);
            float s, c;
            sincosf(dtv * Li, &s, &c);
            const float lr = er * c, li = er * s;
            const float nr = lr - 1.f, ni = li;
            const float den = Lr * Lr + Li * Li;
            const float cr = 2.f * (nr * Lr + ni * Li) / den, ci = 2.f * (ni * Lr - nr * Li) / den;
            float pr = lr, pi = -li;
#pragma unroll
            for (int i = 0; i < 5; ++i) csqr(pr, pi);
            sts128(sbase + OFF_PAR + t * 32, __float_as_uint(lr), __float_as_uint(-li), __float_as_uint(cr), __float_as_uint(ci));
            sts128(sbase + OFF_PAR + t * 32 + 16, __float_as_uint(pr), __float_as_uint(pi), tag, 0);
            __syncwarp();
            if (lane == 0) mbar_arrive(bar_par);
        }
        if (t >= 120) asm volatile("st.shared.b32 [%0], %1;" ::"r"(w_dsk - 480 + 4 * t),
                                   "r"(t < 124 ? __ldg(reinterpret_cast<const uint32_t*>(ssm_D + bid * 8) + (t & 3)) : 0u) : "memory");
        if (t < 64) asm volatile("st.shared.b32 [%0], %1;" ::"r"(w_ones + 4 * t), "r"(0x3F803F80u) : "memory");
        {
            const int cq = lane & 15, rg = (lane >> 4) + 2 * w4;
            uint32_t sk[4][4];
#pragma unroll
            for (int c = 0; c < 4; ++c) {
                const uint4 w = ldg128(shift_k + (size_t)(dt * 128 + 8 * cq + 2 * c) * 4);
                sk[0][c] = __byte_perm(w.x, w.z, 0x5410); sk[1][c] = __byte_perm(w.x, w.z, 0x7632);
                sk[2][c] = __byte_perm(w.y, w.w, 0x5410); sk[3][c] = __byte_perm(w.y, w.w, 0x7632);
            }
#pragma unroll 1
            for (int bt = 0; bt < 2; ++bt) {
                const int t0 = ti * 256 + 128 * bt + 16 * (rg & 4) + 32 * (tt & 1) + 8 * (rg & 3);
                mbar_wait(bar_tick + 8 * (bt ? TK_KV1 : TK_KV0), 0);
                if (t == 0) STAMP(0, 30 + 3 * bt);
                uint4 kk[11], vv[8];
                const __nv_bfloat16* kp = kin + (size_t)t0 * D_DIM + dt * 128 + 8 * cq;
                const __nv_bfloat16* vp = vin + (size_t)t0 * D_DIM + dt * 128 + 8 * cq;
#pragma unroll
                for (int i = 0; i < 11; ++i) {
                    if (i < 3 && t0 == 0) kk[i] = make_uint4(0, 0, 0, 0);
                    else kk[i] = ldg128(kp + (i - 3) * D_DIM);
                    if (GAP_KV && (i == 6 || i == 10)) __nanosleep(GAP_KV);
                }
#pragma unroll
                for (int i = 0; i < 8; ++i) { vv[i] = ldg128(vp + i * D_DIM); if (GAP_KV && i == 3) __nanosleep(GAP_KV); }
                const uint32_t ua = sbase + OFF_CT + bt * 16384 + cq * 128 + ((rg ^ ((2 * ti + bt) & 3) ^ (cq & 7)) << 4);
#pragma unroll
                for (int c = 0; c < 4; ++c) {
                    uint32_t res[8];
#pragma unroll
                    for (int i = 0; i < 8; ++i) {
                        uint32_t ks = hmul((&kk[i].x)[c], sk[3][c]);
                        if (KVFMA) {
                            ks = hfma((&kk[i + 1].x)[c], sk[2][c], ks);
                            ks = hfma((&kk[i + 2].x)[c], sk[1][c], ks);
                            ks = hfma((&kk[i + 3].x)[c], sk[0][c], ks);
                        } else {
                            ks = hadd(ks, hmul((&kk[i + 1].x)[c], sk[2][c]));
                            ks = hadd(ks, hmul((&kk[i + 2].x)[c], sk[1][c]));
                            ks = hadd(ks, hmul((&kk[i + 3].x)[c], sk[0][c]));
                        }
                        res[i] = hmul(ks, (&vv[i].x)[c]);
                    }
                    sts128(ua + (2 * c) * 2048, __byte_perm(res[0], res[1], 0x5410), __byte_perm(res[2], res[3], 0x5410),
                           __byte_perm(res[4], res[5], 0x5410), __byte_perm(res[6], res[7], 0x5410));
                    sts128(ua + (2 * c + 1) * 2048, __byte_perm(res[0], res[1], 0x7632), __byte_perm(res[2], res[3], 0x7632),
                           __byte_perm(res[4], res[5], 0x7632), __byte_perm(res[6], res[7], 0x7632));
                }
                fence_async_smem();
                __syncwarp();
                if (lane == 0) mbar_arrive(bar_stg + 8 * bt);
                if (t == 0) STAMP(0, 21 + bt);
            }
        }
        {
            const int row = bid * 16 + (t >> 3);
            if (GWAIT) mbar_wait(bar_kvrel, 0);
            uint4 xv[16];
#pragma unroll
            for (int n = 0; n < 16; ++n) {
                xv[n] = ldg128(x + (size_t)row * D_DIM + ((t & 7) + 8 * n) * 8);
                if (GAP_KV && (n & 3) == 3) __nanosleep(GAP_KV);
            }
#pragma unroll
            for (int n8 = 0; n8 < 16; n8 += 8) {
                uint4 wv[8];
#pragma unroll
                for (int n = 0; n < 8; ++n) wv[n] = ldg128(gate_w + ((t & 7) + 8 * (n8 + n)) * 8);
#pragma unroll
                for (int n = 0; n < 8; ++n) {
                    uint4& p = xv[n8 + n];
                    p.x = hmul(p.x, wv[n].x); p.y = hmul(p.y, wv[n].y); p.z = hmul(p.z, wv[n].z); p.w = hmul(p.w, wv[n].w);
                }
            }
            float d[4] = {0.f, 0.f, 0.f, 0.f};
            fence_regs(d);
            named_bar(3, 128);
            wgmma_fence();
#pragma unroll
            for (int n = 0; n < 16; ++n)
                asm volatile("{\n.reg .b64 db;\nmov.b64 db, {%8, 8};\n"
                             "wgmma.mma_async.sync.aligned.m64n8k16.f32.bf16.bf16 {%0, %1, %2, %3}, {%4, %5, %6, %7}, db, 1, 1, 1, 0;\n}\n"
                             : "+f"(d[0]), "+f"(d[1]), "+f"(d[2]), "+f"(d[3]) : "r"(xv[n].x), "r"(xv[n].y), "r"(xv[n].z), "r"(xv[n].w), "r"(desc_lo(w_ones, 128)));
            wgmma_commit();
            wgmma_wait<0>();
            fence_regs(d);
#pragma unroll
            for (int n = 0; n < 16; ++n) asm volatile("" ::"r"(xv[n].x), "r"(xv[n].y), "r"(xv[n].z), "r"(xv[n].w) : "memory");
            float sum = d[0] + d[2];
            sum += __shfl_xor_sync(0xffffffffu, sum, 4);
            if ((t & 7) == 0) g_gate[row] = bf16r(1.f / (1.f + expf(-bf16r(sum))));
            if (t == 0) STAMP(0, 4);
            __syncwarp();
            if (lane == 0) mbar_arrive(bar_gate);
        }
        Twiddle tw;
        load_twiddle(tw, reinterpret_cast<const uint4*>(g_tw_tab.w) + t);
        const uint32_t lo = (uint32_t)((16 * w4 + (lane & 7)) * 64 + (((lane >> 3) ^ ((lane >> 1) & 3)) << 4));
        const uint32_t tlo = desc_lo(sbase + OFF_CT, 16);
        float dE[32], dO[32];
        mbar_wait(bar_tab, 0);
        mbar_wait(bar_k, 0);
        if (CWAIT) mbar_wait(bar_ascan, 0);
        if (t == 0) STAMP(0, 1);
        wgmma_fence();
        conv_s1(dE, dO, tlo, desc_lo(sbase + conv_buf(0), 8192));
        wgmma_commit();
        wgmma_wait<0>();
        fence_regs(dE); fence_regs(dO);
        named_bar(3, 128);
#pragma unroll 1
        for (int p = 0; p < 4; p = 2 * p + 1) {
            const int pn = min(2 * p + 1, 3);
            if (t == 0) STAMP(0, 40 + 5 * p);
            conv_pair<true>(dE, dO, tw, lds32(w_dsk + ((lane & 3) ? 16 : 4 * p)), tlo, sbase + conv_buf(0) + (p == 1 ? 16384 : 0),
                            sbase + conv_buf(0) + (p == 0 ? 16384 : 0), lo, 3,
                            [&]() { if (t == 0) STAMP(0, 42 + 5 * p); mbar_wait(bar_k + 8 * pn, 0); if (t == 0) STAMP(0, 43 + 5 * p); });
            if (lane == 0) mbar_arrive(bar_stg + 16 + 8 * p);
        }
        bias_half(0);
    } else {
        asm volatile("setmaxnreg.inc.sync.aligned.u32 %0;" ::"n"(REG_AB));
        const int cw = wg - 1;
        const int t = tid & 127, w4 = t >> 5, g = lane >> 2, t4 = lane & 3;
        {
            float a0[64], a1[64];
#pragma unroll 1
            for (int kb = 0; kb < 16; ++kb) {
                const int st = kb & 3;
                if (cw == 1 && kb == 16 - SKEW1) mbar_wait(bar_ab, 0);
                mbar_wait(bar_full + 8 * st, (kb >> 2) & 1);
                if (kb == 0 && t == 0) STAMP(1, 14 + cw);
                const uint32_t alo = desc_lo(sbase + (cw ? OFF_BB : OFF_CU) + st * 8192, 16), blo = desc_lo(sbase + st * 32768, 16);
                wgmma_fence();
#pragma unroll
                for (int k = 0; k < 4; ++k) {
                    wgmma_n128<0>(a0, alo + 2 * k, blo + 2 * k, k ? 1 : kb);
                    wgmma_n128<0>(a1, alo + 2 * k, blo + 1024 + 2 * k, k ? 1 : kb);
                }
                wgmma_commit();
                if (cw == 1 && kb == 15 - SKEW1) {
                    wgmma_wait<0>();
                    if (t < 2) mbar_arrive(bar_empty + 8 * ((kb - t) & 3));
                } else {
                    wgmma_wait<1>();
                    if (kb > 0 && kb <= 12 && t == 0 && !(cw == 1 && kb == 16 - SKEW1)) mbar_arrive(bar_empty + 8 * ((kb - 1) & 3));
                }
                if (cw == 1 && kb > 12) {
                    if (kb == 13) mbar_wait(bar_adone, 0);
                    if (t == 0) mbar_arrive(bar_empty2 + 8 * (kb - 13));
                }
            }
            if (tid == 192) mbar_arrive(bar_ab);
            float mr, mi, cr, ci, p32r, p32i;
            uint32_t tag;
            mbar_wait(bar_par, 0);
            {
                const uint32_t par = sbase + OFF_PAR + (cw * 32 + w4 * 8 + g) * 32;
                uint32_t dummy;
                asm volatile("ld.shared.v4.f32 {%0,%1,%2,%3}, [%4];" : "=f"(mr), "=f"(mi), "=f"(cr), "=f"(ci) : "r"(par));
                asm volatile("ld.shared.v4.b32 {%0,%1,%2,%3}, [%4];" : "=f"(p32r), "=f"(p32i), "=r"(tag), "=r"(dummy) : "r"(par + 16));
            }
            const float l1i = SW ? mi : -mi;
            auto map = [&](float p, float q, float& r, float& i) {
                if (SW) { r = fmaf(cr, q, -ci * p); i = fmaf(-cr, p, -ci * q); }
                else { r = fmaf(cr, p, -ci * q); i = fmaf(-cr, q, -ci * p); }
            };
            float p64r = p32r, p64i = p32i;
            csqr(p64r, p64i);
            float p128r = p64r, p128i = p64i;
            csqr(p128r, p128i);
            wgmma_wait<0>();
            fence_regs(a0); fence_regs(a1);
            if (cw == 0) { if (lane == 0) mbar_arrive(bar_adone); }
            else if (t == 0) mbar_arrive(bar_empty2 + 24);
            if (t == 0) STAMP(1, 2 + 6 * cw);
            float hr = 0.f, hi = 0.f, ar = 0.f, ai = 0.f;
#pragma unroll
            for (int j = 0; j < 16; ++j)
#pragma unroll
                for (int e = 0; e < 2; ++e) {
                    const float nr = fmaf(mr, ar, fmaf(-l1i, ai, a0[4 * j + e])), ni = fmaf(mr, ai, fmaf(l1i, ar, a0[4 * j + 2 + e]));
                    const float or_ = fmaf(mr, hr, fmaf(-l1i, hi, a1[4 * j + e])), oi = fmaf(mr, hi, fmaf(l1i, hr, a1[2 + 4 * j + e]));
                    ar = nr; ai = ni; hr = or_; hi = oi;
                }
            map(ar, ai, ar, ai);
            map(hr, hi, hr, hi);
            hr += p32r * ar - p32i * ai; hi += p32r * ai + p32i * ar;
            {
                float vr = __shfl_up_sync(0xffffffffu, hr, 1, 4), vi = __shfl_up_sync(0xffffffffu, hi, 1, 4);
                if (t4 >= 1) { hr += p64r * vr - p64i * vi; hi += p64r * vi + p64i * vr; }
                vr = __shfl_up_sync(0xffffffffu, hr, 2, 4); vi = __shfl_up_sync(0xffffffffu, hi, 2, 4);
                if (t4 >= 2) { hr += p128r * vr - p128i * vi; hi += p128r * vi + p128i * vr; }
            }
            unsigned long long* ap = &g_agg[ti * D_DIM + cw * 512 + cg * 32 + w4 * 8 + g];
            if (t4 == 3) asm volatile("{\n.reg .b64 a;\nmov.b64 a, {%1, %2};\nst.relaxed.gpu.global.u64 [%0], a;\n}\n" ::"l"(ap),
                                      "r"((__float_as_uint(hr) & ~1u) | (tag & 1u)), "r"((__float_as_uint(hi) & ~1u) | (tag >> 1)) : "memory");
            float exr = __shfl_up_sync(0xffffffffu, hr, 1, 4), exi = __shfl_up_sync(0xffffffffu, hi, 1, 4);
            if (t4 == 0) { exr = 0.f; exi = 0.f; }
            if (t == 0) STAMP(1, 3 + 6 * cw);
            ci = after(ci, exr);
#pragma unroll
            for (int j = 0; j < 16; ++j)
#pragma unroll
                for (int e = 0; e < 2; ++e) {
                    map(a0[4 * j + e], a0[4 * j + 2 + e], a0[4 * j + e], a0[4 * j + 2 + e]);
                    map(a1[4 * j + e], a1[4 * j + 2 + e], a1[4 * j + e], a1[4 * j + 2 + e]);
                }
            float qr = 1.f, qi = 0.f, ur = 1.f, ui = 0.f;
            if (t4 & 1) { qr = p64r; qi = p64i; }
            if (t4 & 2) cmul(qr, qi, qr, qi, p128r, p128i);
            csqr(p128r, p128i);
            if (t4 & 1) { ur = p128r; ui = p128i; }
            csqr(p128r, p128i);
            if (t4 & 2) cmul(ur, ui, ur, ui, p128r, p128i);
            csqr(p128r, p128i);
            fence_regs(a0); fence_regs(a1);
            if (t == 0) STAMP(1, 7 + 6 * cw);
            if (ti > 0) {
                const unsigned long long tmask = 0x0000000100000001ull, tval = ((unsigned long long)(tag >> 1) << 32) | (tag & 1u);
                unsigned long long u0 = tval, u1 = tval;
                ap -= D_DIM * (1 + t4);
                int it = 0;
                do {
                    asm volatile("{\n.reg .pred p, q;\nsetp.gt.s32 p, %3, 0;\nsetp.gt.s32 q, %3, 4;\n@p ld.relaxed.gpu.global.u64 %0, [%2];\n"
                                 "@q ld.relaxed.gpu.global.u64 %1, [%2+-32768];\n}\n" : "+l"(u0), "+l"(u1) : "l"(ap), "r"(ti - t4) : "memory");
                } while (__any_sync(0xffffffffu, (((u0 ^ tval) | (u1 ^ tval)) & tmask) != 0) && ++it < (1 << 22));
                float Pr = __uint_as_float((unsigned)u1 & ~1u), Pi = __uint_as_float((unsigned)(u1 >> 32) & ~1u);
                cmul(Pr, Pi, Pr, Pi, p128r, p128i);
                Pr += __uint_as_float((unsigned)u0 & ~1u); Pi += __uint_as_float((unsigned)(u0 >> 32) & ~1u);
                cmul(Pr, Pi, Pr, Pi, ur, ui);
                Pr += __shfl_xor_sync(0xffffffffu, Pr, 1); Pi += __shfl_xor_sync(0xffffffffu, Pi, 1);
                Pr += __shfl_xor_sync(0xffffffffu, Pr, 2); Pi += __shfl_xor_sync(0xffffffffu, Pi, 2);
                exr += qr * Pr - qi * Pi;
                exi += qr * Pi + qi * Pr;
            }
            if (t == 0) STAMP(1, 4 + 6 * cw);
            char* hp = reinterpret_cast<char*>(g_H) + (size_t)((2 * ti) * 16 + (cg >> 1)) * 16384 + ((cg & 1) * 32 + w4 * 8 + g) * 64 + ((t4 ^ (g >> 1)) << 4);
            float fxr = ar + p32r * exr - p32i * exi, fxi = ai + p32r * exi + p32i * exr;
            const uint32_t hs = sbase + OFF_BB + (w4 * 8 + g) * 64 + ((t4 ^ (g >> 1)) << 4);
            if (cw == 1) named_bar(2, 128);
            uint32_t im[32];
#pragma unroll
            for (int jj = 0; jj < 4; ++jj) {
                uint32_t pr[4], qq[4];
#pragma unroll
                for (int j4 = 0; j4 < 4; ++j4) {
                    const int j = jj * 4 + j4;
                    const float r0 = fmaf(mr, exr, fmaf(-mi, exi, a0[4 * j])), i0 = fmaf(mr, exi, fmaf(mi, exr, a0[4 * j + 2]));
                    const float r1 = fmaf(mr, fxr, fmaf(-mi, fxi, a1[4 * j])), i1 = fmaf(mr, fxi, fmaf(mi, fxr, a1[2 + 4 * j]));
                    exr = fmaf(mr, r0, fmaf(-mi, i0, a0[4 * j + 1]));
                    exi = fmaf(mr, i0, fmaf(mi, r0, a0[4 * j + 3]));
                    fxr = fmaf(mr, r1, fmaf(-mi, i1, a1[1 + 4 * j]));
                    fxi = fmaf(mr, i1, fmaf(mi, r1, a1[3 + 4 * j]));
                    pr[j4] = pack_bf16(r0, exr); im[j] = pack_bf16(i0, exi);
                    qq[j4] = pack_bf16(r1, fxr); im[16 + j] = pack_bf16(i1, fxi);
                }
                if (cw == 0) {
                    stg128(hp + jj * 4096, pr[0], pr[1], pr[2], pr[3]);
                    stg128(hp + jj * 4096 + 262144, qq[0], qq[1], qq[2], qq[3]);
                } else {
                    sts128(hs + jj * 2048, pr[0], pr[1], pr[2], pr[3]);
                    sts128(hs + jj * 2048 + 8192, qq[0], qq[1], qq[2], qq[3]);
                }
            }
            if (t == 0) STAMP(1, 5 + 6 * cw);
            if (cw == 0) {
                if (lane == 0) mbar_arrive(bar_ascan);
                named_bar(1, 128);
                if (t == 0) { red_release(&g_cnt[(4 * ti) * 32], 4); mbar_arrive(bar_rel); }
                named_bar(1, 128);
                if (t == 0) STAMP(1, 6);
#pragma unroll
                for (int jj = 0; jj < 8; ++jj) stg128(hp + 131072 + (jj & 3) * 4096 + (jj >> 2) * 262144, im[4 * jj], im[4 * jj + 1], im[4 * jj + 2], im[4 * jj + 3]);
            } else {
#pragma unroll
                for (int jj = 0; jj < 8; ++jj) sts128(hs + 16384 + jj * 2048, im[4 * jj], im[4 * jj + 1], im[4 * jj + 2], im[4 * jj + 3]);
                fence_async_smem();
            }
            __syncwarp();
            if (lane == 0) mbar_arrive(bar_hw + 8 * cw + 8);
            if (t == 0) STAMP(1, 32 + cw);
        }
        if (cw == 1) {
            const int t = fresh_tid() & 127, lane = t & 31, w4 = t >> 5;
            Twiddle tw;
            load_twiddle(tw, reinterpret_cast<const uint4*>(g_tw_tab.w) + t);
            const uint32_t lo = (uint32_t)((16 * w4 + (lane & 7)) * 64 + (((lane >> 3) ^ ((lane >> 1) & 3)) << 4));
            const uint32_t tlo = desc_lo(sbase + OFF_CT, 16);
            float dE[32], dO[32];
            mbar_wait(bar_stg, 0);
            mbar_wait(bar_tab, 0);
            mbar_wait(bar_k + 16, 0);
            if (t == 0) STAMP(0, 50);
            wgmma_fence();
            conv_s1(dE, dO, tlo, desc_lo(sbase + conv_buf(2), 8192));
            wgmma_commit();
            wgmma_wait<0>();
            fence_regs(dE); fence_regs(dO);
            named_bar(2, 128);
            conv_pair<false>(dE, dO, tw, lds32(w_dsk + ((lane & 3) ? 16 : 8)), tlo, sbase + conv_buf(2), 0, lo, 2, []() {});
            if (lane == 0) mbar_arrive(bar_stg + 32);
            bias_half(1);
        }
        if (cw == 0) {
            float c0[64], c1[64];
            int st = 0, pst = 0;
            uint32_t ph = 0;
#pragma unroll 1
            for (int kb = 0; kb < 32 - SKEW2; ++kb) {
                const int t = fresh_tid() & 127, lane = t & 31;
                mbar_wait(bar_full2 + 8 * st, st == 4 ? ph ^ PH4 : ph);
                if (kb == 0 && t == 0) STAMP(2, 6);
                if (kb == G2SIG && lane == 0) mbar_arrive(bar_g2);
                const uint32_t alo = desc_lo(sbase + st * 32768, 4096), blo = desc_lo(sbase + st * 32768 + 16384, 16);
                wgmma_fence();
#pragma unroll
                for (int k = 0; k < 4; ++k) {
                    wgmma_n128<1>(c0, alo + 64 * k, blo + 2 * k, k ? 1 : kb);
                    wgmma_n128<1>(c1, alo + 512 + 64 * k, blo + 2 * k, k ? 1 : kb);
                }
                wgmma_commit();
                wgmma_wait<1>();
                if (kb > 0 && t == 0) mbar_arrive(bar_empty2 + 8 * pst);
                pst = st;
                if (++st == (kb < SLOT4 - 1 ? 4 : 5)) { st = 0; ph ^= 1; }
            }
            static_assert(SKEW2 <= 4, "slot release");
            const uint32_t alo = desc_lo(sbase, 4096), blo = desc_lo(sbase + 16384, 16);
#pragma unroll
            for (int kb = 32 - SKEW2; kb < 32; ++kb) {
                mbar_wait(bar_full2 + 8 * ring_slot(kb), ring_par(kb));
                wgmma_fence();
#pragma unroll
                for (int k = 0; k < 4; ++k) wgmma_n128<1>(c0, alo + ring_slot(kb) * 2048 + 64 * k, blo + ring_slot(kb) * 2048 + 2 * k, 1);
                wgmma_commit();
            }
            auto late = [&](int kb) {
                wgmma_fence();
#pragma unroll
                for (int k = 0; k < 4; ++k) wgmma_n128<1>(c1, alo + 512 + ring_slot(kb) * 2048 + 64 * k, blo + ring_slot(kb) * 2048 + 2 * k, 1);
                wgmma_commit();
            };
            late(32 - SKEW2);
            const int t = fresh_tid() & 127, lane = t & 31, w4 = t >> 5, g = lane >> 2, t4 = lane & 3;
            auto epilogue = [&](const float (&a)[64], int b) {
                const uint32_t ad0 = sbase + (b ? OFF_CT : OFF_CU) + (w4 * 16 + g) * 128 + (((2 * t4) ^ g) << 4);
                float gt[2];
                uint32_t bv[4][4];
#pragma unroll
                for (int h = 0; h < 2; ++h) gt[h] = __uint_as_float(lds32(sbase + OFF_PAR + (64 * b + 16 * w4 + 8 * h + g) * 4));
#pragma unroll
                for (int i = 0; i < 4; ++i)
                    asm volatile("ld.shared.v4.b32 {%0,%1,%2,%3}, [%4];" : "=r"(bv[i][0]), "=r"(bv[i][1]), "=r"(bv[i][2]), "=r"(bv[i][3])
                                 : "r"(ad0 + (i & 1) * 1024 + (i >> 1) * 8192) : "memory");
                if (b == 0) wgmma_wait<1>(); else wgmma_wait<0>();
                if (b == 0) fence_regs(c0); else fence_regs(c1);
                if (t == 0) STAMP(2, b ? 2 : 5);
#pragma unroll
                for (int jq = 0; jq < 4; ++jq) {
                    if (b == 0 && jq < SKEW2 - 1) late(33 - SKEW2 + jq);
#pragma unroll
                    for (int h = 0; h < 2; ++h) {
                        const uint32_t ad = ad0 + h * 1024 + jq * 8192;
                        uint32_t (&w)[4] = bv[2 * (jq & 1) + h];
                        const int r = 16 * jq + 2 * h;
                        sts128(ad, __float_as_uint(fmaf(gt[h], a[r], bf_lo(w[0]))), __float_as_uint(fmaf(gt[h], a[r + 1], bf_hi(w[0]))),
                               __float_as_uint(fmaf(gt[h], a[r + 4], bf_lo(w[1]))), __float_as_uint(fmaf(gt[h], a[r + 5], bf_hi(w[1]))));
                        sts128(ad ^ 16, __float_as_uint(fmaf(gt[h], a[r + 8], bf_lo(w[2]))), __float_as_uint(fmaf(gt[h], a[r + 9], bf_hi(w[2]))),
                               __float_as_uint(fmaf(gt[h], a[r + 12], bf_lo(w[3]))), __float_as_uint(fmaf(gt[h], a[r + 13], bf_hi(w[3]))));
                        if (jq < 2) asm volatile("ld.shared.v4.b32 {%0,%1,%2,%3}, [%4];" : "=r"(w[0]), "=r"(w[1]), "=r"(w[2]), "=r"(w[3]) : "r"(ad + 16384) : "memory");
                    }
                    fence_async_smem();
                    __syncwarp();
                    if (lane == 0) mbar_arrive(bar_stg + 48 + 32 * b + 8 * jq);
                }
            };
            mbar_wait(bar_bias, 0);
            if (t == 0) STAMP(2, 4);
            epilogue(c0, 0);
            mbar_wait(bar_bias + 8, 0);
            epilogue(c1, 1);
            if (t == 0) STAMP(2, 7);
        }
    }
}

void make_map(CUtensorMap* m, const void* ptr, int rank, const cuuint64_t* dims, const cuuint64_t* strides, const cuuint32_t* box,
              CUtensorMapSwizzle swz, bool f32 = false) {
    cuuint32_t es[5] = {1, 1, 1, 1, 1};
    get_encode()(m, f32 ? CU_TENSOR_MAP_DATA_TYPE_FLOAT32 : CU_TENSOR_MAP_DATA_TYPE_BFLOAT16, rank, const_cast<void*>(ptr), dims, strides, box, es,
                 CU_TENSOR_MAP_INTERLEAVE_NONE, swz, CU_TENSOR_MAP_L2_PROMOTION_L2_256B, CU_TENSOR_MAP_FLOAT_OOB_FILL_NONE);
}
void make_map_2d(CUtensorMap* m, const void* ptr, uint64_t inner, uint64_t outer, uint32_t box_in, uint32_t box_out) {
    cuuint64_t dims[2] = {inner, outer};
    cuuint64_t strides[1] = {inner * 2};
    cuuint32_t box[2] = {box_in, box_out};
    make_map(m, ptr, 2, dims, strides, box, CU_TENSOR_MAP_SWIZZLE_128B);
}
void make_map_conv(CUtensorMap* m, const void* p, uint32_t nch = 2) {
    cuuint64_t dims[4] = {32, 32, 2, 1024};
    cuuint64_t strides[3] = {128, 64, 4096};
    cuuint32_t box[4] = {32, 32, 2, nch};
    make_map(m, p, 4, dims, strides, box, CU_TENSOR_MAP_SWIZZLE_64B);
}

}

extern "C" void kernel_launch(void* const* d_in, const int* in_sizes, int n_in, void* d_out, int out_size) {
    const __nv_bfloat16* x = (const __nv_bfloat16*)d_in[0];
    const __nv_bfloat16* lam_re = (const __nv_bfloat16*)d_in[1];
    const __nv_bfloat16* lam_im = (const __nv_bfloat16*)d_in[2];
    const __nv_bfloat16* b_re = (const __nv_bfloat16*)d_in[3];
    const __nv_bfloat16* b_im = (const __nv_bfloat16*)d_in[4];
    const __nv_bfloat16* c_re = (const __nv_bfloat16*)d_in[5];
    const __nv_bfloat16* c_im = (const __nv_bfloat16*)d_in[6];
    const __nv_bfloat16* log_dt = (const __nv_bfloat16*)d_in[7];
    const __nv_bfloat16* dskip = (const __nv_bfloat16*)d_in[8];
    const __nv_bfloat16* kin = (const __nv_bfloat16*)d_in[10];
    const __nv_bfloat16* vin = (const __nv_bfloat16*)d_in[11];
    const __nv_bfloat16* shift_k = (const __nv_bfloat16*)d_in[12];
    const __nv_bfloat16* ssm_k = (const __nv_bfloat16*)d_in[13];
    const __nv_bfloat16* ssm_D = (const __nv_bfloat16*)d_in[14];
    const __nv_bfloat16* gate_w = (const __nv_bfloat16*)d_in[15];
    float* out = (float*)d_out;

    void *yptr = nullptr, *kvtptr = nullptr;
    cudaGetSymbolAddress(&yptr, g_y2);
    cudaGetSymbolAddress(&kvtptr, g_kvT);

    Maps maps;
    {
        cuuint64_t dims[5] = {1024, 2, 4, 32, 8};
        cuuint64_t strides[4] = {2048, 64 * 2048, 2 * 2048, 256 * 2048};
        cuuint32_t box[5] = {64, 2, 4, 32, 1};
        make_map(&maps.x5, x, 5, dims, strides, box, CU_TENSOR_MAP_SWIZZLE_128B);
    }
    int bmode = 0;
    {
        const uint64_t a = (uint64_t)b_re, b = (uint64_t)b_im;
        const uint64_t delta = a < b ? b - a : a - b;
        if (delta != 0 && (delta & 15) == 0 && delta < (1ull << 40)) bmode = a < b ? 1 : 2;
        cuuint64_t dims[4] = {1024, 8, 2, 128};
        cuuint64_t strides[3] = {2048, bmode ? delta : 16, 16384};
        cuuint32_t box[4] = {64, 8, 2, 4};
        make_map(&maps.b4, a < b ? b_re : b_im, 4, dims, strides, box, CU_TENSOR_MAP_SWIZZLE_128B);
    }
    make_map_2d(&maps.bre, b_re, 1024, 1024, 64, 8);
    make_map_2d(&maps.bim, b_im, 1024, 1024, 64, 8);
    {
        cuuint64_t dims[3] = {S_LEN, 128, 8};
        cuuint64_t strides[2] = {8 * 4096, 4096};
        cuuint32_t box[3] = {64, 16, 2};
        make_map(&maps.kvst, kvtptr, 3, dims, strides, box, CU_TENSOR_MAP_SWIZZLE_128B);
    }
    make_map_conv(&maps.sk, ssm_k, 1);
    for (int i = 0; i < 2; ++i) {
        cuuint64_t dims[5] = {1024, 2, 4, 4, 32};
        cuuint64_t strides[4] = {2048, 8 * 2048, 2 * 2048, 32 * 2048};
        cuuint32_t box[5] = {64, 2, 4, 4, 4};
        make_map(i ? &maps.cim : &maps.cre, i ? c_im : c_re, 5, dims, strides, box, CU_TENSOR_MAP_SWIZZLE_128B);
    }
    {
        cuuint64_t dims[5] = {S_LEN, 2, 4, 4, 32};
        cuuint64_t strides[4] = {4096, 8 * 4096, 2 * 4096, 32 * 4096};
        cuuint32_t box[5] = {64, 2, 4, 4, 2};
        make_map(&maps.yt, yptr, 5, dims, strides, box, CU_TENSOR_MAP_SWIZZLE_128B);
    }
    {
        cuuint64_t dims[5] = {D_DIM, 8, 4, 8, 8};
        cuuint64_t strides[4] = {4096, 64 * 4096, 8 * 4096, 256 * 4096};
        cuuint32_t box[5] = {32, 8, 4, 2, 1};
        make_map(&maps.out, out, 5, dims, strides, box, CU_TENSOR_MAP_SWIZZLE_128B, true);
    }

    auto kern = bmode == 1 ? fused_kernel<1> : bmode == 2 ? fused_kernel<2> : fused_kernel<0>;
    cudaFuncSetAttribute(kern, cudaFuncAttributeMaxDynamicSharedMemorySize, SMEM_BYTES);
    static int grid = 0;
    if (!grid) {
        int dev = 0, sms = 0;
        cudaGetDevice(&dev);
        cudaDeviceGetAttribute(&sms, cudaDevAttrMultiProcessorCount, dev);
        grid = sms == 132 ? 132 : 128;
    }
    kern<<<grid, 512, SMEM_BYTES>>>(x, kin, vin, ssm_k, shift_k, ssm_D, lam_re, lam_im, log_dt, gate_w, dskip, c_re, c_im, maps);
}
```

```cpp
#include <cuda_runtime.h>
#include <cuda_bf16.h>
#include <cuda.h>
#include <stdint.h>
#include <type_traits>

namespace {
__device__ __forceinline__ uint32_t smem_u32(const void* p) { return (uint32_t)__cvta_generic_to_shared(p); }
__device__ __forceinline__ void mbar_init(uint32_t bar, uint32_t count) {
    asm volatile("mbarrier.init.shared::cta.b64 [%0], %1;" ::"r"(bar), "r"(count) : "memory");
}
__device__ __forceinline__ void mbar_expect_tx(uint32_t bar, uint32_t bytes) {
    asm volatile("mbarrier.arrive.expect_tx.shared::cta.b64 _, [%0], %1;" ::"r"(bar), "r"(bytes) : "memory");
}
__device__ __forceinline__ void mbar_arrive(uint32_t bar) {
    asm volatile("mbarrier.arrive.shared::cta.b64 _, [%0];" ::"r"(bar) : "memory");
}
__device__ __forceinline__ void mbar_wait(uint32_t bar, uint32_t parity) {
    asm volatile(
        "{\n"
        ".reg .pred p;\n"
        ".reg .u32 n;\n"
        "mov.u32 n, 0;\n"
        "LAB_WAIT:\n"
        "mbarrier.try_wait.parity.shared::cta.b64 p, [%0], %1;\n"
        "@p bra LAB_DONE;\n"
        "add.u32 n, n, 1;\n"
        "setp.lt.u32 p, n, 0x400000;\n"
        "@p bra LAB_WAIT;\n"
        "trap;\n"
        "LAB_DONE:\n"
        "}\n" ::"r"(bar), "r"(parity) : "memory");
}
__device__ __forceinline__ void tma_load_2d(uint32_t dst, const CUtensorMap* map, uint32_t bar, int c0, int c1) {
    asm volatile(
        "cp.async.bulk.tensor.2d.shared::cluster.global.mbarrier::complete_tx::bytes [%0], [%1, {%3, %4}], [%2];"
        ::"r"(dst), "l"((uint64_t)map), "r"(bar), "r"(c0), "r"(c1) : "memory");
}
__device__ __forceinline__ void tma_load_4d(uint32_t dst, const CUtensorMap* map, uint32_t bar, int c0, int c1, int c2, int c3) {
    asm volatile(
        "cp.async.bulk.tensor.4d.shared::cluster.global.mbarrier::complete_tx::bytes [%0], [%1, {%3, %4, %5, %6}], [%2];"
        ::"r"(dst), "l"((uint64_t)map), "r"(bar), "r"(c0), "r"(c1), "r"(c2), "r"(c3) : "memory");
}
__device__ __forceinline__ void tma_load_5d(uint32_t dst, const CUtensorMap* map, uint32_t bar, int c0, int c1, int c2, int c3, int c4) {
    asm volatile(
        "cp.async.bulk.tensor.5d.shared::cluster.global.mbarrier::complete_tx::bytes [%0], [%1, {%3, %4, %5, %6, %7}], [%2];"
        ::"r"(dst), "l"((uint64_t)map), "r"(bar), "r"(c0), "r"(c1), "r"(c2), "r"(c3), "r"(c4) : "memory");
}
__device__ __forceinline__ void bulk_load(uint32_t dst, const void* src, uint32_t bytes, uint32_t bar) {
    asm volatile("cp.async.bulk.shared::cluster.global.mbarrier::complete_tx::bytes [%0], [%1], %2, [%3];"
                 ::"r"(dst), "l"(src), "r"(bytes), "r"(bar) : "memory");
}
__device__ __forceinline__ void tma_store_3d(const CUtensorMap* map, uint32_t src, int c0, int c1, int c2) {
    asm volatile("cp.async.bulk.tensor.3d.global.shared::cta.bulk_group [%0, {%2, %3, %4}], [%1];"
                 ::"l"((uint64_t)map), "r"(src), "r"(c0), "r"(c1), "r"(c2) : "memory");
}
__device__ __forceinline__ void bulk_commit() { asm volatile("cp.async.bulk.commit_group;" ::: "memory"); }
__device__ __forceinline__ void bulk_wait0() { asm volatile("cp.async.bulk.wait_group 0;" ::: "memory"); }
__device__ __forceinline__ void bulk_wait_read0() { asm volatile("cp.async.bulk.wait_group.read 0;" ::: "memory"); }
__device__ __forceinline__ void fence_async_smem() { asm volatile("fence.proxy.async.shared::cta;" ::: "memory"); }
__device__ __forceinline__ void named_bar(int id, int n) { asm volatile("bar.sync %0, %1;" ::"r"(id), "r"(n) : "memory"); }
__device__ __forceinline__ void sts128(uint32_t addr, uint32_t a, uint32_t b, uint32_t c, uint32_t d) {
    asm volatile("st.shared.v4.b32 [%0], {%1, %2, %3, %4};" ::"r"(addr), "r"(a), "r"(b), "r"(c), "r"(d) : "memory");
}
__device__ __forceinline__ void prefetch_map(const CUtensorMap* m) {
    asm volatile("prefetch.tensormap [%0];" ::"l"((uint64_t)m) : "memory");
}
__device__ __forceinline__ void wgmma_fence() { asm volatile("wgmma.fence.sync.aligned;" ::: "memory"); }
__device__ __forceinline__ void wgmma_commit() { asm volatile("wgmma.commit_group.sync.aligned;" ::: "memory"); }
template <int N>
__device__ __forceinline__ void wgmma_wait() { asm volatile("wgmma.wait_group.sync.aligned %0;" ::"n"(N) : "memory"); }
template <int N>
__device__ __forceinline__ void fence_regs(float (&a)[N]) {
#pragma unroll
    for (int i = 0; i < N; ++i) asm volatile("" : "+f"(a[i])::"memory");
}
template <int N>
__device__ __forceinline__ void fence_regs(uint32_t (&a)[N]) {
#pragma unroll
    for (int i = 0; i < N; ++i) asm volatile("" : "+r"(a[i])::"memory");
}
#define R8(a, i) "+f"(a[i + 0]), "+f"(a[i + 1]), "+f"(a[i + 2]), "+f"(a[i + 3]), "+f"(a[i + 4]), "+f"(a[i + 5]), "+f"(a[i + 6]), "+f"(a[i + 7])
#define REGS32 "{%0, %1, %2, %3, %4, %5, %6, %7, %8, %9, %10, %11, %12, %13, %14, %15, %16, %17, %18, %19, %20, %21, %22, %23, %24, %25, %26, %27, %28, %29, %30, %31}"
#define REGS16 "{%0, %1, %2, %3, %4, %5, %6, %7, %8, %9, %10, %11, %12, %13, %14, %15}"

__host__ __device__ constexpr uint32_t desc_hi(uint32_t sbo, uint32_t mode) { return (sbo >> 4) | (mode << 30); }
__device__ __forceinline__ uint32_t desc_lo(uint32_t saddr, uint32_t lbo) { return ((saddr & 0x3FFFF) >> 4) | ((lbo >> 4) << 16); }
constexpr uint32_t HI128 = desc_hi(1024, 1), HI64 = desc_hi(512, 2);
#define W8(a, i) "=f"(a[i + 0]), "=f"(a[i + 1]), "=f"(a[i + 2]), "=f"(a[i + 3]), "=f"(a[i + 4]), "=f"(a[i + 5]), "=f"(a[i + 6]), "=f"(a[i + 7])
template <int TA, int TB, int ACC, uint32_t AHI, uint32_t BHI>
__device__ __forceinline__ void wgmma_n64_ss(float (&d)[32], uint32_t alo, uint32_t blo) {
#define N64_TEXT "{\n.reg .pred p;\n.reg .b64 da, db;\nsetp.ne.b32 p, %36, 0;\nmov.b64 da, {%32, %37};\nmov.b64 db, {%33, %38};\n" \
        "wgmma.mma_async.sync.aligned.m64n64k16.f32.bf16.bf16 " REGS32 ", da, db, p, 1, 1, %34, %35;\n}\n"
    if (ACC) asm volatile(N64_TEXT : R8(d, 0), R8(d, 8), R8(d, 16), R8(d, 24) : "r"(alo), "r"(blo), "n"(TA), "n"(TB), "n"(ACC), "n"(AHI), "n"(BHI));
    else asm volatile(N64_TEXT : W8(d, 0), W8(d, 8), W8(d, 16), W8(d, 24) : "r"(alo), "r"(blo), "n"(TA), "n"(TB), "n"(ACC), "n"(AHI), "n"(BHI));
}
template <int ACC, int SA>
__device__ __forceinline__ void wgmma_n32_tt(float (&d)[16], uint32_t alo, uint32_t blo) {
#define N32T_TEXT "{\n.reg .pred p;\n.reg .b64 da, db;\nsetp.ne.b32 p, %18, 0;\nmov.b64 da, {%16, %19};\nmov.b64 db, {%17, %20};\n" \
        "wgmma.mma_async.sync.aligned.m64n32k16.f32.bf16.bf16 " REGS16 ", da, db, p, %21, 1, 1, 1;\n}\n"
    if (ACC) asm volatile(N32T_TEXT : R8(d, 0), R8(d, 8) : "r"(alo), "r"(blo), "n"(ACC), "n"(HI64), "n"(HI128), "n"(SA));
    else asm volatile(N32T_TEXT : W8(d, 0), W8(d, 8) : "r"(alo), "r"(blo), "n"(ACC), "n"(HI64), "n"(HI128), "n"(SA));
}
__device__ __forceinline__ void wgmma_n16_rs(float (&d)[8], const uint32_t (&a)[4], uint32_t blo) {
    asm volatile("{\n.reg .pred p;\n.reg .b64 db;\nsetp.ne.b32 p, 0, 0;\nmov.b64 db, {%12, %13};\n"
        "wgmma.mma_async.sync.aligned.m64n16k16.f32.bf16.bf16 {%0, %1, %2, %3, %4, %5, %6, %7}, {%8, %9, %10, %11}, db, p, 1, 1, 0;\n}\n"
        : W8(d, 0) : "r"(a[0]), "r"(a[1]), "r"(a[2]), "r"(a[3]), "r"(blo), "n"(HI128));
}

__device__ __forceinline__ float bf16r(float x) { return __bfloat162float(__float2bfloat16_rn(x)); }
__device__ __forceinline__ uint32_t pack_bf16(float lo, float hi) {
    __nv_bfloat162 v = __floats2bfloat162_rn(lo, hi);
    return *reinterpret_cast<uint32_t*>(&v);
}
__device__ __forceinline__ __nv_bfloat162 as_bf2(uint32_t w) { return *reinterpret_cast<__nv_bfloat162*>(&w); }
__device__ __forceinline__ uint32_t as_u32(__nv_bfloat162 v) { return *reinterpret_cast<uint32_t*>(&v); }
__device__ __forceinline__ float bf_lo(uint32_t w) { return __uint_as_float(w << 16); }
__device__ __forceinline__ float bf_hi(uint32_t w) { return __uint_as_float(w & 0xFFFF0000u); }
__device__ __forceinline__ void ldsm_x4_t(uint32_t& r0, uint32_t& r1, uint32_t& r2, uint32_t& r3, uint32_t addr) {
    asm volatile("ldmatrix.sync.aligned.m8n8.x4.trans.shared.b16 {%0,%1,%2,%3}, [%4];"
                 : "=r"(r0), "=r"(r1), "=r"(r2), "=r"(r3) : "r"(addr) : "memory");
}
__device__ __forceinline__ void stsm_x4(uint32_t addr, uint32_t r0, uint32_t r1, uint32_t r2, uint32_t r3) {
    asm volatile("stmatrix.sync.aligned.m8n8.x4.shared.b16 [%0], {%1,%2,%3,%4};"
                 ::"r"(addr), "r"(r0), "r"(r1), "r"(r2), "r"(r3) : "memory");
}
__device__ __forceinline__ void stsm_x4_t(uint32_t addr, uint32_t r0, uint32_t r1, uint32_t r2, uint32_t r3) {
    asm volatile("stmatrix.sync.aligned.m8n8.x4.trans.shared.b16 [%0], {%1,%2,%3,%4};"
                 ::"r"(addr), "r"(r0), "r"(r1), "r"(r2), "r"(r3) : "memory");
}
__device__ __forceinline__ uint32_t lds32(uint32_t addr) {
    uint32_t v;
    asm volatile("ld.shared.b32 %0, [%1];" : "=r"(v) : "r"(addr));
    return v;
}

typedef CUresult (*EncodeFn)(CUtensorMap*, CUtensorMapDataType, cuuint32_t, void*, const cuuint64_t*, const cuuint64_t*,
                             const cuuint32_t*, const cuuint32_t*, CUtensorMapInterleave, CUtensorMapSwizzle,
                             CUtensorMapL2promotion, CUtensorMapFloatOOBfill);
EncodeFn get_encode() {
    static EncodeFn fn = nullptr;
    if (!fn) {
        void* p = nullptr;
        cudaDriverEntryPointQueryResult qres;
        cudaGetDriverEntryPoint("cuTensorMapEncodeTiled", &p, cudaEnableDefault, &qres);
        fn = (EncodeFn)p;
    }
    return fn;
}
}
namespace {
constexpr double c_pi = 3.14159265358979323846;
constexpr double c_cos256(int i) {
    i &= 255;
    if (i > 128) i = 256 - i;
    double sgn = 1.0;
    if (i > 64) { i = 128 - i; sgn = -1.0; }
    if (i == 64) return 0.0;
    double x = 2.0 * c_pi * i / 256.0, x2 = x * x, term = 1.0, sum = 1.0;
    for (int k = 1; k < 20; ++k) { term *= -x2 / ((2 * k - 1) * (2 * k)); sum += term; }
    return sgn * sum;
}
constexpr uint32_t c_bf16(double v) {
    if (v == 0.0) return 0u;
    uint32_t s = v < 0 ? 0x8000u : 0u;
    double a = v < 0 ? -v : v;
    int e = 0;
    while (a >= 2.0) { a *= 0.5; ++e; }
    while (a < 1.0) { a *= 2.0; --e; }
    int r = (int)(a * 128.0 + 0.5);
    if (r == 256) { r = 128; ++e; }
    return s | (uint32_t)((e + 127) << 7) | (uint32_t)(r - 128);
}
__host__ __device__ constexpr int conv_k1(int r) { return (r & 8) ? 63 - (((r >> 4) << 3) | (r & 7)) : (((r >> 4) << 3) | (r & 7)); }
struct ConvTab { uint32_t w[96 * 32]; };
constexpr ConvTab make_conv_tab() {
    ConvTab t{};
    uint32_t cs[256] = {};
    for (int i = 0; i < 256; ++i) cs[i] = c_bf16(c_cos256(i));
    for (int n = 0; n < 96; ++n)
        for (int c = 0; c < 64; ++c) {
            int a = 0;
            if (n < 32) {
                const int ro = (n >> 3) & 1, ri = n & 7, co = (c >> 3) & 1, ci = c & 7;
                a = n < 16 ? 8 * ci * (4 * ri + (c >> 4)) : 8 * ri * (4 * ci + (c >> 4));
                a += (ro == co) ? 0 : (ro == 0) ? 192 : 64;
            } else {
                const int r = n - 32, n1 = 2 * (c & 31) + (c >> 5);
                a = n1 * (2 * (((r >> 4) << 3) | (r & 7)) + 1) + ((r & 8) ? 64 : 0);
            }
            const int off = n * 128 + (((c >> 3) ^ (n & 7)) << 4) + (c & 7) * 2;
            t.w[off >> 2] |= cs[a & 255] << ((off & 2) * 8);
        }
    return t;
}
__device__ __align__(128) constexpr ConvTab g_conv_tab = make_conv_tab();

struct Twiddle { uint32_t r[8], i[8], n[8]; };
constexpr double c_cospi(double x) {
    double sgn = 1.0;
    if (x > 0.5) { x = 1.0 - x; sgn = -1.0; }
    const double y = c_pi * x, y2 = y * y;
    double term = 1.0, sum = 1.0;
    for (int k = 1; k < 12; ++k) { term *= -y2 / ((2 * k - 1) * (2 * k)); sum += term; }
    return sgn * sum;
}
struct TwTab { uint32_t w[3072]; };
constexpr TwTab make_tw_tab() {
    TwTab t{};
    for (int th = 0; th < 128; ++th)
        for (int q = 0; q < 8; ++q)
            for (int e = 0; e < 2; ++e) {
                const int k1 = conv_k1(16 * (th >> 5) + 8 * (q & 1) + ((th & 31) >> 2)), n2 = 8 * (q >> 1) + 2 * (th & 3) + e;
                const double x = (double)(n2 * (2 * k1 + 1)) / 4096.0;
                const double cs = c_cospi(x), sn = n2 == 0 ? 0.0 : c_cospi(x > 0.5 ? x - 0.5 : 0.5 - x);
                t.w[((q >> 2) * 128 + th) * 4 + (q & 3)] |= c_bf16(cs * 0.0625) << (16 * e);
                t.w[((2 + (q >> 2)) * 128 + th) * 4 + (q & 3)] |= c_bf16(-sn * 0.0625) << (16 * e);
                t.w[((4 + (q >> 2)) * 128 + th) * 4 + (q & 3)] |= c_bf16(sn * 0.0625) << (16 * e);
            }
    return t;
}
__device__ __align__(128) constexpr TwTab g_tw_tab = make_tw_tab();
__device__ __forceinline__ void load_twiddle(Twiddle& tw, const uint4* p) {
#pragma unroll
    for (int q = 0; q < 2; ++q) {
        const uint4 a = __ldg(p + q * 128);
        const uint4 b = __ldg(p + (2 + q) * 128);
        tw.r[4 * q] = a.x; tw.r[4 * q + 1] = a.y; tw.r[4 * q + 2] = a.z; tw.r[4 * q + 3] = a.w;
        const uint4 n = __ldg(p + (4 + q) * 128);
        tw.n[4 * q] = n.x; tw.n[4 * q + 1] = n.y; tw.n[4 * q + 2] = n.z; tw.n[4 * q + 3] = n.w;
        tw.i[4 * q] = b.x; tw.i[4 * q + 1] = b.y; tw.i[4 * q + 2] = b.z; tw.i[4 * q + 3] = b.w;
    }
}

__device__ __forceinline__ int fresh_tid() { int v; asm volatile("mov.u32 %0, %tid.x;" : "=r"(v)); return v; }
__device__ __forceinline__ uint32_t hmul(uint32_t a, uint32_t b) { return as_u32(__hmul2_rn(as_bf2(a), as_bf2(b))); }
__device__ __forceinline__ uint32_t hadd(uint32_t a, uint32_t b) { return as_u32(__hadd2_rn(as_bf2(a), as_bf2(b))); }
__device__ __forceinline__ uint32_t hsub(uint32_t a, uint32_t b) { return as_u32(__hsub2_rn(as_bf2(a), as_bf2(b))); }
__device__ __forceinline__ uint32_t hfma(uint32_t a, uint32_t b, uint32_t c) { return as_u32(__hfma2(as_bf2(a), as_bf2(b), as_bf2(c))); }

__device__ __forceinline__ void conv_dft8(float (&x)[4][8], const uint32_t (&f)[4][4], uint32_t blo) {
#pragma unroll
    for (int r = 0; r < 4; ++r) wgmma_n16_rs(x[r], f[r], blo + 2 * r);
}
template <class T, int N>
__device__ __forceinline__ void fence_regs4(T (&a)[4][N]) { fence_regs(a[0]); fence_regs(a[1]); fence_regs(a[2]); fence_regs(a[3]); }
__device__ __forceinline__ void conv_s1(float (&dE)[32], float (&dO)[32], uint32_t tlo, uint32_t ulo) {
    wgmma_n64_ss<0, 1, 0, HI128, HI64>(dE, tlo + 256, ulo);
    wgmma_n64_ss<0, 1, 0, HI128, HI64>(dO, tlo + 256 + 4, ulo + 128);
    wgmma_n64_ss<0, 1, 1, HI128, HI64>(dE, tlo + 256 + 2, ulo + 64);
    wgmma_n64_ss<0, 1, 1, HI128, HI64>(dO, tlo + 256 + 6, ulo + 192);
}
template <int S>
__device__ __forceinline__ void conv_t1(const float (&dE)[32], const float (&dO)[32], const Twiddle& tw, float dsk, uint32_t (&f)[4][4]) {
    uint32_t ar[8], ai[8], fs[8], fd[8];
#pragma unroll
    for (int j = 0; j < 4; ++j) {
        const int i = 16 * S + 4 * j;
        const uint32_t e0 = pack_bf16(i == 16 ? dE[i] + dsk : dE[i], dE[i + 1]), e1 = pack_bf16(dE[i + 2], dE[i + 3]);
        const uint32_t o0 = pack_bf16(dO[i], dO[i + 1]), o1 = pack_bf16(dO[i + 2], dO[i + 3]);
        ar[2 * j] = hadd(e0, o0); ai[2 * j] = hadd(e1, o1);
        ar[2 * j + 1] = hsub(e0, o0); ai[2 * j + 1] = hsub(o1, e1);
    }
#pragma unroll
    for (int q = 0; q < 4; ++q) {
        const uint32_t pr = hfma(ar[q], tw.r[q], hmul(ai[q], tw.n[q])), pi = hfma(ar[q], tw.i[q], hmul(ai[q], tw.r[q]));
        fs[q] = hfma(ar[4 + q], tw.r[4 + q], hfma(ai[4 + q], tw.n[4 + q], pr));
        fs[4 + q] = hfma(ar[4 + q], tw.i[4 + q], hfma(ai[4 + q], tw.r[4 + q], pi));
        fd[q] = hfma(pr, 0xC000C000u, fs[q]);
        fd[4 + q] = hfma(pi, 0xC000C000u, fs[4 + q]);
    }
#pragma unroll
    for (int h = 0; h < 2; ++h) {
        f[0][h] = hadd(fs[h], fs[2 + h]); f[0][2 + h] = hadd(fs[4 + h], fs[6 + h]);
        f[2][h] = hsub(fs[h], fs[2 + h]); f[2][2 + h] = hsub(fs[4 + h], fs[6 + h]);
        f[1][h] = hadd(fd[h], fd[6 + h]); f[1][2 + h] = hsub(fd[4 + h], fd[2 + h]);
        f[3][h] = hsub(fd[h], fd[6 + h]); f[3][2 + h] = hadd(fd[4 + h], fd[2 + h]);
    }
}
__device__ __forceinline__ void conv_prod(const float (&xu)[8], const float (&xk)[8], uint32_t (&f)[4]) {
#pragma unroll
    for (int h = 0; h < 2; ++h) {
        float pr[2], pi[2];
#pragma unroll
        for (int e = 0; e < 2; ++e) {
            const float ur = xu[2 * h + e], ui = xu[4 + 2 * h + e], kr = xk[2 * h + e], ki = xk[4 + 2 * h + e];
            pr[e] = fmaf(ur, kr, -ui * ki);
            pi[e] = fmaf(-ur, ki, -ui * kr);
        }
        f[h] = pack_bf16(pr[0], pr[1]);
        f[2 + h] = pack_bf16(pi[0], pi[1]);
    }
}
template <bool SYNC, bool NEXT, class G>
__device__ __forceinline__ void conv_channel(float (&dE)[32], float (&dO)[32], const Twiddle& tw, float dsk, uint32_t tlo, uint32_t nxt,
                                             uint32_t wre, uint32_t wim, int bar, G before_next) {
    float xu[4][8], xk[4][8];
    {
        uint32_t fu[4][4], fk[4][4];
        conv_t1<0>(dE, dO, tw, 0.f, fu);
        wgmma_fence();
        conv_dft8(xu, fu, tlo);
        wgmma_commit();
        conv_t1<1>(dE, dO, tw, dsk, fk);
        wgmma_fence();
        conv_dft8(xk, fk, tlo);
        wgmma_commit();
        before_next();
        wgmma_wait<0>();
        fence_regs4(xu); fence_regs4(xk);
        fence_regs4(fu); fence_regs4(fk);
    }
    uint32_t fp[4][4];
#pragma unroll
    for (int r = 0; r < 4; ++r) conv_prod(xu[r], xk[r], fp[r]);
    wgmma_fence();
    conv_dft8(xu, fp, tlo + 128);
    wgmma_commit();
    if (NEXT) {
        conv_s1(dE, dO, tlo, nxt);
        wgmma_commit();
    }
    wgmma_wait<NEXT ? 1 : 0>();
    fence_regs4(xu);
    fence_regs4(fp);
    uint32_t zr[8], zi[8], wr[8], wi[8];
#pragma unroll
    for (int h = 0; h < 2; ++h) {
        uint32_t yr[4], yi[4];
#pragma unroll
        for (int r = 0; r < 4; ++r) { yr[r] = pack_bf16(xu[r][2 * h], xu[r][2 * h + 1]); yi[r] = pack_bf16(xu[r][4 + 2 * h], xu[r][5 + 2 * h]); }
        const uint32_t u0r = hadd(yr[0], yr[2]), u0i = hadd(yi[0], yi[2]), u1r = hsub(yr[0], yr[2]), u1i = hsub(yi[0], yi[2]);
        const uint32_t v0r = hadd(yr[1], yr[3]), v0i = hadd(yi[1], yi[3]), v1r = hsub(yr[1], yr[3]), v1i = hsub(yi[1], yi[3]);
        zr[h] = hadd(u0r, v0r); zi[h] = hadd(u0i, v0i); zr[4 + h] = hsub(u0r, v0r); zi[4 + h] = hsub(u0i, v0i);
        zr[2 + h] = hadd(u1r, v1i); zi[2 + h] = hsub(u1i, v1r); zr[6 + h] = hsub(u1r, v1i); zi[6 + h] = hadd(u1i, v1r);
    }
#pragma unroll
    for (int q = 0; q < 8; ++q) {
        wr[q] = hfma(zr[q], tw.r[q], hmul(zi[q], tw.n[q]));
        wi[q] = hfma(zr[q], tw.i[q], hmul(zi[q], tw.r[q]));
    }
    if (SYNC) named_bar(bar, 128);
    stsm_x4(wre, hadd(wr[0], wr[1]), hadd(wr[2], wr[3]), hadd(wr[4], wr[5]), hadd(wr[6], wr[7]));
    stsm_x4(wre + 512, hsub(wi[1], wi[0]), hsub(wi[3], wi[2]), hsub(wi[5], wi[4]), hsub(wi[7], wi[6]));
    stsm_x4(wim, hsub(wr[1], wr[0]), hsub(wr[3], wr[2]), hsub(wr[5], wr[4]), hsub(wr[7], wr[6]));
    stsm_x4(wim + 512, hadd(wi[0], wi[1]), hadd(wi[2], wi[3]), hadd(wi[4], wi[5]), hadd(wi[6], wi[7]));
}
template <bool NEXT, class G>
__device__ __forceinline__ void conv_pair(float (&dE)[32], float (&dO)[32], const Twiddle& tw, uint32_t dd, uint32_t tlo, uint32_t u0, uint32_t un,
                                          uint32_t lo, int BAR, G before_next) {
    conv_channel<false, true>(dE, dO, tw, bf_lo(dd), tlo, desc_lo(u0 + 4096, 8192), u0 + lo, u0 + 8192 + lo, BAR, []() {});
    wgmma_wait<0>();
    fence_regs(dE); fence_regs(dO);
    conv_channel<true, NEXT>(dE, dO, tw, bf_hi(dd), tlo, desc_lo(un, 8192), u0 + 4096 + lo, u0 + 12288 + lo, BAR, before_next);
    fence_async_smem();
    named_bar(BAR, 128);
    float ye[16], yo[16];
    wgmma_fence();
    const uint32_t wlo = desc_lo(u0, 4096);
    wgmma_n32_tt<0, 1>(ye, wlo, tlo + 256);
    wgmma_n32_tt<0, -1>(yo, wlo + 512, tlo + 256 + 4);
#pragma unroll
    for (int k = 1; k < 4; ++k) {
        wgmma_n32_tt<1, 1>(ye, wlo + 64 * k, tlo + 256 + 128 * k);
        wgmma_n32_tt<1, -1>(yo, wlo + 512 + 64 * k, tlo + 256 + 4 + 128 * k);
    }
    wgmma_commit();
    wgmma_wait<0>();
    fence_regs(ye); fence_regs(yo);
    if (NEXT) { fence_regs(dE); fence_regs(dO); }
    named_bar(BAR, 128);
    const int t = fresh_tid();
    const uint32_t ya = u0 + (t & 64) * 64 + (t & 31) * 64 + (((((t >> 4) & 2) ^ (t >> 1)) & 3) << 4);
#pragma unroll
    for (int h = 0; h < 2; ++h) {
        stsm_x4_t(ya ^ (16 * h), pack_bf16(ye[2 * h], ye[2 * h + 1]), pack_bf16(ye[4 + 2 * h], ye[5 + 2 * h]),
                  pack_bf16(ye[8 + 2 * h], ye[9 + 2 * h]), pack_bf16(ye[12 + 2 * h], ye[13 + 2 * h]));
        stsm_x4_t((ya ^ (16 * h)) + 2048, pack_bf16(yo[2 * h], yo[2 * h + 1]), pack_bf16(yo[4 + 2 * h], yo[5 + 2 * h]),
                  pack_bf16(yo[8 + 2 * h], yo[9 + 2 * h]), pack_bf16(yo[12 + 2 * h], yo[13 + 2 * h]));
    }
    fence_async_smem();
    __syncwarp();
}
}

namespace {

constexpr int S_LEN = 2048;
constexpr int D_DIM = 1024;

#define REG_P 24
#define REG_AB 168
#define REG_C 152
#define ULATE 3
#define CLATE 4
#define QD 3
#define QKB 18
#define GAP_Y1 50
#define QD2 6
#define KVFINE 0
#define G1ORD 0
#define SKEW1 4
#define TK_PF0 0
#define GAP_PF 300
#define TK_KV0 2
#define TK_KV1 4
#define GAP_KV 50
#define GAP_ST 50
#define GAP_HB 100
#define PFD 7
#define CWAIT 0
#define GAP_Y 100
#define GAP_X 100
#define SLOT4 20
#define SKEW2 4
#define KVFMA 0
#define G2SIG 0
#define GAP_CV 100
#define TK_C 8
#define GWAIT 0

__device__ __align__(1024) __nv_bfloat16 g_H[2 * D_DIM * S_LEN];
__device__ __align__(1024) __nv_bfloat16 g_y2[D_DIM * S_LEN];
__device__ __align__(1024) __nv_bfloat16 g_kvT[D_DIM * S_LEN];
__device__ __align__(128) float g_gate[S_LEN];
__device__ __align__(128) unsigned long long g_agg[8 * D_DIM];
__device__ __align__(128) unsigned int g_cnt[56 * 32];

#define STAMP(k, s) do { } while (0)
#define SAMPLE(i) do { } while (0)

__device__ __forceinline__ void tma_store_5d(const CUtensorMap* map, uint32_t src, int c0, int c1, int c2, int c3, int c4) {
    asm volatile("cp.async.bulk.tensor.5d.global.shared::cta.bulk_group [%0, {%2, %3, %4, %5, %6}], [%1];"
                 ::"l"((uint64_t)map), "r"(src), "r"(c0), "r"(c1), "r"(c2), "r"(c3), "r"(c4) : "memory");
}
#define ELECT "{\n.reg .pred p;\nelect.sync _|p, 0xffffffff;\n@p "
__device__ __forceinline__ void e_expect_tx(uint32_t bar, uint32_t bytes) {
    asm volatile(ELECT "mbarrier.arrive.expect_tx.shared::cta.b64 _, [%0], %1;\n}" ::"r"(bar), "r"(bytes) : "memory");
}
__device__ __forceinline__ void e_arrive(uint32_t bar) {
    asm volatile(ELECT "mbarrier.arrive.shared::cta.b64 _, [%0];\n}" ::"r"(bar) : "memory");
}
__device__ __forceinline__ void e_load_4d(uint32_t dst, const CUtensorMap* map, uint32_t bar, int c0, int c1, int c2, int c3) {
    asm volatile(ELECT "cp.async.bulk.tensor.4d.shared::cluster.global.mbarrier::complete_tx::bytes [%0], [%1, {%3, %4, %5, %6}], [%2];\n}"
        ::"r"(dst), "l"((uint64_t)map), "r"(bar), "r"(c0), "r"(c1), "r"(c2), "r"(c3) : "memory");
}
__device__ __forceinline__ void e_load_5d(uint32_t dst, const CUtensorMap* map, uint32_t bar, int c0, int c1, int c2, int c3, int c4) {
    asm volatile(ELECT "cp.async.bulk.tensor.5d.shared::cluster.global.mbarrier::complete_tx::bytes [%0], [%1, {%3, %4, %5, %6, %7}], [%2];\n}"
        ::"r"(dst), "l"((uint64_t)map), "r"(bar), "r"(c0), "r"(c1), "r"(c2), "r"(c3), "r"(c4) : "memory");
}
__device__ __forceinline__ void e_bulk_load(uint32_t dst, const void* src, uint32_t bytes, uint32_t bar) {
    asm volatile(ELECT "cp.async.bulk.shared::cluster.global.mbarrier::complete_tx::bytes [%0], [%1], %2, [%3];\n}"
                 ::"r"(dst), "l"(src), "r"(bytes), "r"(bar) : "memory");
}
__device__ __forceinline__ void l2_prefetch(const void* p, uint32_t bytes) {
    asm volatile("cp.async.bulk.prefetch.L2.global [%0], %1;" ::"l"(p), "r"(bytes) : "memory");
}
__device__ __forceinline__ void l2_prefetch_4d(const CUtensorMap* map, int c0, int c1, int c2, int c3) {
    asm volatile("cp.async.bulk.prefetch.tensor.4d.L2.global [%0, {%1, %2, %3, %4}];" ::"l"((uint64_t)map), "r"(c0), "r"(c1), "r"(c2), "r"(c3) : "memory");
}
__device__ __forceinline__ void l2_prefetch_5d(const CUtensorMap* map, int c0, int c1, int c2, int c3, int c4) {
    asm volatile("cp.async.bulk.prefetch.tensor.5d.L2.global [%0, {%1, %2, %3, %4, %5}];" ::"l"((uint64_t)map), "r"(c0), "r"(c1), "r"(c2), "r"(c3), "r"(c4) : "memory");
}
__device__ __forceinline__ unsigned int ld_relaxed(const unsigned int* p) {
    unsigned int v;
    asm volatile("ld.relaxed.gpu.global.u32 %0, [%1];" : "=r"(v) : "l"(p) : "memory");
    return v;
}
__device__ __forceinline__ void fence_async_global() { asm volatile("fence.proxy.async.global;" ::: "memory"); }
__device__ __forceinline__ void wait_counter(const unsigned int* p, unsigned int target) {
    unsigned int v;
    int it = 0;
    do { asm volatile("ld.acquire.gpu.global.u32 %0, [%1];" : "=r"(v) : "l"(p) : "memory"); } while (v != target && ++it < (1 << 22));
    fence_async_global();
}
__device__ __forceinline__ void red_release(unsigned int* p, unsigned int n) {
    asm volatile("red.release.gpu.global.add.u32 [%0], %1;" ::"l"(p), "r"(n) : "memory");
}
__device__ __forceinline__ uint4 ldg128(const void* p) {
    uint4 v;
    asm volatile("ld.global.nc.v4.u32 {%0,%1,%2,%3}, [%4];" : "=r"(v.x), "=r"(v.y), "=r"(v.z), "=r"(v.w) : "l"(p));
    return v;
}
__device__ __forceinline__ void stg128(void* p, uint32_t a, uint32_t b, uint32_t c, uint32_t d) {
    asm volatile("st.global.v4.b32 [%0], {%1, %2, %3, %4};" ::"l"(p), "r"(a), "r"(b), "r"(c), "r"(d) : "memory");
}

template <int TA>
__device__ __forceinline__ void wgmma_n128(float (&d)[64], uint32_t alo, uint32_t blo, int acc) {
    asm volatile(
        "{\n.reg .pred p;\n.reg .b64 da, db;\nsetp.ne.b32 p, %67, 0;\nmov.b64 da, {%64, %69};\nmov.b64 db, {%65, %66};\n"
        "wgmma.mma_async.sync.aligned.m64n128k16.f32.bf16.bf16 "
        "{%0, %1, %2, %3, %4, %5, %6, %7, %8, %9, %10, %11, %12, %13, %14, %15, "
        "%16, %17, %18, %19, %20, %21, %22, %23, %24, %25, %26, %27, %28, %29, %30, %31, "
        "%32, %33, %34, %35, %36, %37, %38, %39, %40, %41, %42, %43, %44, %45, %46, %47, "
        "%48, %49, %50, %51, %52, %53, %54, %55, %56, %57, %58, %59, %60, %61, %62, %63}, "
        "da, db, p, 1, 1, %68, 0;\n"
        "}\n"
        : R8(d, 0), R8(d, 8), R8(d, 16), R8(d, 24), R8(d, 32), R8(d, 40), R8(d, 48), R8(d, 56)
        : "r"(alo), "r"(blo), "n"(HI128), "r"(acc), "n"(TA), "n"(TA ? HI64 : HI128));
}

constexpr int NST = 5;
constexpr int XTRA = SKEW1 - 4;
static_assert(SKEW1 >= 4 && SKEW1 <= 12, "skew");
constexpr int OFF_BB = 4 * 32768;
constexpr int OFF_CT = 5 * 32768;
constexpr int OFF_CU = OFF_CT + 32768;
__host__ __device__ constexpr uint32_t conv_buf(int p) { return OFF_CT + 16384 + (p == 3 ? 0 : p) * 16384; }
constexpr int OFF_PAR = OFF_CU + 32768;
constexpr int OFF_BAR = OFF_PAR + 2048;
constexpr int SMEM_BYTES = OFF_BAR + 896;
static_assert(SMEM_BYTES <= 232448, "smem layout");

static_assert(SLOT4 % 4 == 0 && SLOT4 <= 24, "ring");
constexpr uint32_t PH4 = (SLOT4 / 4 - 1) & 1;
__host__ __device__ constexpr int ring_slot(int kb) { return (kb - SLOT4 + 4) % 5; }
__host__ __device__ constexpr uint32_t ring_par(int kb) { return ((SLOT4 / 4 - 1 + (kb - SLOT4 + 4) / 5) & 1) ^ (ring_slot(kb) == 4 ? PH4 : 0); }

struct Maps {
    CUtensorMap x5, b4, cre, cim, sk, yt, out, kvst, bre, bim;
};

__device__ __forceinline__ void cmul(float& r, float& i, float ar, float ai, float br, float bi) {
    const float a = ar * br - ai * bi, b = ar * bi + ai * br;
    r = a; i = b;
}
__device__ __forceinline__ void csqr(float& r, float& i) { const float a = r * r - i * i, b = 2.f * r * i; r = a; i = b; }
__device__ __forceinline__ float after(float v, float dep) { return __float_as_uint(dep) == 0x7fedcba9u ? dep : v; }

template <int BMODE>
__global__ void __launch_bounds__(512, 1)
fused_kernel(const __nv_bfloat16* __restrict__ x,
             const __nv_bfloat16* __restrict__ kin, const __nv_bfloat16* __restrict__ vin, const __nv_bfloat16* __restrict__ ssm_k,
             const __nv_bfloat16* __restrict__ shift_k, const __nv_bfloat16* __restrict__ ssm_D,
             const __nv_bfloat16* __restrict__ lam_re, const __nv_bfloat16* __restrict__ lam_im,
             const __nv_bfloat16* __restrict__ log_dt, const __nv_bfloat16* __restrict__ gate_w,
             const __nv_bfloat16* __restrict__ dskip,
             const __nv_bfloat16* __restrict__ c_re, const __nv_bfloat16* __restrict__ c_im,
             const __grid_constant__ Maps maps) {
    constexpr bool MERGED = BMODE != 0, SW = BMODE == 2;
    extern __shared__ __align__(1024) unsigned char smem_raw[];
    const uint32_t sbase = smem_u32(smem_raw);
    const uint32_t bar_full = sbase + OFF_BAR;
    const uint32_t bar_empty = bar_full + 32;
    const uint32_t bar_full2 = bar_empty + 32;
    const uint32_t bar_empty2 = bar_full2 + 40;
    const uint32_t bar_k = bar_empty2 + 40;
    const uint32_t bar_tab = bar_k + 32;
    const uint32_t bar_ab = bar_tab + 8;
    const uint32_t bar_adone = bar_ab + 8;
    const uint32_t bar_par = bar_adone + 8;
    const uint32_t bar_y = bar_par + 8;
    const uint32_t bar_rel = bar_y + 8;
    const uint32_t bar_kvrel = bar_rel + 8;
    const uint32_t bar_yrel = bar_kvrel + 8;
    const uint32_t bar_y1 = bar_yrel + 8;
    const uint32_t bar_fh = bar_y1 + 8;
    const uint32_t bar_tick = bar_fh + 24;
    const uint32_t bar_stg = bar_tick + 104;
    const uint32_t bar_bias = bar_stg + 112;
    const uint32_t bar_hw = bar_bias + 16;
    const uint32_t bar_gate = bar_hw + 32;
    const uint32_t bar_ascan = bar_gate + 8;
    const uint32_t bar_g2 = bar_hw;
    const uint32_t w_bid = bar_full + 600, w_dsk = bar_full + 608, w_ones = bar_full + 640;
    const int tid = threadIdx.x, warp = __shfl_sync(0xffffffffu, tid >> 5, 0), wg = warp >> 2, lane = tid & 31;
    int bid = blockIdx.x;
    {
        unsigned int sm, nsm;
        asm volatile("mov.u32 %0, %smid;" : "=r"(sm));
        asm volatile("mov.u32 %0, %nsmid;" : "=r"(nsm));
        if (gridDim.x == 132 && nsm == 132) {
            const int tpc = sm >> 1;
            int gp, ix;
            if (tpc < 32) { gp = tpc & 7; ix = tpc >> 3; }
            else if (tpc < 60) { ix = ((tpc - 32) * 37) >> 8; gp = tpc - 31 - 7 * ix; ix += 4; }
            else { gp = 0; ix = tpc - 58; }
            bid = (tpc | 1) == 61 ? 128 : (4 * (gp >> 1) + (ix >> 1)) * 8 + 4 * (gp & 1) + 2 * (ix & 1) + (sm & 1);
        }
    }
    if (bid >= 128) {
        if (tid == 0) {
            __nanosleep(2000);
            const unsigned int target = (ld_relaxed(&g_cnt[32 * 32]) & ~63u) + 64u;
            for (int i = 0; i < 8; ++i)
                for (int it = 0; ld_relaxed(&g_cnt[(40 + i) * 32]) != target && it < (1 << 12); ++it) __nanosleep(500);
        }
        return;
    }
    const int tt = bid >> 3, dt = bid & 7;
    const int ti = tt >> 1;
    const int cg = (dt >> 2) * 8 + (tt & 1) * 4 + (dt & 3);
    if (warp == 0) {
        if (lane == 0) {
            STAMP(1, 0);
#pragma unroll
            for (int s = 0; s < 4; ++s) mbar_init(bar_full + 8 * s, 1);
            asm volatile("fence.mbarrier_init.release.cluster;" ::: "memory");
        }
        __syncwarp();
        if (MERGED) {
#pragma unroll 1
            for (int it = 0; it < 4; ++it) {
                e_expect_tx(bar_full + 8 * it, 49152);
                e_load_4d(sbase + OFF_CU + it * 8192, &maps.b4, bar_full + 8 * it, it * 64, 0, 0, cg * 4);
                e_load_5d(sbase + ((it - XTRA) & 3) * 32768, &maps.x5, bar_full + 8 * it, it * 64, 0, 0, 0, ti);
                e_load_4d(sbase + OFF_BB + it * 8192, &maps.b4, bar_full + 8 * it, it * 64, 0, 0, 64 + cg * 4);
                if (it == 0) asm volatile("bar.arrive 4, 512;" ::: "memory");
            }
        }
        if (lane == 0) STAMP(1, 1);
    } else if (tid == 32) {
        if (sbase & 1023) __trap();
#pragma unroll
        for (int s = 0; s < 4; ++s) mbar_init(bar_empty + 8 * s, 2);
#pragma unroll
        for (int s = 0; s < NST; ++s) { mbar_init(bar_full2 + 8 * s, 1); mbar_init(bar_empty2 + 8 * s, 1); }
        mbar_init(bar_k, 1); mbar_init(bar_k + 8, 1); mbar_init(bar_k + 16, 1); mbar_init(bar_k + 24, 1);
        mbar_init(bar_tab, 1);
        mbar_init(bar_ab, 1);
        mbar_init(bar_adone, 4);
        mbar_init(bar_par, 2);
        asm volatile("fence.mbarrier_init.release.cluster;" ::: "memory");
    } else if (tid == 64) {
#pragma unroll
        for (int s = 0; s < 21; ++s) mbar_init(bar_y + 8 * s, 1);
    } else if (tid == 96) {
#pragma unroll
        for (int s = 0; s < 22; ++s) mbar_init(bar_stg + 8 * s, 4);
    } else if (tid == 128) {
        asm volatile("st.shared.b32 [%0], %1;" ::"r"(w_bid), "r"(bid) : "memory");
        SAMPLE(0);
    }
    if (MERGED) {
        if (warp == 0) asm volatile("bar.sync 5, 64;" ::: "memory");
        else {
            __syncwarp();
            asm volatile("bar.sync 4, 512;" ::: "memory");
            if (warp == 1) asm volatile("bar.arrive 5, 64;" ::: "memory");
        }
    } else {
        __syncthreads();
    }

    if (wg == 0) {
        asm volatile("setmaxnreg.dec.sync.aligned.u32 %0;" ::"n"(REG_P));
        if (warp == 0) {
#pragma unroll 1
            for (int it = MERGED ? 4 : 0; it < 16 + XTRA; ++it) {
                const int st = it & 3, kb = it < 16 ? it : it - SKEW1;
                const bool fa = it < 16, fb = it < 16 - SKEW1 || it >= 12;
                const uint32_t bf = bar_full + 8 * st;
                mbar_wait(bar_empty + 8 * st, ((it >> 2) & 1) ^ 1);
                e_expect_tx(bf, fa && fb ? 49152 : 40960);
                e_load_5d(sbase + ((it - XTRA) & 3) * 32768, &maps.x5, bf, kb * 64, 0, 0, 0, ti);
                if (MERGED) {
                    if (fa) e_load_4d(sbase + OFF_CU + st * 8192, &maps.b4, bf, kb * 64, 0, 0, cg * 4);
                    if (fb) e_load_4d(sbase + OFF_BB + st * 8192, &maps.b4, bf, kb * 64, 0, 0, 64 + cg * 4);
                } else {
                    if (lane < 16 && ((lane & 8) ? fb : fa))
                        tma_load_2d(sbase + ((lane & 8) ? OFF_BB : OFF_CU) + st * 8192 + (lane & 7) * 1024, (lane & 1) ? &maps.bim : &maps.bre, bf,
                                    kb * 64, (lane >> 3) * 512 + cg * 32 + ((lane & 7) >> 1) * 8);
                    __syncwarp();
                }
                if (it >= 4 && it < 16) e_arrive(bar_tick + 8 * (it - 3));
                if (lane == 0) STAMP(1, 16 + it);
                if (lane == 0 && it < 16) SAMPLE(it - 3);
            }
            int st = 0;
            uint32_t ph = 0;
#pragma unroll 1
            for (int kb = 0; kb < 32; ++kb) {
                const uint32_t bf = bar_full2 + 8 * st;
                if (kb == CLATE) mbar_wait(bar_rel, 0);
                mbar_wait(bar_empty2 + 8 * st, st == 4 ? ph ^ PH4 : ph);
                e_expect_tx(bf, 32768);
                e_load_5d(sbase + st * 32768 + 16384, &maps.cre + ((kb >> 3) & 1), bf, ((kb >> 4) * 8 + (kb & 7)) * 64, 0, 0, 0, dt * 4);
                if (lane == 0) STAMP(2, 16 + kb);
                if (lane == 0 && (kb & 3) == 0) SAMPLE(13 + (kb >> 2));
                if (++st == (kb < SLOT4 - 1 ? 4 : 5)) { st = 0; ph ^= 1; }
            }
        } else if (warp == 1) {
            mbar_wait(bar_full, 0);
            e_arrive(bar_tick);
            if (MERGED && PFD && lane == 0) {
#pragma unroll 1
                for (int n = 0; n + PFD < 16; ++n) {
                    mbar_wait(bar_tick + 8 * n, 0);
                    if (cg >= 4 && max(cg - PFD, 0) == n) l2_prefetch_5d(&maps.x5, cg * 64, 0, 0, 0, ti);
                    if (ti >= 2 && max(2 * ti - PFD, 0) == n) {
#pragma unroll 1
                        for (int i = 0; i < 4; ++i) l2_prefetch_4d(&maps.b4, (2 * ti + (i >> 1)) * 64, 0, 0, (i & 1) * 64 + cg * 4);
                    }
                }
            }
            __syncwarp();
            const unsigned int target = (ld_relaxed(&g_cnt[(4 * ti) * 32]) & ~63u) + 64u;
            const char* hp = reinterpret_cast<const char*>(g_H) + (size_t)tt * 262144;
            mbar_wait(bar_adone, 0);
            e_expect_tx(bar_k + 8, 16384);
            e_expect_tx(bar_k + 16, 16384);
#pragma unroll 1
            for (int c = 2; c < 6; ++c) {
                e_load_4d(sbase + conv_buf(0) + (c >> 1) * 16384 + (c & 1) * 4096 + 8192, &maps.sk, bar_k + 8 * (c >> 1), 0, 0, 0, bid * 8 + c);
                if (GAP_CV) __nanosleep(GAP_CV);
            }
            mbar_wait(bar_rel, 0);
            int st = 0;
            uint32_t ph = 0;
#pragma unroll 1
            for (int q = 0; q < 4; ++q) {
                if (lane == 0) STAMP(0, 8 + 2 * q);
                if (q == 0) wait_counter(&g_cnt[(4 * ti) * 32], target);
                else { mbar_wait(bar_fh + 8 * q - 8, 0); fence_async_global(); }
                if (lane == 0) STAMP(0, 9 + 2 * q);
#pragma unroll 1
                for (int kb = 0; kb < 8; ++kb) {
                    mbar_wait(bar_empty2 + 8 * st, st == 4 ? ph ^ PH4 : ph);
                    e_bulk_load(sbase + st * 32768, hp + kb * 16384, 16384, bar_full2 + 8 * st);
                    if (++st == (8 * q + kb < SLOT4 - 1 ? 4 : 5)) { st = 0; ph ^= 1; }
                }
                hp += (q & 1) ? 4194304 - 131072 : 131072;
            }
        } else if (warp == 2) {
            if (lane == 0) {
                mbar_wait(bar_tick + 8, 0);
                const unsigned int target = (ld_relaxed(&g_cnt[(40 + dt) * 32]) & ~63u) + 64u;
                asm volatile("st.shared.b32 [%0], %1;" ::"r"(w_bid + 4), "r"(target) : "memory");
                prefetch_map(&maps.kvst); prefetch_map(&maps.sk);
#pragma unroll 1
                for (int bt = 0; bt < 2; ++bt) {
                    mbar_wait(bar_stg + 8 * bt, 0);
#pragma unroll 1
                    for (int i = 0; i < 4; ++i) {
                        if (i) __nanosleep(GAP_ST);
                        tma_store_3d(&maps.kvst, sbase + OFF_CT + bt * 16384 + i * 4096, (tt & 1) * 1024 + ti * 128 + 64 * bt, dt * 16, 2 * i);
                    }
                    bulk_commit();
                }
                bulk_wait0();
                fence_async_global();
                red_release(&g_cnt[(40 + dt) * 32], 4);
                mbar_arrive(bar_kvrel);
                STAMP(0, 23);
                mbar_expect_tx(bar_tab, 12288);
                bulk_load(sbase + OFF_CT, &g_conv_tab, 12288, bar_tab);
                mbar_expect_tx(bar_k, 16384);
                tma_load_4d(sbase + conv_buf(0) + 8192, &maps.sk, bar_k, 0, 0, 0, bid * 8);
                tma_load_4d(sbase + conv_buf(0) + 12288, &maps.sk, bar_k, 0, 0, 0, bid * 8 + 1);
                wait_counter(&g_cnt[(40 + (bid >> 4)) * 32], target);
                STAMP(0, 19);
#pragma unroll 1
                for (int p = 0; p < 3; ++p) {
                    if (p == 1) mbar_wait(bar_adone, 0);
                    if (p == ULATE) mbar_wait(bar_rel, 0);
                    bulk_load(sbase + conv_buf(p), g_kvT + (size_t)(bid * 8 + 2 * p) * 2048, 8192, bar_k + 8 * p);
                    if (GAP_CV) __nanosleep(GAP_CV);
                }
                prefetch_map(&maps.out); prefetch_map(&maps.yt);
#pragma unroll 1
                for (int p = 0; p < 4; ++p) {
                    mbar_wait(bar_stg + 16 + 8 * p, 0);
                    if (p == 0) {
                        mbar_expect_tx(bar_k + 24, 16384);
                        tma_load_4d(sbase + conv_buf(3) + 8192, &maps.sk, bar_k + 24, 0, 0, 0, bid * 8 + 6);
                        mbar_wait(bar_g2, 0);
                        tma_load_4d(sbase + conv_buf(3) + 12288, &maps.sk, bar_k + 24, 0, 0, 0, bid * 8 + 7);
                    }
#pragma unroll 1
                    for (int i = 0; i < 2; ++i) {
                        if (i) __nanosleep(GAP_Y);
                        asm volatile("cp.async.bulk.global.shared::cta.bulk_group [%0], [%1], 4096;"
                                     ::"l"(g_y2 + (size_t)(bid * 8 + 2 * p + i) * 2048), "r"(sbase + conv_buf(p) + i * 4096) : "memory");
                    }
                    bulk_commit();
                    STAMP(0, 24 + p);
                    if (p == 0) {
                        bulk_wait_read0();
                        bulk_load(sbase + conv_buf(3), g_kvT + (size_t)(bid * 8 + 6) * 2048, 8192, bar_k + 24);
                    }
                    if (p == 2) {
                        bulk_wait0();
                        fence_async_global();
                        red_release(&g_cnt[(48 + (bid >> 4)) * 32], 4);
                        mbar_arrive(bar_yrel);
                        STAMP(0, 3);
                    }
                }
                bulk_wait0();
                fence_async_global();
                red_release(&g_cnt[(32 + (bid >> 4)) * 32], 4);
                STAMP(0, 2);
                wait_counter(&g_cnt[(32 + dt) * 32], target);
                STAMP(0, 5);
                mbar_expect_tx(bar_y, 8192);
                tma_load_5d(sbase + OFF_CU + 24576, &maps.yt, bar_y, (tt & 1) * 1024 + ti * 128, 0, 0, 3, dt * 4);
                tma_load_5d(sbase + OFF_CU + 28672, &maps.yt, bar_y, (tt & 1) * 1024 + ti * 128 + 64, 0, 0, 3, dt * 4);
#pragma unroll 1
                for (int i = 0; i < 8; ++i) {
                    mbar_wait(bar_stg + 48 + 8 * i, 0);
                    tma_store_5d(&maps.out, sbase + ((i & 4) ? OFF_CT : OFF_CU) + (i & 3) * 8192, dt * 128 + (i & 3) * 32, 0, 0, (tt & 1) * 4 + ((i & 4) >> 1), ti);
                    bulk_commit();
                }
                bulk_wait_read0();
                STAMP(2, 3);
                SAMPLE(21);
            }
        } else if (lane == 0) {
            mbar_wait(bar_tick + 8 * TK_PF0, 0);
#pragma unroll 1
            for (int i = 0; i < 8; ++i) {
                l2_prefetch(((i & 1) ? vin : kin) + (size_t)(ti * 256 + 32 * (i & 4) + (bid & 15) * 8 + 2 * (i & 2)) * D_DIM, 8192);
                __nanosleep(GAP_PF);
            }
            if (bid < 3) l2_prefetch(reinterpret_cast<const char*>(&g_conv_tab) + bid * 4096, 4096);
            prefetch_map(&maps.cre); prefetch_map(&maps.cim);
            mbar_wait(bar_tick + 8 * TK_C, 0);
#pragma unroll 1
            for (int i = 0; i < 8; ++i) {
                l2_prefetch((i & 1) ? ((i & 4) ? c_im : c_re) + (size_t)bid * 8192 + (i & 2) * 2048 : ssm_k + (size_t)bid * 16384 + (i >> 1) * 4096, 8192);
                __nanosleep(GAP_PF);
            }
            const unsigned int target = (ld_relaxed(&g_cnt[(4 * ti + 1) * 32]) & ~63u) + 64u;
            mbar_wait(bar_gate, 0);
#pragma unroll 1
            for (int q = 1; q < 4; ++q) {
                if (q < 3) mbar_wait(bar_hw + 8 * q, 0);
                if (q > 1) {
                    mbar_wait(bar_g2, 0);
                    char* hp = reinterpret_cast<char*>(g_H) + (size_t)((16 + 2 * ti) * 16 + (q & 1) * 8 + (cg >> 1)) * 16384 + (cg & 1) * 2048;
#pragma unroll 1
                    for (int i = 0; i < 8; ++i) {
                        asm volatile("cp.async.bulk.global.shared::cta.bulk_group [%0], [%1], 2048;"
                                     ::"l"(hp + (i & 3) * 4096 + (i >> 2) * 262144), "r"(sbase + OFF_BB + (q & 1) * 16384 + i * 2048) : "memory");
                        __nanosleep(GAP_HB);
                    }
                    bulk_commit();
                    if (q == 3) {
                        wait_counter(&g_cnt[(4 * ti + 2) * 32], target);
                        mbar_arrive(bar_fh + 8);
                    }
                    bulk_wait0();
                    if (q == 3) mbar_arrive(bar_empty2 + 32);
                    fence_async_global();
                }
                red_release(&g_cnt[(4 * ti + q) * 32], 4);
                STAMP(0, 36 + q);
                if (q != 2) {
                    wait_counter(&g_cnt[(4 * ti + q) * 32], target);
                    mbar_arrive(bar_fh + 8 * q - 8);
                }
            }
        }
    } else if (wg == 3) {
        asm volatile("setmaxnreg.inc.sync.aligned.u32 %0;" ::"n"(REG_C));
        const int t = tid & 127, w4 = t >> 5;
        mbar_wait(bar_tick, 0);
        if (t < 64) {
            const int ch = (t >> 5) * 512 + cg * 32 + (t & 31);
            unsigned long long oldagg;
            asm volatile("ld.relaxed.gpu.global.u64 %0, [%1];" : "=l"(oldagg) : "l"(&g_agg[ti * D_DIM + ch]) : "memory");
            const float Lr = __bfloat162float(lam_re[ch]), Li = __bfloat162float(lam_im[ch]);
            const float dtv = bf16r(expf(__bfloat162float(log_dt[ch])));
            const unsigned int tag = ((((unsigned int)oldagg & 1u) | ((unsigned int)(oldagg >> 31) & 2u)) + 1u) & 3u;
            const float er = expf(dtv * Lr);
            float s, c;
            sincosf(dtv * Li, &s, &c);
            const float lr = er * c, li = er * s;
            const float nr = lr - 1.f, ni = li;
            const float den = Lr * Lr + Li * Li;
            const float cr = 2.f * (nr * Lr + ni * Li) / den, ci = 2.f * (ni * Lr - nr * Li) / den;
            float pr = lr, pi = -li;
#pragma unroll
            for (int i = 0; i < 5; ++i) csqr(pr, pi);
            sts128(sbase + OFF_PAR + t * 32, __float_as_uint(lr), __float_as_uint(-li), __float_as_uint(cr), __float_as_uint(ci));
            sts128(sbase + OFF_PAR + t * 32 + 16, __float_as_uint(pr), __float_as_uint(pi), tag, 0);
            __syncwarp();
            if (lane == 0) mbar_arrive(bar_par);
        }
        if (t >= 120) asm volatile("st.shared.b32 [%0], %1;" ::"r"(w_dsk - 480 + 4 * t),
                                   "r"(t < 124 ? __ldg(reinterpret_cast<const uint32_t*>(ssm_D + bid * 8) + (t & 3)) : 0u) : "memory");
        if (t < 64) asm volatile("st.shared.b32 [%0], %1;" ::"r"(w_ones + 4 * t), "r"(0x3F803F80u) : "memory");
        {
            const int cq = lane & 15, rg = (lane >> 4) + 2 * w4;
            uint32_t sk[4][4];
#pragma unroll
            for (int c = 0; c < 4; ++c) {
                const uint4 w = ldg128(shift_k + (size_t)(dt * 128 + 8 * cq + 2 * c) * 4);
                sk[0][c] = __byte_perm(w.x, w.z, 0x5410); sk[1][c] = __byte_perm(w.x, w.z, 0x7632);
                sk[2][c] = __byte_perm(w.y, w.w, 0x5410); sk[3][c] = __byte_perm(w.y, w.w, 0x7632);
            }
#pragma unroll 1
            for (int bt = 0; bt < 2; ++bt) {
                const int t0 = ti * 256 + 128 * bt + 16 * (rg & 4) + 32 * (tt & 1) + 8 * (rg & 3);
                mbar_wait(bar_tick + 8 * (bt ? TK_KV1 : TK_KV0), 0);
                if (t == 0) STAMP(0, 30 + 3 * bt);
                uint4 kk[11], vv[8];
                const __nv_bfloat16* kp = kin + (size_t)t0 * D_DIM + dt * 128 + 8 * cq;
                const __nv_bfloat16* vp = vin + (size_t)t0 * D_DIM + dt * 128 + 8 * cq;
#pragma unroll
                for (int i = 0; i < 11; ++i) {
                    if (i < 3 && t0 == 0) kk[i] = make_uint4(0, 0, 0, 0);
                    else kk[i] = ldg128(kp + (i - 3) * D_DIM);
                    if (KVFINE ? (i & 1) : (i == 6 || i == 10)) __nanosleep(GAP_KV);
                }
#pragma unroll
                for (int i = 0; i < 8; ++i) { vv[i] = ldg128(vp + i * D_DIM); if (KVFINE ? !(i & 1) : i == 3) __nanosleep(GAP_KV); }
                const uint32_t ua = sbase + OFF_CT + bt * 16384 + cq * 128 + ((rg ^ ((2 * ti + bt) & 3) ^ (cq & 7)) << 4);
#pragma unroll
                for (int c = 0; c < 4; ++c) {
                    uint32_t res[8];
#pragma unroll
                    for (int i = 0; i < 8; ++i) {
                        uint32_t ks = hmul((&kk[i].x)[c], sk[3][c]);
                        if (KVFMA) {
                            ks = hfma((&kk[i + 1].x)[c], sk[2][c], ks);
                            ks = hfma((&kk[i + 2].x)[c], sk[1][c], ks);
                            ks = hfma((&kk[i + 3].x)[c], sk[0][c], ks);
                        } else {
                            ks = hadd(ks, hmul((&kk[i + 1].x)[c], sk[2][c]));
                            ks = hadd(ks, hmul((&kk[i + 2].x)[c], sk[1][c]));
                            ks = hadd(ks, hmul((&kk[i + 3].x)[c], sk[0][c]));
                        }
                        res[i] = hmul(ks, (&vv[i].x)[c]);
                    }
                    sts128(ua + (2 * c) * 2048, __byte_perm(res[0], res[1], 0x5410), __byte_perm(res[2], res[3], 0x5410),
                           __byte_perm(res[4], res[5], 0x5410), __byte_perm(res[6], res[7], 0x5410));
                    sts128(ua + (2 * c + 1) * 2048, __byte_perm(res[0], res[1], 0x7632), __byte_perm(res[2], res[3], 0x7632),
                           __byte_perm(res[4], res[5], 0x7632), __byte_perm(res[6], res[7], 0x7632));
                }
                fence_async_smem();
                __syncwarp();
                if (lane == 0) mbar_arrive(bar_stg + 8 * bt);
                if (t == 0) STAMP(0, 21 + bt);
            }
        }
        {
            const int row = bid * 16 + (t >> 3);
            if (GWAIT) mbar_wait(bar_kvrel, 0);
            uint4 xv[16];
#pragma unroll
            for (int n = 0; n < 16; ++n) {
                xv[n] = ldg128(x + (size_t)row * D_DIM + ((t & 7) + 8 * n) * 8);
                if (KVFINE ? (n & 1) : (n & 3) == 3) __nanosleep(GAP_KV);
            }
#pragma unroll
            for (int n8 = 0; n8 < 16; n8 += 8) {
                uint4 wv[8];
#pragma unroll
                for (int n = 0; n < 8; ++n) wv[n] = ldg128(gate_w + ((t & 7) + 8 * (n8 + n)) * 8);
#pragma unroll
                for (int n = 0; n < 8; ++n) {
                    uint4& p = xv[n8 + n];
                    p.x = hmul(p.x, wv[n].x); p.y = hmul(p.y, wv[n].y); p.z = hmul(p.z, wv[n].z); p.w = hmul(p.w, wv[n].w);
                }
            }
            float d[4] = {0.f, 0.f, 0.f, 0.f};
            fence_regs(d);
            named_bar(3, 128);
            wgmma_fence();
#pragma unroll
            for (int n = 0; n < 16; ++n)
                asm volatile("{\n.reg .b64 db;\nmov.b64 db, {%8, 8};\n"
                             "wgmma.mma_async.sync.aligned.m64n8k16.f32.bf16.bf16 {%0, %1, %2, %3}, {%4, %5, %6, %7}, db, 1, 1, 1, 0;\n}\n"
                             : "+f"(d[0]), "+f"(d[1]), "+f"(d[2]), "+f"(d[3]) : "r"(xv[n].x), "r"(xv[n].y), "r"(xv[n].z), "r"(xv[n].w), "r"(desc_lo(w_ones, 128)));
            wgmma_commit();
            wgmma_wait<0>();
            fence_regs(d);
#pragma unroll
            for (int n = 0; n < 16; ++n) asm volatile("" ::"r"(xv[n].x), "r"(xv[n].y), "r"(xv[n].z), "r"(xv[n].w) : "memory");
            float sum = d[0] + d[2];
            sum += __shfl_xor_sync(0xffffffffu, sum, 4);
            if ((t & 7) == 0) g_gate[row] = bf16r(1.f / (1.f + expf(-bf16r(sum))));
            if (t == 0) STAMP(0, 4);
            __syncwarp();
            if (lane == 0) mbar_arrive(bar_gate);
        }
        Twiddle tw;
        load_twiddle(tw, reinterpret_cast<const uint4*>(g_tw_tab.w) + t);
        const uint32_t lo = (uint32_t)((16 * w4 + (lane & 7)) * 64 + (((lane >> 3) ^ ((lane >> 1) & 3)) << 4));
        const uint32_t tlo = desc_lo(sbase + OFF_CT, 16);
        float dE[32], dO[32];
        mbar_wait(bar_tab, 0);
        mbar_wait(bar_k, 0);
        if (CWAIT) mbar_wait(bar_ascan, 0);
        if (t == 0) STAMP(0, 1);
        wgmma_fence();
        conv_s1(dE, dO, tlo, desc_lo(sbase + conv_buf(0), 8192));
        wgmma_commit();
        wgmma_wait<0>();
        fence_regs(dE); fence_regs(dO);
        named_bar(3, 128);
#pragma unroll 1
        for (int p = 0; p < 4; p = 2 * p + 1) {
            const int pn = min(2 * p + 1, 3);
            if (t == 0) STAMP(0, 40 + 5 * p);
            conv_pair<true>(dE, dO, tw, lds32(w_dsk + ((lane & 3) ? 16 : 4 * p)), tlo, sbase + conv_buf(0) + (p == 1 ? 16384 : 0),
                            sbase + conv_buf(0) + (p == 0 ? 16384 : 0), lo, 3,
                            [&]() { if (t == 0) STAMP(0, 42 + 5 * p); mbar_wait(bar_k + 8 * pn, 0); if (t == 0) STAMP(0, 43 + 5 * p); });
            if (lane == 0) mbar_arrive(bar_stg + 16 + 8 * p);
        }
        if (t == 0) STAMP(0, 59);
        __syncwarp();
    } else {
        asm volatile("setmaxnreg.inc.sync.aligned.u32 %0;" ::"n"(REG_AB));
        const int cw = wg - 1;
        const int t = tid & 127, w4 = t >> 5, g = lane >> 2, t4 = lane & 3;
        {
            float a0[64], a1[64];
            auto release = [&](int it) {
                if (it < 12 + XTRA && t <= ((it >= 16 - SKEW1 && it < 12) || it >= 16)) mbar_arrive(bar_empty + 8 * (it & 3));
            };
#pragma unroll 1
            for (int kb = 0; kb < 16; ++kb) {
                const int it = cw == 1 && kb >= 16 - SKEW1 ? kb + XTRA : kb, st = it & 3;
                if (cw == 1 && kb == 16 - SKEW1) mbar_wait(bar_ab, 0);
                mbar_wait(bar_full + 8 * st, (it >> 2) & 1);
                if (kb == 0 && t == 0) STAMP(1, 14 + cw);
                const uint32_t alo = desc_lo(sbase + (cw ? OFF_BB : OFF_CU) + st * 8192, 16), blo = desc_lo(sbase + ((it - XTRA) & 3) * 32768, 16);
                wgmma_fence();
#pragma unroll
                for (int k = 0; k < 4; ++k) {
                    wgmma_n128<0>(a0, alo + 2 * k, blo + 2 * k, k ? 1 : kb);
                    if (!G1ORD) wgmma_n128<0>(a1, alo + 2 * k, blo + 1024 + 2 * k, k ? 1 : kb);
                }
                if (G1ORD) {
#pragma unroll
                    for (int k = 0; k < 4; ++k) wgmma_n128<0>(a1, alo + 2 * k, blo + 1024 + 2 * k, k ? 1 : kb);
                }
                wgmma_commit();
                wgmma_wait<1>();
                if (kb > 0 && !(cw == 1 && kb == 16 - SKEW1)) release(it - 1);
                if (cw == 1 && kb == 15 - SKEW1) {
                    wgmma_wait<0>();
                    release(it);
                }
                if (cw == 1 && kb > 12) {
                    if (kb == 13) mbar_wait(bar_adone, 0);
                    if (t == 0) mbar_arrive(bar_empty2 + 8 * (kb - 13));
                }
            }
            if (tid == 192) mbar_arrive(bar_ab);
            float mr, mi, cr, ci, p32r, p32i;
            uint32_t tag;
            mbar_wait(bar_par, 0);
            {
                const uint32_t par = sbase + OFF_PAR + (cw * 32 + w4 * 8 + g) * 32;
                uint32_t dummy;
                asm volatile("ld.shared.v4.f32 {%0,%1,%2,%3}, [%4];" : "=f"(mr), "=f"(mi), "=f"(cr), "=f"(ci) : "r"(par));
                asm volatile("ld.shared.v4.b32 {%0,%1,%2,%3}, [%4];" : "=f"(p32r), "=f"(p32i), "=r"(tag), "=r"(dummy) : "r"(par + 16));
            }
            const float l1i = SW ? mi : -mi;
            auto map = [&](float p, float q, float& r, float& i) {
                if (SW) { r = fmaf(cr, q, -ci * p); i = fmaf(-cr, p, -ci * q); }
                else { r = fmaf(cr, p, -ci * q); i = fmaf(-cr, q, -ci * p); }
            };
            float p64r = p32r, p64i = p32i;
            csqr(p64r, p64i);
            float p128r = p64r, p128i = p64i;
            csqr(p128r, p128i);
            wgmma_wait<0>();
            fence_regs(a0); fence_regs(a1);
            if (cw == 0) { release(15); if (lane == 0) mbar_arrive(bar_adone); }
            else if (t == 0) mbar_arrive(bar_empty2 + 24);
            if (t == 0) STAMP(1, 2 + 6 * cw);
            float hr = 0.f, hi = 0.f, ar = 0.f, ai = 0.f;
#pragma unroll
            for (int j = 0; j < 16; ++j)
#pragma unroll
                for (int e = 0; e < 2; ++e) {
                    const float nr = fmaf(mr, ar, fmaf(-l1i, ai, a0[4 * j + e])), ni = fmaf(mr, ai, fmaf(l1i, ar, a0[4 * j + 2 + e]));
                    const float or_ = fmaf(mr, hr, fmaf(-l1i, hi, a1[4 * j + e])), oi = fmaf(mr, hi, fmaf(l1i, hr, a1[2 + 4 * j + e]));
                    ar = nr; ai = ni; hr = or_; hi = oi;
                }
            map(ar, ai, ar, ai);
            map(hr, hi, hr, hi);
            hr += p32r * ar - p32i * ai; hi += p32r * ai + p32i * ar;
            {
                float vr = __shfl_up_sync(0xffffffffu, hr, 1, 4), vi = __shfl_up_sync(0xffffffffu, hi, 1, 4);
                if (t4 >= 1) { hr += p64r * vr - p64i * vi; hi += p64r * vi + p64i * vr; }
                vr = __shfl_up_sync(0xffffffffu, hr, 2, 4); vi = __shfl_up_sync(0xffffffffu, hi, 2, 4);
                if (t4 >= 2) { hr += p128r * vr - p128i * vi; hi += p128r * vi + p128i * vr; }
            }
            unsigned long long* ap = &g_agg[ti * D_DIM + cw * 512 + cg * 32 + w4 * 8 + g];
            if (t4 == 3) asm volatile("{\n.reg .b64 a;\nmov.b64 a, {%1, %2};\nst.relaxed.gpu.global.u64 [%0], a;\n}\n" ::"l"(ap),
                                      "r"((__float_as_uint(hr) & ~1u) | (tag & 1u)), "r"((__float_as_uint(hi) & ~1u) | (tag >> 1)) : "memory");
            float exr = __shfl_up_sync(0xffffffffu, hr, 1, 4), exi = __shfl_up_sync(0xffffffffu, hi, 1, 4);
            if (t4 == 0) { exr = 0.f; exi = 0.f; }
            if (t == 0) STAMP(1, 3 + 6 * cw);
            ci = after(ci, exr);
#pragma unroll
            for (int j = 0; j < 16; ++j)
#pragma unroll
                for (int e = 0; e < 2; ++e) {
                    map(a0[4 * j + e], a0[4 * j + 2 + e], a0[4 * j + e], a0[4 * j + 2 + e]);
                    map(a1[4 * j + e], a1[4 * j + 2 + e], a1[4 * j + e], a1[4 * j + 2 + e]);
                }
            float qr = 1.f, qi = 0.f, ur = 1.f, ui = 0.f;
            if (t4 & 1) { qr = p64r; qi = p64i; }
            if (t4 & 2) cmul(qr, qi, qr, qi, p128r, p128i);
            csqr(p128r, p128i);
            if (t4 & 1) { ur = p128r; ui = p128i; }
            csqr(p128r, p128i);
            if (t4 & 2) cmul(ur, ui, ur, ui, p128r, p128i);
            csqr(p128r, p128i);
            fence_regs(a0); fence_regs(a1);
            if (t == 0) STAMP(1, 7 + 6 * cw);
            if (ti > 0) {
                const unsigned long long tmask = 0x0000000100000001ull, tval = ((unsigned long long)(tag >> 1) << 32) | (tag & 1u);
                unsigned long long u0 = tval, u1 = tval;
                ap -= D_DIM * (1 + t4);
                int it = 0;
                do {
                    asm volatile("{\n.reg .pred p, q;\nsetp.gt.s32 p, %3, 0;\nsetp.gt.s32 q, %3, 4;\n@p ld.relaxed.gpu.global.u64 %0, [%2];\n"
                                 "@q ld.relaxed.gpu.global.u64 %1, [%2+-32768];\n}\n" : "+l"(u0), "+l"(u1) : "l"(ap), "r"(ti - t4) : "memory");
                } while (__any_sync(0xffffffffu, (((u0 ^ tval) | (u1 ^ tval)) & tmask) != 0) && ++it < (1 << 22));
                float Pr = __uint_as_float((unsigned)u1 & ~1u), Pi = __uint_as_float((unsigned)(u1 >> 32) & ~1u);
                cmul(Pr, Pi, Pr, Pi, p128r, p128i);
                Pr += __uint_as_float((unsigned)u0 & ~1u); Pi += __uint_as_float((unsigned)(u0 >> 32) & ~1u);
                cmul(Pr, Pi, Pr, Pi, ur, ui);
                Pr += __shfl_xor_sync(0xffffffffu, Pr, 1); Pi += __shfl_xor_sync(0xffffffffu, Pi, 1);
                Pr += __shfl_xor_sync(0xffffffffu, Pr, 2); Pi += __shfl_xor_sync(0xffffffffu, Pi, 2);
                exr += qr * Pr - qi * Pi;
                exi += qr * Pi + qi * Pr;
            }
            if (t == 0) STAMP(1, 4 + 6 * cw);
            char* hp = reinterpret_cast<char*>(g_H) + (size_t)((2 * ti) * 16 + (cg >> 1)) * 16384 + ((cg & 1) * 32 + w4 * 8 + g) * 64 + ((t4 ^ (g >> 1)) << 4);
            float fxr = ar + p32r * exr - p32i * exi, fxi = ai + p32r * exi + p32i * exr;
            const uint32_t hs = sbase + OFF_BB + (w4 * 8 + g) * 64 + ((t4 ^ (g >> 1)) << 4);
            if (cw == 1) named_bar(2, 128);
            uint32_t im[32];
#pragma unroll
            for (int jj = 0; jj < 4; ++jj) {
                uint32_t pr[4], qq[4];
#pragma unroll
                for (int j4 = 0; j4 < 4; ++j4) {
                    const int j = jj * 4 + j4;
                    const float r0 = fmaf(mr, exr, fmaf(-mi, exi, a0[4 * j])), i0 = fmaf(mr, exi, fmaf(mi, exr, a0[4 * j + 2]));
                    const float r1 = fmaf(mr, fxr, fmaf(-mi, fxi, a1[4 * j])), i1 = fmaf(mr, fxi, fmaf(mi, fxr, a1[2 + 4 * j]));
                    exr = fmaf(mr, r0, fmaf(-mi, i0, a0[4 * j + 1]));
                    exi = fmaf(mr, i0, fmaf(mi, r0, a0[4 * j + 3]));
                    fxr = fmaf(mr, r1, fmaf(-mi, i1, a1[1 + 4 * j]));
                    fxi = fmaf(mr, i1, fmaf(mi, r1, a1[3 + 4 * j]));
                    pr[j4] = pack_bf16(r0, exr); im[j] = pack_bf16(i0, exi);
                    qq[j4] = pack_bf16(r1, fxr); im[16 + j] = pack_bf16(i1, fxi);
                }
                if (cw == 0) {
                    stg128(hp + jj * 4096, pr[0], pr[1], pr[2], pr[3]);
                    stg128(hp + jj * 4096 + 262144, qq[0], qq[1], qq[2], qq[3]);
                } else {
                    sts128(hs + jj * 2048, pr[0], pr[1], pr[2], pr[3]);
                    sts128(hs + jj * 2048 + 8192, qq[0], qq[1], qq[2], qq[3]);
                }
            }
            if (t == 0) STAMP(1, 5 + 6 * cw);
            if (cw == 0) {
                if (lane == 0) mbar_arrive(bar_ascan);
                named_bar(1, 128);
                if (t == 0) { red_release(&g_cnt[(4 * ti) * 32], 4); mbar_arrive(bar_rel); }
                named_bar(1, 128);
                if (t == 0) STAMP(1, 6);
#pragma unroll
                for (int jj = 0; jj < 8; ++jj) stg128(hp + 131072 + (jj & 3) * 4096 + (jj >> 2) * 262144, im[4 * jj], im[4 * jj + 1], im[4 * jj + 2], im[4 * jj + 3]);
            } else {
#pragma unroll
                for (int jj = 0; jj < 8; ++jj) sts128(hs + 16384 + jj * 2048, im[4 * jj], im[4 * jj + 1], im[4 * jj + 2], im[4 * jj + 3]);
                fence_async_smem();
            }
            __syncwarp();
            if (lane == 0) mbar_arrive(bar_hw + 8 * cw + 8);
            if (t == 0) STAMP(1, 50 + cw);
        }
        if (cw == 1) {
            const int t = fresh_tid() & 127, lane = t & 31, w4 = t >> 5;
            Twiddle tw;
            load_twiddle(tw, reinterpret_cast<const uint4*>(g_tw_tab.w) + t);
            const uint32_t lo = (uint32_t)((16 * w4 + (lane & 7)) * 64 + (((lane >> 3) ^ ((lane >> 1) & 3)) << 4));
            const uint32_t tlo = desc_lo(sbase + OFF_CT, 16);
            float dE[32], dO[32];
            mbar_wait(bar_stg, 0);
            mbar_wait(bar_tab, 0);
            mbar_wait(bar_k + 16, 0);
            if (t == 0) STAMP(0, 50);
            wgmma_fence();
            conv_s1(dE, dO, tlo, desc_lo(sbase + conv_buf(2), 8192));
            wgmma_commit();
            wgmma_wait<0>();
            fence_regs(dE); fence_regs(dO);
            named_bar(2, 128);
            conv_pair<false>(dE, dO, tw, lds32(w_dsk + ((lane & 3) ? 16 : 8)), tlo, sbase + conv_buf(2), 0, lo, 2, []() {});
            if (lane == 0) mbar_arrive(bar_stg + 32);
            {
            const int t = fresh_tid() & 127, lane = t & 31, w4 = t >> 5, g = lane >> 2, t4 = lane & 3;
            const int bid = lds32(w_bid), dt = bid & 7;
            const int trow = (bid >> 4) * 256 + 4 * (bid & 8) + 128 * (w4 & 1) + 8 * (w4 >> 1) + g;
            uint4 xv[16], dk[4];
            const __nv_bfloat16* xp = x + (size_t)trow * D_DIM + dt * 128 + 8 * t4;
#pragma unroll
            for (int i = 0; i < 16; ++i) {
                xv[i] = ldg128(xp + (size_t)(16 * (i >> 3) + 64 * ((i >> 2) & 1)) * D_DIM + 32 * (i & 3));
                if (i & 1) __nanosleep(GAP_X);
            }
#pragma unroll
            for (int jq = 0; jq < 4; ++jq) dk[jq] = ldg128(dskip + dt * 128 + 32 * jq + 8 * t4);
            mbar_wait(bar_fh, 0);
            uint32_t omg[4], g2[4];
#pragma unroll
            for (int i = 0; i < 4; ++i) {
                const float gt = __ldcg(g_gate + trow + 16 * (i >> 1) + 64 * (i & 1));
                if (t4 == 0) asm volatile("st.shared.f32 [%0], %1;" ::"r"(sbase + OFF_PAR + (64 * (i >> 1) + 16 * w4 + 8 * (i & 1) + g) * 4), "f"(gt) : "memory");
                omg[i] = pack_bf16(2.f - 2.f * gt, 2.f - 2.f * gt); g2[i] = pack_bf16(gt, gt);
            }
            if (t == 0) {
                mbar_wait(bar_yrel, 0);
                wait_counter(&g_cnt[(48 + dt) * 32], lds32(w_bid + 4));
                STAMP(0, 16);
                mbar_expect_tx(bar_y1, 24576);
#pragma unroll 1
                for (int i = 0; i < 6; ++i) {
                    tma_load_5d(sbase + OFF_CU + i * 4096, &maps.yt, bar_y1, (bid & 8) * 128 + (bid >> 4) * 128 + (i & 1) * 64, 0, 0, i >> 1, dt * 4);
                    if (GAP_Y1) __nanosleep(GAP_Y1);
                }
            }
            __syncwarp();
            const uint32_t ya = sbase + OFF_CU + (w4 & 1) * 4096 + lane * 128 + ((((w4 >> 1) ^ ((bid >> 3 & 2) + (w4 & 1))) ^ (lane & 7)) << 4);
#pragma unroll
            for (int p = 0; p < 4; ++p) {
                if (p == 0) mbar_wait(bar_y1, 0);
                if (p == 3) {
                    if (t == 0) STAMP(0, 17);
                    mbar_wait(bar_y, 0);
                    if (t == 0) STAMP(0, 6);
                }
#pragma unroll
                for (int i = 0; i < 4; ++i) {
                    uint32_t yw[4];
                    ldsm_x4_t(yw[0], yw[1], yw[2], yw[3], (ya ^ ((i & 1) << 6) ^ ((i & 2) << 4)) + p * 8192);
#pragma unroll
                    for (int jq = 0; jq < 4; ++jq) {
                        uint32_t& w = (&xv[4 * i + jq].x)[p];
                        w = hfma(g2[i], hmul(w, (&dk[jq].x)[p]), hmul(omg[i], hmul(w, yw[jq])));
                    }
                }
            }
            named_bar(2, 128);
#pragma unroll
            for (int i = 0; i < 16; ++i) {
                sts128(sbase + (i & 8 ? OFF_CT : OFF_CU) + (i & 3) * 8192 + (w4 * 16 + g + (i & 4) * 2) * 128 + (((2 * t4) ^ g) << 4), xv[i].x, xv[i].y, xv[i].z, xv[i].w);
                if ((i & 7) == 7) {
                    __syncwarp();
                    if (lane == 0) mbar_arrive(bar_bias + (i & 8));
                }
            }
            if (t == 0) STAMP(0, 7);
            }
        }
        if (cw == 0) {
            float c0[64], c1[64];
            int st = 0, pst = 0;
            uint32_t ph = 0;
            auto kblock = [&](int kb, auto shallow) {
                const int t = fresh_tid() & 127, lane = t & 31;
                mbar_wait(bar_full2 + 8 * st, st == 4 ? ph ^ PH4 : ph);
                if (kb == 0 && t == 0) STAMP(2, 6);
                if (kb == G2SIG && lane == 0) mbar_arrive(bar_g2);
                const uint32_t alo = desc_lo(sbase + st * 32768, 4096), blo = desc_lo(sbase + st * 32768 + 16384, 16);
                constexpr int Q = decltype(shallow)::value;
#pragma unroll
                for (int j = 0; j < 8; ++j) {
                    wgmma_fence();
                    if (j & 1) wgmma_n128<1>(c1, alo + 512 + 64 * (j >> 1), blo + 2 * (j >> 1), j >> 1 ? 1 : kb);
                    else wgmma_n128<1>(c0, alo + 64 * (j >> 1), blo + 2 * (j >> 1), j >> 1 ? 1 : kb);
                    wgmma_commit();
                    wgmma_wait<Q>();
                    if (j == Q - 1 && kb > 0 && t == 0) mbar_arrive(bar_empty2 + 8 * pst);
                }
                pst = st;
                if (++st == (kb < SLOT4 - 1 ? 4 : 5)) { st = 0; ph ^= 1; }
            };
#pragma unroll 1
            for (int kb = 0; kb < QKB; ++kb) kblock(kb, std::integral_constant<int, QD>());
#pragma unroll 1
            for (int kb = QKB; kb < 32 - SKEW2; ++kb) kblock(kb, std::integral_constant<int, QD2>());
            static_assert(SKEW2 <= 4, "slot release");
            const uint32_t alo = desc_lo(sbase, 4096), blo = desc_lo(sbase + 16384, 16);
#pragma unroll
            for (int kb = 32 - SKEW2; kb < 32; ++kb) {
                mbar_wait(bar_full2 + 8 * ring_slot(kb), ring_par(kb));
                wgmma_fence();
#pragma unroll
                for (int k = 0; k < 4; ++k) wgmma_n128<1>(c0, alo + ring_slot(kb) * 2048 + 64 * k, blo + ring_slot(kb) * 2048 + 2 * k, 1);
                wgmma_commit();
            }
            auto late = [&](int kb) {
                wgmma_fence();
#pragma unroll
                for (int k = 0; k < 4; ++k) wgmma_n128<1>(c1, alo + 512 + ring_slot(kb) * 2048 + 64 * k, blo + ring_slot(kb) * 2048 + 2 * k, 1);
                wgmma_commit();
            };
            late(32 - SKEW2);
            const int t = fresh_tid() & 127, lane = t & 31, w4 = t >> 5, g = lane >> 2, t4 = lane & 3;
            auto epilogue = [&](const float (&a)[64], int b) {
                const uint32_t ad0 = sbase + (b ? OFF_CT : OFF_CU) + (w4 * 16 + g) * 128 + (((2 * t4) ^ g) << 4);
                float gt[2];
                uint32_t bv[4][4];
#pragma unroll
                for (int h = 0; h < 2; ++h) gt[h] = __uint_as_float(lds32(sbase + OFF_PAR + (64 * b + 16 * w4 + 8 * h + g) * 4));
#pragma unroll
                for (int i = 0; i < 4; ++i)
                    asm volatile("ld.shared.v4.b32 {%0,%1,%2,%3}, [%4];" : "=r"(bv[i][0]), "=r"(bv[i][1]), "=r"(bv[i][2]), "=r"(bv[i][3])
                                 : "r"(ad0 + (i & 1) * 1024 + (i >> 1) * 8192) : "memory");
                if (b == 0) wgmma_wait<1>(); else wgmma_wait<0>();
                if (b == 0) fence_regs(c0); else fence_regs(c1);
                if (t == 0) STAMP(2, b ? 2 : 5);
#pragma unroll
                for (int jq = 0; jq < 4; ++jq) {
                    if (b == 0 && jq < SKEW2 - 1) late(33 - SKEW2 + jq);
#pragma unroll
                    for (int h = 0; h < 2; ++h) {
                        const uint32_t ad = ad0 + h * 1024 + jq * 8192;
                        uint32_t (&w)[4] = bv[2 * (jq & 1) + h];
                        const int r = 16 * jq + 2 * h;
                        sts128(ad, __float_as_uint(fmaf(gt[h], a[r], bf_lo(w[0]))), __float_as_uint(fmaf(gt[h], a[r + 1], bf_hi(w[0]))),
                               __float_as_uint(fmaf(gt[h], a[r + 4], bf_lo(w[1]))), __float_as_uint(fmaf(gt[h], a[r + 5], bf_hi(w[1]))));
                        sts128(ad ^ 16, __float_as_uint(fmaf(gt[h], a[r + 8], bf_lo(w[2]))), __float_as_uint(fmaf(gt[h], a[r + 9], bf_hi(w[2]))),
                               __float_as_uint(fmaf(gt[h], a[r + 12], bf_lo(w[3]))), __float_as_uint(fmaf(gt[h], a[r + 13], bf_hi(w[3]))));
                        if (jq < 2) asm volatile("ld.shared.v4.b32 {%0,%1,%2,%3}, [%4];" : "=r"(w[0]), "=r"(w[1]), "=r"(w[2]), "=r"(w[3]) : "r"(ad + 16384) : "memory");
                    }
                    fence_async_smem();
                    __syncwarp();
                    if (lane == 0) mbar_arrive(bar_stg + 48 + 32 * b + 8 * jq);
                }
            };
            mbar_wait(bar_bias, 0);
            if (t == 0) STAMP(2, 4);
            epilogue(c0, 0);
            mbar_wait(bar_bias + 8, 0);
            epilogue(c1, 1);
            if (t == 0) STAMP(2, 7);
        }
    }
}

void make_map(CUtensorMap* m, const void* ptr, int rank, const cuuint64_t* dims, const cuuint64_t* strides, const cuuint32_t* box,
              CUtensorMapSwizzle swz, bool f32 = false) {
    cuuint32_t es[5] = {1, 1, 1, 1, 1};
    get_encode()(m, f32 ? CU_TENSOR_MAP_DATA_TYPE_FLOAT32 : CU_TENSOR_MAP_DATA_TYPE_BFLOAT16, rank, const_cast<void*>(ptr), dims, strides, box, es,
                 CU_TENSOR_MAP_INTERLEAVE_NONE, swz, CU_TENSOR_MAP_L2_PROMOTION_L2_256B, CU_TENSOR_MAP_FLOAT_OOB_FILL_NONE);
}
void make_map_2d(CUtensorMap* m, const void* ptr, uint64_t inner, uint64_t outer, uint32_t box_in, uint32_t box_out) {
    cuuint64_t dims[2] = {inner, outer};
    cuuint64_t strides[1] = {inner * 2};
    cuuint32_t box[2] = {box_in, box_out};
    make_map(m, ptr, 2, dims, strides, box, CU_TENSOR_MAP_SWIZZLE_128B);
}
void make_map_conv(CUtensorMap* m, const void* p, uint32_t nch = 2) {
    cuuint64_t dims[4] = {32, 32, 2, 1024};
    cuuint64_t strides[3] = {128, 64, 4096};
    cuuint32_t box[4] = {32, 32, 2, nch};
    make_map(m, p, 4, dims, strides, box, CU_TENSOR_MAP_SWIZZLE_64B);
}

}

extern "C" void kernel_launch(void* const* d_in, const int* in_sizes, int n_in, void* d_out, int out_size) {
    const __nv_bfloat16* x = (const __nv_bfloat16*)d_in[0];
    const __nv_bfloat16* lam_re = (const __nv_bfloat16*)d_in[1];
    const __nv_bfloat16* lam_im = (const __nv_bfloat16*)d_in[2];
    const __nv_bfloat16* b_re = (const __nv_bfloat16*)d_in[3];
    const __nv_bfloat16* b_im = (const __nv_bfloat16*)d_in[4];
    const __nv_bfloat16* c_re = (const __nv_bfloat16*)d_in[5];
    const __nv_bfloat16* c_im = (const __nv_bfloat16*)d_in[6];
    const __nv_bfloat16* log_dt = (const __nv_bfloat16*)d_in[7];
    const __nv_bfloat16* dskip = (const __nv_bfloat16*)d_in[8];
    const __nv_bfloat16* kin = (const __nv_bfloat16*)d_in[10];
    const __nv_bfloat16* vin = (const __nv_bfloat16*)d_in[11];
    const __nv_bfloat16* shift_k = (const __nv_bfloat16*)d_in[12];
    const __nv_bfloat16* ssm_k = (const __nv_bfloat16*)d_in[13];
    const __nv_bfloat16* ssm_D = (const __nv_bfloat16*)d_in[14];
    const __nv_bfloat16* gate_w = (const __nv_bfloat16*)d_in[15];
    float* out = (float*)d_out;

    void *yptr = nullptr, *kvtptr = nullptr;
    cudaGetSymbolAddress(&yptr, g_y2);
    cudaGetSymbolAddress(&kvtptr, g_kvT);

    Maps maps;
    {
        cuuint64_t dims[5] = {1024, 2, 4, 32, 8};
        cuuint64_t strides[4] = {2048, 64 * 2048, 2 * 2048, 256 * 2048};
        cuuint32_t box[5] = {64, 2, 4, 32, 1};
        make_map(&maps.x5, x, 5, dims, strides, box, CU_TENSOR_MAP_SWIZZLE_128B);
    }
    int bmode = 0;
    {
        const uint64_t a = (uint64_t)b_re, b = (uint64_t)b_im;
        const uint64_t delta = a < b ? b - a : a - b;
        if (delta != 0 && (delta & 15) == 0 && delta < (1ull << 40)) bmode = a < b ? 1 : 2;
        cuuint64_t dims[4] = {1024, 8, 2, 128};
        cuuint64_t strides[3] = {2048, bmode ? delta : 16, 16384};
        cuuint32_t box[4] = {64, 8, 2, 4};
        make_map(&maps.b4, a < b ? b_re : b_im, 4, dims, strides, box, CU_TENSOR_MAP_SWIZZLE_128B);
    }
    make_map_2d(&maps.bre, b_re, 1024, 1024, 64, 8);
    make_map_2d(&maps.bim, b_im, 1024, 1024, 64, 8);
    {
        cuuint64_t dims[3] = {S_LEN, 128, 8};
        cuuint64_t strides[2] = {8 * 4096, 4096};
        cuuint32_t box[3] = {64, 16, 2};
        make_map(&maps.kvst, kvtptr, 3, dims, strides, box, CU_TENSOR_MAP_SWIZZLE_128B);
    }
    make_map_conv(&maps.sk, ssm_k, 1);
    for (int i = 0; i < 2; ++i) {
        cuuint64_t dims[5] = {1024, 2, 4, 4, 32};
        cuuint64_t strides[4] = {2048, 8 * 2048, 2 * 2048, 32 * 2048};
        cuuint32_t box[5] = {64, 2, 4, 4, 4};
        make_map(i ? &maps.cim : &maps.cre, i ? c_im : c_re, 5, dims, strides, box, CU_TENSOR_MAP_SWIZZLE_128B);
    }
    {
        cuuint64_t dims[5] = {S_LEN, 2, 4, 4, 32};
        cuuint64_t strides[4] = {4096, 8 * 4096, 2 * 4096, 32 * 4096};
        cuuint32_t box[5] = {64, 2, 4, 1, 4};
        make_map(&maps.yt, yptr, 5, dims, strides, box, CU_TENSOR_MAP_SWIZZLE_128B);
    }
    {
        cuuint64_t dims[5] = {D_DIM, 8, 4, 8, 8};
        cuuint64_t strides[4] = {4096, 64 * 4096, 8 * 4096, 256 * 4096};
        cuuint32_t box[5] = {32, 8, 4, 2, 1};
        make_map(&maps.out, out, 5, dims, strides, box, CU_TENSOR_MAP_SWIZZLE_128B, true);
    }

    auto kern = bmode == 1 ? fused_kernel<1> : bmode == 2 ? fused_kernel<2> : fused_kernel<0>;
    cudaFuncSetAttribute(kern, cudaFuncAttributeMaxDynamicSharedMemorySize, SMEM_BYTES);
    static int grid = 0;
    if (!grid) {
        int dev = 0, sms = 0;
        cudaGetDevice(&dev);
        cudaDeviceGetAttribute(&sms, cudaDevAttrMultiProcessorCount, dev);
        grid = sms == 132 ? 132 : 128;
    }
    kern<<<grid, 512, SMEM_BYTES>>>(x, kin, vin, ssm_k, shift_k, ssm_D, lam_re, lam_im, log_dt, gate_w, dskip, c_re, c_im, maps);
}
```

```cpp
#include <cuda_runtime.h>
#include <cuda_bf16.h>
#include <cuda.h>
#include <stdint.h>
#include <type_traits>

namespace {
__device__ __forceinline__ uint32_t smem_u32(const void* p) { return (uint32_t)__cvta_generic_to_shared(p); }
__device__ __forceinline__ void mbar_init(uint32_t bar, uint32_t count) {
    asm volatile("mbarrier.init.shared::cta.b64 [%0], %1;" ::"r"(bar), "r"(count) : "memory");
}
__device__ __forceinline__ void mbar_expect_tx(uint32_t bar, uint32_t bytes) {
    asm volatile("mbarrier.arrive.expect_tx.shared::cta.b64 _, [%0], %1;" ::"r"(bar), "r"(bytes) : "memory");
}
__device__ __forceinline__ void mbar_arrive(uint32_t bar) {
    asm volatile("mbarrier.arrive.shared::cta.b64 _, [%0];" ::"r"(bar) : "memory");
}
__device__ __forceinline__ void mbar_wait(uint32_t bar, uint32_t parity) {
    asm volatile(
        "{\n"
        ".reg .pred p;\n"
        ".reg .u32 n;\n"
        "mov.u32 n, 0;\n"
        "LAB_WAIT:\n"
        "mbarrier.try_wait.parity.shared::cta.b64 p, [%0], %1;\n"
        "@p bra LAB_DONE;\n"
        "add.u32 n, n, 1;\n"
        "setp.lt.u32 p, n, 0x400000;\n"
        "@p bra LAB_WAIT;\n"
        "trap;\n"
        "LAB_DONE:\n"
        "}\n" ::"r"(bar), "r"(parity) : "memory");
}
__device__ __forceinline__ void tma_load_2d(uint32_t dst, const CUtensorMap* map, uint32_t bar, int c0, int c1) {
    asm volatile(
        "cp.async.bulk.tensor.2d.shared::cluster.global.mbarrier::complete_tx::bytes [%0], [%1, {%3, %4}], [%2];"
        ::"r"(dst), "l"((uint64_t)map), "r"(bar), "r"(c0), "r"(c1) : "memory");
}
__device__ __forceinline__ void tma_load_4d(uint32_t dst, const CUtensorMap* map, uint32_t bar, int c0, int c1, int c2, int c3) {
    asm volatile(
        "cp.async.bulk.tensor.4d.shared::cluster.global.mbarrier::complete_tx::bytes [%0], [%1, {%3, %4, %5, %6}], [%2];"
        ::"r"(dst), "l"((uint64_t)map), "r"(bar), "r"(c0), "r"(c1), "r"(c2), "r"(c3) : "memory");
}
__device__ __forceinline__ void tma_load_5d(uint32_t dst, const CUtensorMap* map, uint32_t bar, int c0, int c1, int c2, int c3, int c4) {
    asm volatile(
        "cp.async.bulk.tensor.5d.shared::cluster.global.mbarrier::complete_tx::bytes [%0], [%1, {%3, %4, %5, %6, %7}], [%2];"
        ::"r"(dst), "l"((uint64_t)map), "r"(bar), "r"(c0), "r"(c1), "r"(c2), "r"(c3), "r"(c4) : "memory");
}
__device__ __forceinline__ void bulk_load(uint32_t dst, const void* src, uint32_t bytes, uint32_t bar) {
    asm volatile("cp.async.bulk.shared::cluster.global.mbarrier::complete_tx::bytes [%0], [%1], %2, [%3];"
                 ::"r"(dst), "l"(src), "r"(bytes), "r"(bar) : "memory");
}
__device__ __forceinline__ void tma_store_3d(const CUtensorMap* map, uint32_t src, int c0, int c1, int c2) {
    asm volatile("cp.async.bulk.tensor.3d.global.shared::cta.bulk_group [%0, {%2, %3, %4}], [%1];"
                 ::"l"((uint64_t)map), "r"(src), "r"(c0), "r"(c1), "r"(c2) : "memory");
}
__device__ __forceinline__ void bulk_commit() { asm volatile("cp.async.bulk.commit_group;" ::: "memory"); }
__device__ __forceinline__ void bulk_wait0() { asm volatile("cp.async.bulk.wait_group 0;" ::: "memory"); }
__device__ __forceinline__ void bulk_wait_read0() { asm volatile("cp.async.bulk.wait_group.read 0;" ::: "memory"); }
__device__ __forceinline__ void fence_async_smem() { asm volatile("fence.proxy.async.shared::cta;" ::: "memory"); }
__device__ __forceinline__ void named_bar(int id, int n) { asm volatile("bar.sync %0, %1;" ::"r"(id), "r"(n) : "memory"); }
__device__ __forceinline__ void sts128(uint32_t addr, uint32_t a, uint32_t b, uint32_t c, uint32_t d) {
    asm volatile("st.shared.v4.b32 [%0], {%1, %2, %3, %4};" ::"r"(addr), "r"(a), "r"(b), "r"(c), "r"(d) : "memory");
}
__device__ __forceinline__ void prefetch_map(const CUtensorMap* m) {
    asm volatile("prefetch.tensormap [%0];" ::"l"((uint64_t)m) : "memory");
}
__device__ __forceinline__ void wgmma_fence() { asm volatile("wgmma.fence.sync.aligned;" ::: "memory"); }
__device__ __forceinline__ void wgmma_commit() { asm volatile("wgmma.commit_group.sync.aligned;" ::: "memory"); }
template <int N>
__device__ __forceinline__ void wgmma_wait() { asm volatile("wgmma.wait_group.sync.aligned %0;" ::"n"(N) : "memory"); }
template <int N>
__device__ __forceinline__ void fence_regs(float (&a)[N]) {
#pragma unroll
    for (int i = 0; i < N; ++i) asm volatile("" : "+f"(a[i])::"memory");
}
template <int N>
__device__ __forceinline__ void fence_regs(uint32_t (&a)[N]) {
#pragma unroll
    for (int i = 0; i < N; ++i) asm volatile("" : "+r"(a[i])::"memory");
}
#define R8(a, i) "+f"(a[i + 0]), "+f"(a[i + 1]), "+f"(a[i + 2]), "+f"(a[i + 3]), "+f"(a[i + 4]), "+f"(a[i + 5]), "+f"(a[i + 6]), "+f"(a[i + 7])
#define REGS32 "{%0, %1, %2, %3, %4, %5, %6, %7, %8, %9, %10, %11, %12, %13, %14, %15, %16, %17, %18, %19, %20, %21, %22, %23, %24, %25, %26, %27, %28, %29, %30, %31}"
#define REGS16 "{%0, %1, %2, %3, %4, %5, %6, %7, %8, %9, %10, %11, %12, %13, %14, %15}"

__host__ __device__ constexpr uint32_t desc_hi(uint32_t sbo, uint32_t mode) { return (sbo >> 4) | (mode << 30); }
__device__ __forceinline__ uint32_t desc_lo(uint32_t saddr, uint32_t lbo) { return ((saddr & 0x3FFFF) >> 4) | ((lbo >> 4) << 16); }
constexpr uint32_t HI128 = desc_hi(1024, 1), HI64 = desc_hi(512, 2);
#define W8(a, i) "=f"(a[i + 0]), "=f"(a[i + 1]), "=f"(a[i + 2]), "=f"(a[i + 3]), "=f"(a[i + 4]), "=f"(a[i + 5]), "=f"(a[i + 6]), "=f"(a[i + 7])
template <int TA, int TB, int ACC, uint32_t AHI, uint32_t BHI>
__device__ __forceinline__ void wgmma_n64_ss(float (&d)[32], uint32_t alo, uint32_t blo) {
#define N64_TEXT "{\n.reg .pred p;\n.reg .b64 da, db;\nsetp.ne.b32 p, %36, 0;\nmov.b64 da, {%32, %37};\nmov.b64 db, {%33, %38};\n" \
        "wgmma.mma_async.sync.aligned.m64n64k16.f32.bf16.bf16 " REGS32 ", da, db, p, 1, 1, %34, %35;\n}\n"
    if (ACC) asm volatile(N64_TEXT : R8(d, 0), R8(d, 8), R8(d, 16), R8(d, 24) : "r"(alo), "r"(blo), "n"(TA), "n"(TB), "n"(ACC), "n"(AHI), "n"(BHI));
    else asm volatile(N64_TEXT : W8(d, 0), W8(d, 8), W8(d, 16), W8(d, 24) : "r"(alo), "r"(blo), "n"(TA), "n"(TB), "n"(ACC), "n"(AHI), "n"(BHI));
}
template <int ACC, int SA>
__device__ __forceinline__ void wgmma_n32_tt(float (&d)[16], uint32_t alo, uint32_t blo) {
#define N32T_TEXT "{\n.reg .pred p;\n.reg .b64 da, db;\nsetp.ne.b32 p, %18, 0;\nmov.b64 da, {%16, %19};\nmov.b64 db, {%17, %20};\n" \
        "wgmma.mma_async.sync.aligned.m64n32k16.f32.bf16.bf16 " REGS16 ", da, db, p, %21, 1, 1, 1;\n}\n"
    if (ACC) asm volatile(N32T_TEXT : R8(d, 0), R8(d, 8) : "r"(alo), "r"(blo), "n"(ACC), "n"(HI64), "n"(HI128), "n"(SA));
    else asm volatile(N32T_TEXT : W8(d, 0), W8(d, 8) : "r"(alo), "r"(blo), "n"(ACC), "n"(HI64), "n"(HI128), "n"(SA));
}
__device__ __forceinline__ void wgmma_n16_rs(float (&d)[8], const uint32_t (&a)[4], uint32_t blo) {
    asm volatile("{\n.reg .pred p;\n.reg .b64 db;\nsetp.ne.b32 p, 0, 0;\nmov.b64 db, {%12, %13};\n"
        "wgmma.mma_async.sync.aligned.m64n16k16.f32.bf16.bf16 {%0, %1, %2, %3, %4, %5, %6, %7}, {%8, %9, %10, %11}, db, p, 1, 1, 0;\n}\n"
        : W8(d, 0) : "r"(a[0]), "r"(a[1]), "r"(a[2]), "r"(a[3]), "r"(blo), "n"(HI128));
}

__device__ __forceinline__ float bf16r(float x) { return __bfloat162float(__float2bfloat16_rn(x)); }
__device__ __forceinline__ uint32_t pack_bf16(float lo, float hi) {
    __nv_bfloat162 v = __floats2bfloat162_rn(lo, hi);
    return *reinterpret_cast<uint32_t*>(&v);
}
__device__ __forceinline__ __nv_bfloat162 as_bf2(uint32_t w) { return *reinterpret_cast<__nv_bfloat162*>(&w); }
__device__ __forceinline__ uint32_t as_u32(__nv_bfloat162 v) { return *reinterpret_cast<uint32_t*>(&v); }
__device__ __forceinline__ float bf_lo(uint32_t w) { return __uint_as_float(w << 16); }
__device__ __forceinline__ float bf_hi(uint32_t w) { return __uint_as_float(w & 0xFFFF0000u); }
__device__ __forceinline__ void ldsm_x4_t(uint32_t& r0, uint32_t& r1, uint32_t& r2, uint32_t& r3, uint32_t addr) {
    asm volatile("ldmatrix.sync.aligned.m8n8.x4.trans.shared.b16 {%0,%1,%2,%3}, [%4];"
                 : "=r"(r0), "=r"(r1), "=r"(r2), "=r"(r3) : "r"(addr) : "memory");
}
__device__ __forceinline__ void stsm_x4(uint32_t addr, uint32_t r0, uint32_t r1, uint32_t r2, uint32_t r3) {
    asm volatile("stmatrix.sync.aligned.m8n8.x4.shared.b16 [%0], {%1,%2,%3,%4};"
                 ::"r"(addr), "r"(r0), "r"(r1), "r"(r2), "r"(r3) : "memory");
}
__device__ __forceinline__ void stsm_x4_t(uint32_t addr, uint32_t r0, uint32_t r1, uint32_t r2, uint32_t r3) {
    asm volatile("stmatrix.sync.aligned.m8n8.x4.trans.shared.b16 [%0], {%1,%2,%3,%4};"
                 ::"r"(addr), "r"(r0), "r"(r1), "r"(r2), "r"(r3) : "memory");
}
__device__ __forceinline__ uint32_t lds32(uint32_t addr) {
    uint32_t v;
    asm volatile("ld.shared.b32 %0, [%1];" : "=r"(v) : "r"(addr));
    return v;
}

typedef CUresult (*EncodeFn)(CUtensorMap*, CUtensorMapDataType, cuuint32_t, void*, const cuuint64_t*, const cuuint64_t*,
                             const cuuint32_t*, const cuuint32_t*, CUtensorMapInterleave, CUtensorMapSwizzle,
                             CUtensorMapL2promotion, CUtensorMapFloatOOBfill);
EncodeFn get_encode() {
    static EncodeFn fn = nullptr;
    if (!fn) {
        void* p = nullptr;
        cudaDriverEntryPointQueryResult qres;
        cudaGetDriverEntryPoint("cuTensorMapEncodeTiled", &p, cudaEnableDefault, &qres);
        fn = (EncodeFn)p;
    }
    return fn;
}
}
namespace {
constexpr double c_pi = 3.14159265358979323846;
constexpr double c_cos256(int i) {
    i &= 255;
    if (i > 128) i = 256 - i;
    double sgn = 1.0;
    if (i > 64) { i = 128 - i; sgn = -1.0; }
    if (i == 64) return 0.0;
    double x = 2.0 * c_pi * i / 256.0, x2 = x * x, term = 1.0, sum = 1.0;
    for (int k = 1; k < 20; ++k) { term *= -x2 / ((2 * k - 1) * (2 * k)); sum += term; }
    return sgn * sum;
}
constexpr uint32_t c_bf16(double v) {
    if (v == 0.0) return 0u;
    uint32_t s = v < 0 ? 0x8000u : 0u;
    double a = v < 0 ? -v : v;
    int e = 0;
    while (a >= 2.0) { a *= 0.5; ++e; }
    while (a < 1.0) { a *= 2.0; --e; }
    int r = (int)(a * 128.0 + 0.5);
    if (r == 256) { r = 128; ++e; }
    return s | (uint32_t)((e + 127) << 7) | (uint32_t)(r - 128);
}
__host__ __device__ constexpr int conv_k1(int r) { return (r & 8) ? 63 - (((r >> 4) << 3) | (r & 7)) : (((r >> 4) << 3) | (r & 7)); }
struct ConvTab { uint32_t w[96 * 32]; };
constexpr ConvTab make_conv_tab() {
    ConvTab t{};
    uint32_t cs[256] = {};
    for (int i = 0; i < 256; ++i) cs[i] = c_bf16(c_cos256(i));
    for (int n = 0; n < 96; ++n)
        for (int c = 0; c < 64; ++c) {
            int a = 0;
            if (n < 32) {
                const int ro = (n >> 3) & 1, ri = n & 7, co = (c >> 3) & 1, ci = c & 7;
                a = n < 16 ? 8 * ci * (4 * ri + (c >> 4)) : 8 * ri * (4 * ci + (c >> 4));
                a += (ro == co) ? 0 : (ro == 0) ? 192 : 64;
            } else {
                const int r = n - 32, n1 = 2 * (c & 31) + (c >> 5);
                a = n1 * (2 * (((r >> 4) << 3) | (r & 7)) + 1) + ((r & 8) ? 64 : 0);
            }
            const int off = n * 128 + (((c >> 3) ^ (n & 7)) << 4) + (c & 7) * 2;
            t.w[off >> 2] |= cs[a & 255] << ((off & 2) * 8);
        }
    return t;
}
__device__ __align__(128) constexpr ConvTab g_conv_tab = make_conv_tab();

struct Twiddle { uint32_t r[8], i[8], n[8]; };
constexpr double c_cospi(double x) {
    double sgn = 1.0;
    if (x > 0.5) { x = 1.0 - x; sgn = -1.0; }
    const double y = c_pi * x, y2 = y * y;
    double term = 1.0, sum = 1.0;
    for (int k = 1; k < 12; ++k) { term *= -y2 / ((2 * k - 1) * (2 * k)); sum += term; }
    return sgn * sum;
}
struct TwTab { uint32_t w[3072]; };
constexpr TwTab make_tw_tab() {
    TwTab t{};
    for (int th = 0; th < 128; ++th)
        for (int q = 0; q < 8; ++q)
            for (int e = 0; e < 2; ++e) {
                const int k1 = conv_k1(16 * (th >> 5) + 8 * (q & 1) + ((th & 31) >> 2)), n2 = 8 * (q >> 1) + 2 * (th & 3) + e;
                const double x = (double)(n2 * (2 * k1 + 1)) / 4096.0;
                const double cs = c_cospi(x), sn = n2 == 0 ? 0.0 : c_cospi(x > 0.5 ? x - 0.5 : 0.5 - x);
                t.w[((q >> 2) * 128 + th) * 4 + (q & 3)] |= c_bf16(cs * 0.0625) << (16 * e);
                t.w[((2 + (q >> 2)) * 128 + th) * 4 + (q & 3)] |= c_bf16(-sn * 0.0625) << (16 * e);
                t.w[((4 + (q >> 2)) * 128 + th) * 4 + (q & 3)] |= c_bf16(sn * 0.0625) << (16 * e);
            }
    return t;
}
__device__ __align__(128) constexpr TwTab g_tw_tab = make_tw_tab();
__device__ __forceinline__ void load_twiddle(Twiddle& tw, const uint4* p) {
#pragma unroll
    for (int q = 0; q < 2; ++q) {
        const uint4 a = __ldg(p + q * 128);
        const uint4 b = __ldg(p + (2 + q) * 128);
        tw.r[4 * q] = a.x; tw.r[4 * q + 1] = a.y; tw.r[4 * q + 2] = a.z; tw.r[4 * q + 3] = a.w;
        const uint4 n = __ldg(p + (4 + q) * 128);
        tw.n[4 * q] = n.x; tw.n[4 * q + 1] = n.y; tw.n[4 * q + 2] = n.z; tw.n[4 * q + 3] = n.w;
        tw.i[4 * q] = b.x; tw.i[4 * q + 1] = b.y; tw.i[4 * q + 2] = b.z; tw.i[4 * q + 3] = b.w;
    }
}

__device__ __forceinline__ int fresh_tid() { int v; asm volatile("mov.u32 %0, %tid.x;" : "=r"(v)); return v; }
__device__ __forceinline__ uint32_t hmul(uint32_t a, uint32_t b) { return as_u32(__hmul2_rn(as_bf2(a), as_bf2(b))); }
__device__ __forceinline__ uint32_t hadd(uint32_t a, uint32_t b) { return as_u32(__hadd2_rn(as_bf2(a), as_bf2(b))); }
__device__ __forceinline__ uint32_t hsub(uint32_t a, uint32_t b) { return as_u32(__hsub2_rn(as_bf2(a), as_bf2(b))); }
__device__ __forceinline__ uint32_t hfma(uint32_t a, uint32_t b, uint32_t c) { return as_u32(__hfma2(as_bf2(a), as_bf2(b), as_bf2(c))); }

__device__ __forceinline__ void conv_dft8(float (&x)[4][8], const uint32_t (&f)[4][4], uint32_t blo) {
#pragma unroll
    for (int r = 0; r < 4; ++r) wgmma_n16_rs(x[r], f[r], blo + 2 * r);
}
template <class T, int N>
__device__ __forceinline__ void fence_regs4(T (&a)[4][N]) { fence_regs(a[0]); fence_regs(a[1]); fence_regs(a[2]); fence_regs(a[3]); }
__device__ __forceinline__ void conv_s1(float (&dE)[32], float (&dO)[32], uint32_t tlo, uint32_t ulo) {
    wgmma_n64_ss<0, 1, 0, HI128, HI64>(dE, tlo + 256, ulo);
    wgmma_n64_ss<0, 1, 0, HI128, HI64>(dO, tlo + 256 + 4, ulo + 128);
    wgmma_n64_ss<0, 1, 1, HI128, HI64>(dE, tlo + 256 + 2, ulo + 64);
    wgmma_n64_ss<0, 1, 1, HI128, HI64>(dO, tlo + 256 + 6, ulo + 192);
}
template <int S>
__device__ __forceinline__ void conv_t1(const float (&dE)[32], const float (&dO)[32], const Twiddle& tw, float dsk, uint32_t (&f)[4][4]) {
    uint32_t ar[8], ai[8], fs[8], fd[8];
#pragma unroll
    for (int j = 0; j < 4; ++j) {
        const int i = 16 * S + 4 * j;
        const uint32_t e0 = pack_bf16(i == 16 ? dE[i] + dsk : dE[i], dE[i + 1]), e1 = pack_bf16(dE[i + 2], dE[i + 3]);
        const uint32_t o0 = pack_bf16(dO[i], dO[i + 1]), o1 = pack_bf16(dO[i + 2], dO[i + 3]);
        ar[2 * j] = hadd(e0, o0); ai[2 * j] = hadd(e1, o1);
        ar[2 * j + 1] = hsub(e0, o0); ai[2 * j + 1] = hsub(o1, e1);
    }
#pragma unroll
    for (int q = 0; q < 4; ++q) {
        const uint32_t pr = hfma(ar[q], tw.r[q], hmul(ai[q], tw.n[q])), pi = hfma(ar[q], tw.i[q], hmul(ai[q], tw.r[q]));
        fs[q] = hfma(ar[4 + q], tw.r[4 + q], hfma(ai[4 + q], tw.n[4 + q], pr));
        fs[4 + q] = hfma(ar[4 + q], tw.i[4 + q], hfma(ai[4 + q], tw.r[4 + q], pi));
        fd[q] = hfma(pr, 0xC000C000u, fs[q]);
        fd[4 + q] = hfma(pi, 0xC000C000u, fs[4 + q]);
    }
#pragma unroll
    for (int h = 0; h < 2; ++h) {
        f[0][h] = hadd(fs[h], fs[2 + h]); f[0][2 + h] = hadd(fs[4 + h], fs[6 + h]);
        f[2][h] = hsub(fs[h], fs[2 + h]); f[2][2 + h] = hsub(fs[4 + h], fs[6 + h]);
        f[1][h] = hadd(fd[h], fd[6 + h]); f[1][2 + h] = hsub(fd[4 + h], fd[2 + h]);
        f[3][h] = hsub(fd[h], fd[6 + h]); f[3][2 + h] = hadd(fd[4 + h], fd[2 + h]);
    }
}
__device__ __forceinline__ void conv_prod(const float (&xu)[8], const float (&xk)[8], uint32_t (&f)[4]) {
#pragma unroll
    for (int h = 0; h < 2; ++h) {
        float pr[2], pi[2];
#pragma unroll
        for (int e = 0; e < 2; ++e) {
            const float ur = xu[2 * h + e], ui = xu[4 + 2 * h + e], kr = xk[2 * h + e], ki = xk[4 + 2 * h + e];
            pr[e] = fmaf(ur, kr, -ui * ki);
            pi[e] = fmaf(-ur, ki, -ui * kr);
        }
        f[h] = pack_bf16(pr[0], pr[1]);
        f[2 + h] = pack_bf16(pi[0], pi[1]);
    }
}
template <bool SYNC, bool NEXT, class G>
__device__ __forceinline__ void conv_channel(float (&dE)[32], float (&dO)[32], const Twiddle& tw, float dsk, uint32_t tlo, uint32_t nxt,
                                             uint32_t wre, uint32_t wim, int bar, G before_next) {
    float xu[4][8], xk[4][8];
    {
        uint32_t fu[4][4], fk[4][4];
        conv_t1<0>(dE, dO, tw, 0.f, fu);
        wgmma_fence();
        conv_dft8(xu, fu, tlo);
        wgmma_commit();
        conv_t1<1>(dE, dO, tw, dsk, fk);
        wgmma_fence();
        conv_dft8(xk, fk, tlo);
        wgmma_commit();
        before_next();
        wgmma_wait<0>();
        fence_regs4(xu); fence_regs4(xk);
        fence_regs4(fu); fence_regs4(fk);
    }
    uint32_t fp[4][4];
#pragma unroll
    for (int r = 0; r < 4; ++r) conv_prod(xu[r], xk[r], fp[r]);
    wgmma_fence();
    conv_dft8(xu, fp, tlo + 128);
    wgmma_commit();
    if (NEXT) {
        conv_s1(dE, dO, tlo, nxt);
        wgmma_commit();
    }
    wgmma_wait<NEXT ? 1 : 0>();
    fence_regs4(xu);
    fence_regs4(fp);
    uint32_t zr[8], zi[8], wr[8], wi[8];
#pragma unroll
    for (int h = 0; h < 2; ++h) {
        uint32_t yr[4], yi[4];
#pragma unroll
        for (int r = 0; r < 4; ++r) { yr[r] = pack_bf16(xu[r][2 * h], xu[r][2 * h + 1]); yi[r] = pack_bf16(xu[r][4 + 2 * h], xu[r][5 + 2 * h]); }
        const uint32_t u0r = hadd(yr[0], yr[2]), u0i = hadd(yi[0], yi[2]), u1r = hsub(yr[0], yr[2]), u1i = hsub(yi[0], yi[2]);
        const uint32_t v0r = hadd(yr[1], yr[3]), v0i = hadd(yi[1], yi[3]), v1r = hsub(yr[1], yr[3]), v1i = hsub(yi[1], yi[3]);
        zr[h] = hadd(u0r, v0r); zi[h] = hadd(u0i, v0i); zr[4 + h] = hsub(u0r, v0r); zi[4 + h] = hsub(u0i, v0i);
        zr[2 + h] = hadd(u1r, v1i); zi[2 + h] = hsub(u1i, v1r); zr[6 + h] = hsub(u1r, v1i); zi[6 + h] = hadd(u1i, v1r);
    }
#pragma unroll
    for (int q = 0; q < 8; ++q) {
        wr[q] = hfma(zr[q], tw.r[q], hmul(zi[q], tw.n[q]));
        wi[q] = hfma(zr[q], tw.i[q], hmul(zi[q], tw.r[q]));
    }
    if (SYNC) named_bar(bar, 128);
    stsm_x4(wre, hadd(wr[0], wr[1]), hadd(wr[2], wr[3]), hadd(wr[4], wr[5]), hadd(wr[6], wr[7]));
    stsm_x4(wre + 512, hsub(wi[1], wi[0]), hsub(wi[3], wi[2]), hsub(wi[5], wi[4]), hsub(wi[7], wi[6]));
    stsm_x4(wim, hsub(wr[1], wr[0]), hsub(wr[3], wr[2]), hsub(wr[5], wr[4]), hsub(wr[7], wr[6]));
    stsm_x4(wim + 512, hadd(wi[0], wi[1]), hadd(wi[2], wi[3]), hadd(wi[4], wi[5]), hadd(wi[6], wi[7]));
}
template <bool NEXT, class G>
__device__ __forceinline__ void conv_pair(float (&dE)[32], float (&dO)[32], const Twiddle& tw, uint32_t dd, uint32_t tlo, uint32_t u0, uint32_t un,
                                          uint32_t lo, int BAR, G before_next) {
    conv_channel<false, true>(dE, dO, tw, bf_lo(dd), tlo, desc_lo(u0 + 4096, 8192), u0 + lo, u0 + 8192 + lo, BAR, []() {});
    wgmma_wait<0>();
    fence_regs(dE); fence_regs(dO);
    conv_channel<true, NEXT>(dE, dO, tw, bf_hi(dd), tlo, desc_lo(un, 8192), u0 + 4096 + lo, u0 + 12288 + lo, BAR, before_next);
    fence_async_smem();
    named_bar(BAR, 128);
    float ye[16], yo[16];
    wgmma_fence();
    const uint32_t wlo = desc_lo(u0, 4096);
    wgmma_n32_tt<0, 1>(ye, wlo, tlo + 256);
    wgmma_n32_tt<0, -1>(yo, wlo + 512, tlo + 256 + 4);
#pragma unroll
    for (int k = 1; k < 4; ++k) {
        wgmma_n32_tt<1, 1>(ye, wlo + 64 * k, tlo + 256 + 128 * k);
        wgmma_n32_tt<1, -1>(yo, wlo + 512 + 64 * k, tlo + 256 + 4 + 128 * k);
    }
    wgmma_commit();
    wgmma_wait<0>();
    fence_regs(ye); fence_regs(yo);
    if (NEXT) { fence_regs(dE); fence_regs(dO); }
    named_bar(BAR, 128);
    const int t = fresh_tid();
    const uint32_t ya = u0 + (t & 64) * 64 + (t & 31) * 64 + (((((t >> 4) & 2) ^ (t >> 1)) & 3) << 4);
#pragma unroll
    for (int h = 0; h < 2; ++h) {
        stsm_x4_t(ya ^ (16 * h), pack_bf16(ye[2 * h], ye[2 * h + 1]), pack_bf16(ye[4 + 2 * h], ye[5 + 2 * h]),
                  pack_bf16(ye[8 + 2 * h], ye[9 + 2 * h]), pack_bf16(ye[12 + 2 * h], ye[13 + 2 * h]));
        stsm_x4_t((ya ^ (16 * h)) + 2048, pack_bf16(yo[2 * h], yo[2 * h + 1]), pack_bf16(yo[4 + 2 * h], yo[5 + 2 * h]),
                  pack_bf16(yo[8 + 2 * h], yo[9 + 2 * h]), pack_bf16(yo[12 + 2 * h], yo[13 + 2 * h]));
    }
    fence_async_smem();
    __syncwarp();
}
}

namespace {

constexpr int S_LEN = 2048;
constexpr int D_DIM = 1024;

#define REG_P 24
#define REG_AB 168
#define REG_C 152
#define ULATE 3
#define CLATE 4
#define QD 3
#define QKB 18
#define GAP_Y1 50
#define QD2 6
#define KVFINE 0
#define G1ORD 0
#define BWAIT 1
#define SKEW1 4
#define TK_PF0 0
#define GAP_PF 300
#define TK_KV0 2
#define TK_KV1 4
#define GAP_KV 50
#define GAP_ST 50
#define GAP_HB 100
#define PFD 7
#define CWAIT 0
#define GAP_Y 100
#define GAP_X 100
#define SLOT4 20
#define SKEW2 4
#define KVFMA 0
#define G2SIG 0
#define GAP_CV 100
#define TK_C 8
#define GWAIT 0

__device__ __align__(1024) __nv_bfloat16 g_H[2 * D_DIM * S_LEN];
__device__ __align__(1024) __nv_bfloat16 g_y2[D_DIM * S_LEN];
__device__ __align__(1024) __nv_bfloat16 g_kvT[D_DIM * S_LEN];
__device__ __align__(128) float g_gate[S_LEN];
__device__ __align__(128) unsigned long long g_agg[8 * D_DIM];
__device__ __align__(128) unsigned int g_cnt[56 * 32];

#define STAMP(k, s) do { } while (0)
#define SAMPLE(i) do { } while (0)

__device__ __forceinline__ void tma_store_5d(const CUtensorMap* map, uint32_t src, int c0, int c1, int c2, int c3, int c4) {
    asm volatile("cp.async.bulk.tensor.5d.global.shared::cta.bulk_group [%0, {%2, %3, %4, %5, %6}], [%1];"
                 ::"l"((uint64_t)map), "r"(src), "r"(c0), "r"(c1), "r"(c2), "r"(c3), "r"(c4) : "memory");
}
#define ELECT "{\n.reg .pred p;\nelect.sync _|p, 0xffffffff;\n@p "
__device__ __forceinline__ void e_expect_tx(uint32_t bar, uint32_t bytes) {
    asm volatile(ELECT "mbarrier.arrive.expect_tx.shared::cta.b64 _, [%0], %1;\n}" ::"r"(bar), "r"(bytes) : "memory");
}
__device__ __forceinline__ void e_arrive(uint32_t bar) {
    asm volatile(ELECT "mbarrier.arrive.shared::cta.b64 _, [%0];\n}" ::"r"(bar) : "memory");
}
__device__ __forceinline__ void e_load_4d(uint32_t dst, const CUtensorMap* map, uint32_t bar, int c0, int c1, int c2, int c3) {
    asm volatile(ELECT "cp.async.bulk.tensor.4d.shared::cluster.global.mbarrier::complete_tx::bytes [%0], [%1, {%3, %4, %5, %6}], [%2];\n}"
        ::"r"(dst), "l"((uint64_t)map), "r"(bar), "r"(c0), "r"(c1), "r"(c2), "r"(c3) : "memory");
}
__device__ __forceinline__ void e_load_5d(uint32_t dst, const CUtensorMap* map, uint32_t bar, int c0, int c1, int c2, int c3, int c4) {
    asm volatile(ELECT "cp.async.bulk.tensor.5d.shared::cluster.global.mbarrier::complete_tx::bytes [%0], [%1, {%3, %4, %5, %6, %7}], [%2];\n}"
        ::"r"(dst), "l"((uint64_t)map), "r"(bar), "r"(c0), "r"(c1), "r"(c2), "r"(c3), "r"(c4) : "memory");
}
__device__ __forceinline__ void e_bulk_load(uint32_t dst, const void* src, uint32_t bytes, uint32_t bar) {
    asm volatile(ELECT "cp.async.bulk.shared::cluster.global.mbarrier::complete_tx::bytes [%0], [%1], %2, [%3];\n}"
                 ::"r"(dst), "l"(src), "r"(bytes), "r"(bar) : "memory");
}
__device__ __forceinline__ void l2_prefetch(const void* p, uint32_t bytes) {
    asm volatile("cp.async.bulk.prefetch.L2.global [%0], %1;" ::"l"(p), "r"(bytes) : "memory");
}
__device__ __forceinline__ void l2_prefetch_4d(const CUtensorMap* map, int c0, int c1, int c2, int c3) {
    asm volatile("cp.async.bulk.prefetch.tensor.4d.L2.global [%0, {%1, %2, %3, %4}];" ::"l"((uint64_t)map), "r"(c0), "r"(c1), "r"(c2), "r"(c3) : "memory");
}
__device__ __forceinline__ void l2_prefetch_5d(const CUtensorMap* map, int c0, int c1, int c2, int c3, int c4) {
    asm volatile("cp.async.bulk.prefetch.tensor.5d.L2.global [%0, {%1, %2, %3, %4, %5}];" ::"l"((uint64_t)map), "r"(c0), "r"(c1), "r"(c2), "r"(c3), "r"(c4) : "memory");
}
__device__ __forceinline__ unsigned int ld_relaxed(const unsigned int* p) {
    unsigned int v;
    asm volatile("ld.relaxed.gpu.global.u32 %0, [%1];" : "=r"(v) : "l"(p) : "memory");
    return v;
}
__device__ __forceinline__ void fence_async_global() { asm volatile("fence.proxy.async.global;" ::: "memory"); }
__device__ __forceinline__ void wait_counter(const unsigned int* p, unsigned int target) {
    unsigned int v;
    int it = 0;
    do { asm volatile("ld.acquire.gpu.global.u32 %0, [%1];" : "=r"(v) : "l"(p) : "memory"); } while (v != target && ++it < (1 << 22));
    fence_async_global();
}
__device__ __forceinline__ void red_release(unsigned int* p, unsigned int n) {
    asm volatile("red.release.gpu.global.add.u32 [%0], %1;" ::"l"(p), "r"(n) : "memory");
}
__device__ __forceinline__ uint4 ldg128(const void* p) {
    uint4 v;
    asm volatile("ld.global.nc.v4.u32 {%0,%1,%2,%3}, [%4];" : "=r"(v.x), "=r"(v.y), "=r"(v.z), "=r"(v.w) : "l"(p));
    return v;
}
__device__ __forceinline__ void stg128(void* p, uint32_t a, uint32_t b, uint32_t c, uint32_t d) {
    asm volatile("st.global.v4.b32 [%0], {%1, %2, %3, %4};" ::"l"(p), "r"(a), "r"(b), "r"(c), "r"(d) : "memory");
}

template <int TA>
__device__ __forceinline__ void wgmma_n128(float (&d)[64], uint32_t alo, uint32_t blo, int acc) {
    asm volatile(
        "{\n.reg .pred p;\n.reg .b64 da, db;\nsetp.ne.b32 p, %67, 0;\nmov.b64 da, {%64, %69};\nmov.b64 db, {%65, %66};\n"
        "wgmma.mma_async.sync.aligned.m64n128k16.f32.bf16.bf16 "
        "{%0, %1, %2, %3, %4, %5, %6, %7, %8, %9, %10, %11, %12, %13, %14, %15, "
        "%16, %17, %18, %19, %20, %21, %22, %23, %24, %25, %26, %27, %28, %29, %30, %31, "
        "%32, %33, %34, %35, %36, %37, %38, %39, %40, %41, %42, %43, %44, %45, %46, %47, "
        "%48, %49, %50, %51, %52, %53, %54, %55, %56, %57, %58, %59, %60, %61, %62, %63}, "
        "da, db, p, 1, 1, %68, 0;\n"
        "}\n"
        : R8(d, 0), R8(d, 8), R8(d, 16), R8(d, 24), R8(d, 32), R8(d, 40), R8(d, 48), R8(d, 56)
        : "r"(alo), "r"(blo), "n"(HI128), "r"(acc), "n"(TA), "n"(TA ? HI64 : HI128));
}

constexpr int NST = 5;
constexpr int XTRA = SKEW1 - 4;
static_assert(SKEW1 >= 4 && SKEW1 <= 12, "skew");
constexpr int OFF_BB = 4 * 32768;
constexpr int OFF_CT = 5 * 32768;
constexpr int OFF_CU = OFF_CT + 32768;
__host__ __device__ constexpr uint32_t conv_buf(int p) { return OFF_CT + 16384 + (p == 3 ? 0 : p) * 16384; }
constexpr int OFF_PAR = OFF_CU + 32768;
constexpr int OFF_BAR = OFF_PAR + 2048;
constexpr int SMEM_BYTES = OFF_BAR + 896;
static_assert(SMEM_BYTES <= 232448, "smem layout");

static_assert(SLOT4 % 4 == 0 && SLOT4 <= 24, "ring");
constexpr uint32_t PH4 = (SLOT4 / 4 - 1) & 1;
__host__ __device__ constexpr int ring_slot(int kb) { return (kb - SLOT4 + 4) % 5; }
__host__ __device__ constexpr uint32_t ring_par(int kb) { return ((SLOT4 / 4 - 1 + (kb - SLOT4 + 4) / 5) & 1) ^ (ring_slot(kb) == 4 ? PH4 : 0); }

struct Maps {
    CUtensorMap x5, b4, cre, cim, sk, yt, out, kvst, bre, bim;
    unsigned char tile[132];
};

__device__ __forceinline__ void cmul(float& r, float& i, float ar, float ai, float br, float bi) {
    const float a = ar * br - ai * bi, b = ar * bi + ai * br;
    r = a; i = b;
}
__device__ __forceinline__ void csqr(float& r, float& i) { const float a = r * r - i * i, b = 2.f * r * i; r = a; i = b; }
__device__ __forceinline__ float after(float v, float dep) { return __float_as_uint(dep) == 0x7fedcba9u ? dep : v; }

template <int BMODE>
__global__ void __launch_bounds__(512, 1)
fused_kernel(const __nv_bfloat16* __restrict__ x,
             const __nv_bfloat16* __restrict__ kin, const __nv_bfloat16* __restrict__ vin, const __nv_bfloat16* __restrict__ ssm_k,
             const __nv_bfloat16* __restrict__ shift_k, const __nv_bfloat16* __restrict__ ssm_D,
             const __nv_bfloat16* __restrict__ lam_re, const __nv_bfloat16* __restrict__ lam_im,
             const __nv_bfloat16* __restrict__ log_dt, const __nv_bfloat16* __restrict__ gate_w,
             const __nv_bfloat16* __restrict__ dskip,
             const __nv_bfloat16* __restrict__ c_re, const __nv_bfloat16* __restrict__ c_im,
             const __grid_constant__ Maps maps) {
    constexpr bool MERGED = BMODE != 0, SW = BMODE == 2;
    extern __shared__ __align__(1024) unsigned char smem_raw[];
    const uint32_t sbase = smem_u32(smem_raw);
    const uint32_t bar_full = sbase + OFF_BAR;
    const uint32_t bar_empty = bar_full + 32;
    const uint32_t bar_full2 = bar_empty + 32;
    const uint32_t bar_empty2 = bar_full2 + 40;
    const uint32_t bar_k = bar_empty2 + 40;
    const uint32_t bar_tab = bar_k + 32;
    const uint32_t bar_ab = bar_tab + 8;
    const uint32_t bar_adone = bar_ab + 8;
    const uint32_t bar_par = bar_adone + 8;
    const uint32_t bar_y = bar_par + 8;
    const uint32_t bar_rel = bar_y + 8;
    const uint32_t bar_kvrel = bar_rel + 8;
    const uint32_t bar_yrel = bar_kvrel + 8;
    const uint32_t bar_y1 = bar_yrel + 8;
    const uint32_t bar_fh = bar_y1 + 8;
    const uint32_t bar_tick = bar_fh + 24;
    const uint32_t bar_stg = bar_tick + 104;
    const uint32_t bar_bias = bar_stg + 112;
    const uint32_t bar_hw = bar_bias + 16;
    const uint32_t bar_gate = bar_hw + 32;
    const uint32_t bar_ascan = bar_gate + 8;
    const uint32_t bar_g2 = bar_hw;
    const uint32_t w_bid = bar_full + 600, w_dsk = bar_full + 608, w_ones = bar_full + 640;
    const int tid = threadIdx.x;
    if (tid == 0) { prefetch_map(&maps.x5); prefetch_map(&maps.b4); }
    int bid;
    {
        unsigned int sm, nsm;
        asm volatile("mov.u32 %0, %smid;" : "=r"(sm));
        asm volatile("mov.u32 %0, %nsmid;" : "=r"(nsm));
        bid = gridDim.x == 132 && nsm == 132 ? maps.tile[sm] : blockIdx.x;
    }
    const int tt = bid >> 3, dt = bid & 7;
    const int ti = tt >> 1;
    const int cg = (dt >> 2) * 8 + (tt & 1) * 4 + (dt & 3);
    if (MERGED && tid == 0 && bid < 128) {
        STAMP(1, 0);
        mbar_init(bar_full, 1);
        asm volatile("fence.mbarrier_init.release.cluster;" ::: "memory");
        mbar_expect_tx(bar_full, 49152);
        tma_load_4d(sbase + OFF_CU, &maps.b4, bar_full, 0, 0, 0, cg * 4);
        tma_load_5d(sbase + ((0 - XTRA) & 3) * 32768, &maps.x5, bar_full, 0, 0, 0, 0, ti);
        tma_load_4d(sbase + OFF_BB, &maps.b4, bar_full, 0, 0, 0, 64 + cg * 4);
    }
    __syncwarp();
    const int warp = __shfl_sync(0xffffffffu, tid >> 5, 0), wg = warp >> 2, lane = tid & 31;
    if (bid >= 128) {
        if (tid == 0) {
            __nanosleep(2000);
            const unsigned int target = (ld_relaxed(&g_cnt[32 * 32]) & ~63u) + 64u;
            for (int i = 0; i < 8; ++i)
                for (int it = 0; ld_relaxed(&g_cnt[(40 + i) * 32]) != target && it < (1 << 12); ++it) __nanosleep(500);
        }
        return;
    }
    if (warp == 0) {
        if (lane == 0) {
#pragma unroll
            for (int s = MERGED; s < 4; ++s) mbar_init(bar_full + 8 * s, 1);
            asm volatile("fence.mbarrier_init.release.cluster;" ::: "memory");
        }
        __syncwarp();
        if (MERGED) {
            asm volatile("bar.arrive 4, 512;" ::: "memory");
#pragma unroll 1
            for (int it = 1; it < 4; ++it) {
                e_expect_tx(bar_full + 8 * it, 49152);
                e_load_4d(sbase + OFF_CU + it * 8192, &maps.b4, bar_full + 8 * it, it * 64, 0, 0, cg * 4);
                e_load_5d(sbase + ((it - XTRA) & 3) * 32768, &maps.x5, bar_full + 8 * it, it * 64, 0, 0, 0, ti);
                e_load_4d(sbase + OFF_BB + it * 8192, &maps.b4, bar_full + 8 * it, it * 64, 0, 0, 64 + cg * 4);
            }
        }
        if (lane == 0) STAMP(1, 1);
    } else if (tid == 32) {
        if (sbase & 1023) __trap();
#pragma unroll
        for (int s = 0; s < 4; ++s) mbar_init(bar_empty + 8 * s, 2);
#pragma unroll
        for (int s = 0; s < NST; ++s) { mbar_init(bar_full2 + 8 * s, 1); mbar_init(bar_empty2 + 8 * s, 1); }
        mbar_init(bar_k, 1); mbar_init(bar_k + 8, 1); mbar_init(bar_k + 16, 1); mbar_init(bar_k + 24, 1);
        mbar_init(bar_tab, 1);
        mbar_init(bar_ab, 1);
        mbar_init(bar_adone, 4);
        mbar_init(bar_par, 2);
        asm volatile("fence.mbarrier_init.release.cluster;" ::: "memory");
    } else if (tid == 64) {
#pragma unroll
        for (int s = 0; s < 21; ++s) mbar_init(bar_y + 8 * s, 1);
    } else if (tid == 96) {
#pragma unroll
        for (int s = 0; s < 22; ++s) mbar_init(bar_stg + 8 * s, 4);
    } else if (tid == 128) {
        asm volatile("st.shared.b32 [%0], %1;" ::"r"(w_bid), "r"(bid) : "memory");
        SAMPLE(0);
    }
    if (MERGED) {
        if (warp == 0) asm volatile("bar.sync 5, 64;" ::: "memory");
        else {
            __syncwarp();
            asm volatile("bar.sync 4, 512;" ::: "memory");
            if (warp == 1) asm volatile("bar.arrive 5, 64;" ::: "memory");
        }
    } else {
        __syncthreads();
    }

    if (wg == 0) {
        asm volatile("setmaxnreg.dec.sync.aligned.u32 %0;" ::"n"(REG_P));
        if (warp == 0) {
#pragma unroll 1
            for (int it = MERGED ? 4 : 0; it < 16 + XTRA; ++it) {
                const int st = it & 3, kb = it < 16 ? it : it - SKEW1;
                const bool fa = it < 16, fb = it < 16 - SKEW1 || it >= 12;
                const uint32_t bf = bar_full + 8 * st;
                mbar_wait(bar_empty + 8 * st, ((it >> 2) & 1) ^ 1);
                e_expect_tx(bf, fa && fb ? 49152 : 40960);
                e_load_5d(sbase + ((it - XTRA) & 3) * 32768, &maps.x5, bf, kb * 64, 0, 0, 0, ti);
                if (MERGED) {
                    if (fa) e_load_4d(sbase + OFF_CU + st * 8192, &maps.b4, bf, kb * 64, 0, 0, cg * 4);
                    if (fb) e_load_4d(sbase + OFF_BB + st * 8192, &maps.b4, bf, kb * 64, 0, 0, 64 + cg * 4);
                } else {
                    if (lane < 16 && ((lane & 8) ? fb : fa))
                        tma_load_2d(sbase + ((lane & 8) ? OFF_BB : OFF_CU) + st * 8192 + (lane & 7) * 1024, (lane & 1) ? &maps.bim : &maps.bre, bf,
                                    kb * 64, (lane >> 3) * 512 + cg * 32 + ((lane & 7) >> 1) * 8);
                    __syncwarp();
                }
                if (it >= 4 && it < 16) e_arrive(bar_tick + 8 * (it - 3));
                if (lane == 0) STAMP(1, 16 + it);
                if (lane == 0 && it < 16) SAMPLE(it - 3);
            }
            int st = 0;
            uint32_t ph = 0;
#pragma unroll 1
            for (int kb = 0; kb < 32; ++kb) {
                const uint32_t bf = bar_full2 + 8 * st;
                if (kb == CLATE) { mbar_wait(bar_ascan, 0); __nanosleep(100); }
                mbar_wait(bar_empty2 + 8 * st, st == 4 ? ph ^ PH4 : ph);
                e_expect_tx(bf, 32768);
                e_load_5d(sbase + st * 32768 + 16384, &maps.cre + ((kb >> 3) & 1), bf, ((kb >> 4) * 8 + (kb & 7)) * 64, 0, 0, 0, dt * 4);
                if (lane == 0) STAMP(2, 16 + kb);
                if (lane == 0 && (kb & 3) == 0) SAMPLE(13 + (kb >> 2));
                if (++st == (kb < SLOT4 - 1 ? 4 : 5)) { st = 0; ph ^= 1; }
            }
        } else if (warp == 1) {
            mbar_wait(bar_full, 0);
            e_arrive(bar_tick);
            if (MERGED && PFD && lane == 0) {
#pragma unroll 1
                for (int n = 0; n + PFD < 16; ++n) {
                    mbar_wait(bar_tick + 8 * n, 0);
                    if (cg >= 4 && max(cg - PFD, 0) == n) l2_prefetch_5d(&maps.x5, cg * 64, 0, 0, 0, ti);
                    if (ti >= 2 && max(2 * ti - PFD, 0) == n) {
#pragma unroll 1
                        for (int i = 0; i < 4; ++i) l2_prefetch_4d(&maps.b4, (2 * ti + (i >> 1)) * 64, 0, 0, (i & 1) * 64 + cg * 4);
                    }
                }
            }
            __syncwarp();
            const unsigned int target = (ld_relaxed(&g_cnt[(4 * ti) * 32]) & ~63u) + 64u;
            const char* hp = reinterpret_cast<const char*>(g_H) + (size_t)tt * 262144;
            mbar_wait(bar_adone, 0);
            e_expect_tx(bar_k + 8, 16384);
            e_expect_tx(bar_k + 16, 16384);
#pragma unroll 1
            for (int c = 2; c < 6; ++c) {
                e_load_4d(sbase + conv_buf(0) + (c >> 1) * 16384 + (c & 1) * 4096 + 8192, &maps.sk, bar_k + 8 * (c >> 1), 0, 0, 0, bid * 8 + c);
                if (GAP_CV) __nanosleep(GAP_CV);
            }
            mbar_wait(bar_rel, 0);
            int st = 0;
            uint32_t ph = 0;
#pragma unroll 1
            for (int q = 0; q < 4; ++q) {
                if (lane == 0) STAMP(0, 8 + 2 * q);
                if (q == 0) wait_counter(&g_cnt[(4 * ti) * 32], target);
                else { mbar_wait(bar_fh + 8 * q - 8, 0); fence_async_global(); }
                if (lane == 0) STAMP(0, 9 + 2 * q);
#pragma unroll 1
                for (int kb = 0; kb < 8; ++kb) {
                    mbar_wait(bar_empty2 + 8 * st, st == 4 ? ph ^ PH4 : ph);
                    e_bulk_load(sbase + st * 32768, hp + kb * 16384, 16384, bar_full2 + 8 * st);
                    if (++st == (8 * q + kb < SLOT4 - 1 ? 4 : 5)) { st = 0; ph ^= 1; }
                }
                hp += (q & 1) ? 4194304 - 131072 : 131072;
            }
        } else if (warp == 2) {
            if (lane == 0) {
                mbar_wait(bar_tick + 8, 0);
                const unsigned int target = (ld_relaxed(&g_cnt[(40 + dt) * 32]) & ~63u) + 64u;
                asm volatile("st.shared.b32 [%0], %1;" ::"r"(w_bid + 4), "r"(target) : "memory");
                prefetch_map(&maps.kvst); prefetch_map(&maps.sk);
#pragma unroll 1
                for (int bt = 0; bt < 2; ++bt) {
                    mbar_wait(bar_stg + 8 * bt, 0);
#pragma unroll 1
                    for (int i = 0; i < 4; ++i) {
                        if (i) __nanosleep(GAP_ST);
                        tma_store_3d(&maps.kvst, sbase + OFF_CT + bt * 16384 + i * 4096, (tt & 1) * 1024 + ti * 128 + 64 * bt, dt * 16, 2 * i);
                    }
                    bulk_commit();
                }
                bulk_wait0();
                fence_async_global();
                red_release(&g_cnt[(40 + dt) * 32], 4);
                mbar_arrive(bar_kvrel);
                STAMP(0, 23);
                mbar_expect_tx(bar_tab, 12288);
                bulk_load(sbase + OFF_CT, &g_conv_tab, 12288, bar_tab);
                mbar_expect_tx(bar_k, 16384);
                tma_load_4d(sbase + conv_buf(0) + 8192, &maps.sk, bar_k, 0, 0, 0, bid * 8);
                tma_load_4d(sbase + conv_buf(0) + 12288, &maps.sk, bar_k, 0, 0, 0, bid * 8 + 1);
                wait_counter(&g_cnt[(40 + (bid >> 4)) * 32], target);
                STAMP(0, 19);
#pragma unroll 1
                for (int p = 0; p < 3; ++p) {
                    if (p == 1) mbar_wait(bar_adone, 0);
                    if (p == ULATE) { mbar_wait(bar_ascan, 0); __nanosleep(100); }
                    bulk_load(sbase + conv_buf(p), g_kvT + (size_t)(bid * 8 + 2 * p) * 2048, 8192, bar_k + 8 * p);
                    if (GAP_CV) __nanosleep(GAP_CV);
                }
                prefetch_map(&maps.out); prefetch_map(&maps.yt);
#pragma unroll 1
                for (int p = 0; p < 4; ++p) {
                    mbar_wait(bar_stg + 16 + 8 * p, 0);
                    if (p == 0) {
                        mbar_expect_tx(bar_k + 24, 16384);
                        tma_load_4d(sbase + conv_buf(3) + 8192, &maps.sk, bar_k + 24, 0, 0, 0, bid * 8 + 6);
                        mbar_wait(bar_g2, 0);
                        tma_load_4d(sbase + conv_buf(3) + 12288, &maps.sk, bar_k + 24, 0, 0, 0, bid * 8 + 7);
                    }
#pragma unroll 1
                    for (int i = 0; i < 2; ++i) {
                        if (i) __nanosleep(GAP_Y);
                        asm volatile("cp.async.bulk.global.shared::cta.bulk_group [%0], [%1], 4096;"
                                     ::"l"(g_y2 + (size_t)(bid * 8 + 2 * p + i) * 2048), "r"(sbase + conv_buf(p) + i * 4096) : "memory");
                    }
                    bulk_commit();
                    STAMP(0, 24 + p);
                    if (p == 0) {
                        bulk_wait_read0();
                        bulk_load(sbase + conv_buf(3), g_kvT + (size_t)(bid * 8 + 6) * 2048, 8192, bar_k + 24);
                    }
                    if (p == 2) {
                        bulk_wait0();
                        fence_async_global();
                        red_release(&g_cnt[(48 + (bid >> 4)) * 32], 4);
                        mbar_arrive(bar_yrel);
                        STAMP(0, 3);
                    }
                }
                bulk_wait0();
                fence_async_global();
                red_release(&g_cnt[(32 + (bid >> 4)) * 32], 4);
                STAMP(0, 2);
                wait_counter(&g_cnt[(32 + dt) * 32], target);
                STAMP(0, 5);
                mbar_expect_tx(bar_y, 8192);
                tma_load_5d(sbase + OFF_CU + 24576, &maps.yt, bar_y, (tt & 1) * 1024 + ti * 128, 0, 0, 3, dt * 4);
                tma_load_5d(sbase + OFF_CU + 28672, &maps.yt, bar_y, (tt & 1) * 1024 + ti * 128 + 64, 0, 0, 3, dt * 4);
#pragma unroll 1
                for (int i = 0; i < 8; ++i) {
                    mbar_wait(bar_stg + 48 + 8 * i, 0);
                    tma_store_5d(&maps.out, sbase + ((i & 4) ? OFF_CT : OFF_CU) + (i & 3) * 8192, dt * 128 + (i & 3) * 32, 0, 0, (tt & 1) * 4 + ((i & 4) >> 1), ti);
                    bulk_commit();
                }
                bulk_wait_read0();
                STAMP(2, 3);
                SAMPLE(21);
            }
        } else if (lane == 0) {
            mbar_wait(bar_tick + 8 * TK_PF0, 0);
#pragma unroll 1
            for (int i = 0; i < 8; ++i) {
                l2_prefetch(((i & 1) ? vin : kin) + (size_t)(ti * 256 + 32 * (i & 4) + (bid & 15) * 8 + 2 * (i & 2)) * D_DIM, 8192);
                __nanosleep(GAP_PF);
            }
            if (bid < 3) l2_prefetch(reinterpret_cast<const char*>(&g_conv_tab) + bid * 4096, 4096);
            prefetch_map(&maps.cre); prefetch_map(&maps.cim);
            mbar_wait(bar_tick + 8 * TK_C, 0);
#pragma unroll 1
            for (int i = 0; i < 8; ++i) {
                l2_prefetch((i & 1) ? ((i & 4) ? c_im : c_re) + (size_t)bid * 8192 + (i & 2) * 2048 : ssm_k + (size_t)bid * 16384 + (i >> 1) * 4096, 8192);
                __nanosleep(GAP_PF);
            }
            const unsigned int target = (ld_relaxed(&g_cnt[(4 * ti + 1) * 32]) & ~63u) + 64u;
            mbar_wait(bar_gate, 0);
#pragma unroll 1
            for (int q = 1; q < 4; ++q) {
                if (q < 3) mbar_wait(bar_hw + 8 * q, 0);
                if (q > 1) {
                    mbar_wait(bar_g2, 0);
                    char* hp = reinterpret_cast<char*>(g_H) + (size_t)((16 + 2 * ti) * 16 + (q & 1) * 8 + (cg >> 1)) * 16384 + (cg & 1) * 2048;
#pragma unroll 1
                    for (int i = 0; i < 8; ++i) {
                        asm volatile("cp.async.bulk.global.shared::cta.bulk_group [%0], [%1], 2048;"
                                     ::"l"(hp + (i & 3) * 4096 + (i >> 2) * 262144), "r"(sbase + OFF_BB + (q & 1) * 16384 + i * 2048) : "memory");
                        __nanosleep(GAP_HB);
                    }
                    bulk_commit();
                    if (q == 3) {
                        wait_counter(&g_cnt[(4 * ti + 2) * 32], target);
                        mbar_arrive(bar_fh + 8);
                    }
                    bulk_wait0();
                    if (q == 3) mbar_arrive(bar_empty2 + 32);
                    fence_async_global();
                }
                red_release(&g_cnt[(4 * ti + q) * 32], 4);
                STAMP(0, 36 + q);
                if (q != 2) {
                    wait_counter(&g_cnt[(4 * ti + q) * 32], target);
                    mbar_arrive(bar_fh + 8 * q - 8);
                }
            }
        }
    } else if (wg == 3) {
        asm volatile("setmaxnreg.inc.sync.aligned.u32 %0;" ::"n"(REG_C));
        const int t = tid & 127, w4 = t >> 5;
        mbar_wait(bar_tick, 0);
        if (t < 64) {
            const int ch = (t >> 5) * 512 + cg * 32 + (t & 31);
            unsigned long long oldagg;
            asm volatile("ld.relaxed.gpu.global.u64 %0, [%1];" : "=l"(oldagg) : "l"(&g_agg[ti * D_DIM + ch]) : "memory");
            const float Lr = __bfloat162float(lam_re[ch]), Li = __bfloat162float(lam_im[ch]);
            const float dtv = bf16r(expf(__bfloat162float(log_dt[ch])));
            const unsigned int tag = ((((unsigned int)oldagg & 1u) | ((unsigned int)(oldagg >> 31) & 2u)) + 1u) & 3u;
            const float er = expf(dtv * Lr);
            float s, c;
            sincosf(dtv * Li, &s, &c);
            const float lr = er * c, li = er * s;
            const float nr = lr - 1.f, ni = li;
            const float den = Lr * Lr + Li * Li;
            const float cr = 2.f * (nr * Lr + ni * Li) / den, ci = 2.f * (ni * Lr - nr * Li) / den;
            float pr = lr, pi = -li;
#pragma unroll
            for (int i = 0; i < 5; ++i) csqr(pr, pi);
            sts128(sbase + OFF_PAR + t * 32, __float_as_uint(lr), __float_as_uint(-li), __float_as_uint(cr), __float_as_uint(ci));
            sts128(sbase + OFF_PAR + t * 32 + 16, __float_as_uint(pr), __float_as_uint(pi), tag, 0);
            __syncwarp();
            if (lane == 0) mbar_arrive(bar_par);
        }
        if (t >= 120) asm volatile("st.shared.b32 [%0], %1;" ::"r"(w_dsk - 480 + 4 * t),
                                   "r"(t < 124 ? __ldg(reinterpret_cast<const uint32_t*>(ssm_D + bid * 8) + (t & 3)) : 0u) : "memory");
        if (t < 64) asm volatile("st.shared.b32 [%0], %1;" ::"r"(w_ones + 4 * t), "r"(0x3F803F80u) : "memory");
        {
            const int cq = lane & 15, rg = (lane >> 4) + 2 * w4;
            uint32_t sk[4][4];
#pragma unroll
            for (int c = 0; c < 4; ++c) {
                const uint4 w = ldg128(shift_k + (size_t)(dt * 128 + 8 * cq + 2 * c) * 4);
                sk[0][c] = __byte_perm(w.x, w.z, 0x5410); sk[1][c] = __byte_perm(w.x, w.z, 0x7632);
                sk[2][c] = __byte_perm(w.y, w.w, 0x5410); sk[3][c] = __byte_perm(w.y, w.w, 0x7632);
            }
#pragma unroll 1
            for (int bt = 0; bt < 2; ++bt) {
                const int t0 = ti * 256 + 128 * bt + 16 * (rg & 4) + 32 * (tt & 1) + 8 * (rg & 3);
                mbar_wait(bar_tick + 8 * (bt ? TK_KV1 : TK_KV0), 0);
                if (t == 0) STAMP(0, 30 + 3 * bt);
                uint4 kk[11], vv[8];
                const __nv_bfloat16* kp = kin + (size_t)t0 * D_DIM + dt * 128 + 8 * cq;
                const __nv_bfloat16* vp = vin + (size_t)t0 * D_DIM + dt * 128 + 8 * cq;
#pragma unroll
                for (int i = 0; i < 11; ++i) {
                    if (i < 3 && t0 == 0) kk[i] = make_uint4(0, 0, 0, 0);
                    else kk[i] = ldg128(kp + (i - 3) * D_DIM);
                    if (KVFINE ? (i & 1) : (i == 6 || i == 10)) __nanosleep(GAP_KV);
                }
#pragma unroll
                for (int i = 0; i < 8; ++i) { vv[i] = ldg128(vp + i * D_DIM); if (KVFINE ? !(i & 1) : i == 3) __nanosleep(GAP_KV); }
                const uint32_t ua = sbase + OFF_CT + bt * 16384 + cq * 128 + ((rg ^ ((2 * ti + bt) & 3) ^ (cq & 7)) << 4);
#pragma unroll
                for (int c = 0; c < 4; ++c) {
                    uint32_t res[8];
#pragma unroll
                    for (int i = 0; i < 8; ++i) {
                        uint32_t ks = hmul((&kk[i].x)[c], sk[3][c]);
                        if (KVFMA) {
                            ks = hfma((&kk[i + 1].x)[c], sk[2][c], ks);
                            ks = hfma((&kk[i + 2].x)[c], sk[1][c], ks);
                            ks = hfma((&kk[i + 3].x)[c], sk[0][c], ks);
                        } else {
                            ks = hadd(ks, hmul((&kk[i + 1].x)[c], sk[2][c]));
                            ks = hadd(ks, hmul((&kk[i + 2].x)[c], sk[1][c]));
                            ks = hadd(ks, hmul((&kk[i + 3].x)[c], sk[0][c]));
                        }
                        res[i] = hmul(ks, (&vv[i].x)[c]);
                    }
                    sts128(ua + (2 * c) * 2048, __byte_perm(res[0], res[1], 0x5410), __byte_perm(res[2], res[3], 0x5410),
                           __byte_perm(res[4], res[5], 0x5410), __byte_perm(res[6], res[7], 0x5410));
                    sts128(ua + (2 * c + 1) * 2048, __byte_perm(res[0], res[1], 0x7632), __byte_perm(res[2], res[3], 0x7632),
                           __byte_perm(res[4], res[5], 0x7632), __byte_perm(res[6], res[7], 0x7632));
                }
                fence_async_smem();
                __syncwarp();
                if (lane == 0) mbar_arrive(bar_stg + 8 * bt);
                if (t == 0) STAMP(0, 21 + bt);
            }
        }
        {
            const int row = bid * 16 + (t >> 3);
            if (GWAIT) mbar_wait(bar_kvrel, 0);
            uint4 xv[16];
#pragma unroll
            for (int n = 0; n < 16; ++n) {
                xv[n] = ldg128(x + (size_t)row * D_DIM + ((t & 7) + 8 * n) * 8);
                if (KVFINE ? (n & 1) : (n & 3) == 3) __nanosleep(GAP_KV);
            }
#pragma unroll
            for (int n8 = 0; n8 < 16; n8 += 8) {
                uint4 wv[8];
#pragma unroll
                for (int n = 0; n < 8; ++n) wv[n] = ldg128(gate_w + ((t & 7) + 8 * (n8 + n)) * 8);
#pragma unroll
                for (int n = 0; n < 8; ++n) {
                    uint4& p = xv[n8 + n];
                    p.x = hmul(p.x, wv[n].x); p.y = hmul(p.y, wv[n].y); p.z = hmul(p.z, wv[n].z); p.w = hmul(p.w, wv[n].w);
                }
            }
            float d[4] = {0.f, 0.f, 0.f, 0.f};
            fence_regs(d);
            named_bar(3, 128);
            wgmma_fence();
#pragma unroll
            for (int n = 0; n < 16; ++n)
                asm volatile("{\n.reg .b64 db;\nmov.b64 db, {%8, 8};\n"
                             "wgmma.mma_async.sync.aligned.m64n8k16.f32.bf16.bf16 {%0, %1, %2, %3}, {%4, %5, %6, %7}, db, 1, 1, 1, 0;\n}\n"
                             : "+f"(d[0]), "+f"(d[1]), "+f"(d[2]), "+f"(d[3]) : "r"(xv[n].x), "r"(xv[n].y), "r"(xv[n].z), "r"(xv[n].w), "r"(desc_lo(w_ones, 128)));
            wgmma_commit();
            wgmma_wait<0>();
            fence_regs(d);
#pragma unroll
            for (int n = 0; n < 16; ++n) asm volatile("" ::"r"(xv[n].x), "r"(xv[n].y), "r"(xv[n].z), "r"(xv[n].w) : "memory");
            float sum = d[0] + d[2];
            sum += __shfl_xor_sync(0xffffffffu, sum, 4);
            if ((t & 7) == 0) g_gate[row] = bf16r(1.f / (1.f + expf(-bf16r(sum))));
            if (t == 0) STAMP(0, 4);
            __syncwarp();
            if (lane == 0) mbar_arrive(bar_gate);
        }
        Twiddle tw;
        load_twiddle(tw, reinterpret_cast<const uint4*>(g_tw_tab.w) + t);
        const uint32_t lo = (uint32_t)((16 * w4 + (lane & 7)) * 64 + (((lane >> 3) ^ ((lane >> 1) & 3)) << 4));
        const uint32_t tlo = desc_lo(sbase + OFF_CT, 16);
        float dE[32], dO[32];
        mbar_wait(bar_tab, 0);
        mbar_wait(bar_k, 0);
        if (CWAIT) mbar_wait(bar_ascan, 0);
        if (t == 0) STAMP(0, 1);
        wgmma_fence();
        conv_s1(dE, dO, tlo, desc_lo(sbase + conv_buf(0), 8192));
        wgmma_commit();
        wgmma_wait<0>();
        fence_regs(dE); fence_regs(dO);
        named_bar(3, 128);
#pragma unroll 1
        for (int p = 0; p < 4; p = 2 * p + 1) {
            const int pn = min(2 * p + 1, 3);
            if (t == 0) STAMP(0, 40 + 5 * p);
            conv_pair<true>(dE, dO, tw, lds32(w_dsk + ((lane & 3) ? 16 : 4 * p)), tlo, sbase + conv_buf(0) + (p == 1 ? 16384 : 0),
                            sbase + conv_buf(0) + (p == 0 ? 16384 : 0), lo, 3,
                            [&]() { if (t == 0) STAMP(0, 42 + 5 * p); mbar_wait(bar_k + 8 * pn, 0); if (t == 0) STAMP(0, 43 + 5 * p); });
            if (lane == 0) mbar_arrive(bar_stg + 16 + 8 * p);
        }
        if (t == 0) STAMP(0, 59);
        __syncwarp();
    } else {
        asm volatile("setmaxnreg.inc.sync.aligned.u32 %0;" ::"n"(REG_AB));
        const int cw = wg - 1;
        const int t = tid & 127, w4 = t >> 5, g = lane >> 2, t4 = lane & 3;
        {
            float a0[64], a1[64];
            auto release = [&](int it) {
                if (it < 12 + XTRA && t <= ((it >= 16 - SKEW1 && it < 12) || it >= 16)) mbar_arrive(bar_empty + 8 * (it & 3));
            };
#pragma unroll 1
            for (int kb = 0; kb < 16; ++kb) {
                const int it = cw == 1 && kb >= 16 - SKEW1 ? kb + XTRA : kb, st = it & 3;
                if (cw == 1 && kb == 16 - SKEW1) mbar_wait(bar_ab, 0);
                mbar_wait(bar_full + 8 * st, (it >> 2) & 1);
                if (kb == 0 && t == 0) STAMP(1, 14 + cw);
                const uint32_t alo = desc_lo(sbase + (cw ? OFF_BB : OFF_CU) + st * 8192, 16), blo = desc_lo(sbase + ((it - XTRA) & 3) * 32768, 16);
                wgmma_fence();
#pragma unroll
                for (int k = 0; k < 4; ++k) {
                    wgmma_n128<0>(a0, alo + 2 * k, blo + 2 * k, k ? 1 : kb);
                    if (!G1ORD) wgmma_n128<0>(a1, alo + 2 * k, blo + 1024 + 2 * k, k ? 1 : kb);
                }
                if (G1ORD) {
#pragma unroll
                    for (int k = 0; k < 4; ++k) wgmma_n128<0>(a1, alo + 2 * k, blo + 1024 + 2 * k, k ? 1 : kb);
                }
                wgmma_commit();
                wgmma_wait<1>();
                if (kb > 0 && !(cw == 1 && kb == 16 - SKEW1)) release(it - 1);
                if (cw == 1 && kb == 15 - SKEW1) {
                    wgmma_wait<0>();
                    release(it);
                }
                if (cw == 1 && kb > 12) {
                    if (kb == 13) mbar_wait(bar_adone, 0);
                    if (t == 0) mbar_arrive(bar_empty2 + 8 * (kb - 13));
                }
            }
            if (tid == 192) mbar_arrive(bar_ab);
            float mr, mi, cr, ci, p32r, p32i;
            uint32_t tag;
            mbar_wait(bar_par, 0);
            {
                const uint32_t par = sbase + OFF_PAR + (cw * 32 + w4 * 8 + g) * 32;
                uint32_t dummy;
                asm volatile("ld.shared.v4.f32 {%0,%1,%2,%3}, [%4];" : "=f"(mr), "=f"(mi), "=f"(cr), "=f"(ci) : "r"(par));
                asm volatile("ld.shared.v4.b32 {%0,%1,%2,%3}, [%4];" : "=f"(p32r), "=f"(p32i), "=r"(tag), "=r"(dummy) : "r"(par + 16));
            }
            const float l1i = SW ? mi : -mi;
            auto map = [&](float p, float q, float& r, float& i) {
                if (SW) { r = fmaf(cr, q, -ci * p); i = fmaf(-cr, p, -ci * q); }
                else { r = fmaf(cr, p, -ci * q); i = fmaf(-cr, q, -ci * p); }
            };
            float p64r = p32r, p64i = p32i;
            csqr(p64r, p64i);
            float p128r = p64r, p128i = p64i;
            csqr(p128r, p128i);
            wgmma_wait<0>();
            fence_regs(a0); fence_regs(a1);
            if (cw == 0) { release(15); if (lane == 0) mbar_arrive(bar_adone); }
            else if (t == 0) mbar_arrive(bar_empty2 + 24);
            if (t == 0) STAMP(1, 2 + 6 * cw);
            if (BWAIT == 1 && cw == 1) mbar_wait(bar_ascan, 0);
            float hr = 0.f, hi = 0.f, ar = 0.f, ai = 0.f;
#pragma unroll
            for (int j = 0; j < 16; ++j)
#pragma unroll
                for (int e = 0; e < 2; ++e) {
                    const float nr = fmaf(mr, ar, fmaf(-l1i, ai, a0[4 * j + e])), ni = fmaf(mr, ai, fmaf(l1i, ar, a0[4 * j + 2 + e]));
                    const float or_ = fmaf(mr, hr, fmaf(-l1i, hi, a1[4 * j + e])), oi = fmaf(mr, hi, fmaf(l1i, hr, a1[2 + 4 * j + e]));
                    ar = nr; ai = ni; hr = or_; hi = oi;
                }
            map(ar, ai, ar, ai);
            map(hr, hi, hr, hi);
            hr += p32r * ar - p32i * ai; hi += p32r * ai + p32i * ar;
            {
                float vr = __shfl_up_sync(0xffffffffu, hr, 1, 4), vi = __shfl_up_sync(0xffffffffu, hi, 1, 4);
                if (t4 >= 1) { hr += p64r * vr - p64i * vi; hi += p64r * vi + p64i * vr; }
                vr = __shfl_up_sync(0xffffffffu, hr, 2, 4); vi = __shfl_up_sync(0xffffffffu, hi, 2, 4);
                if (t4 >= 2) { hr += p128r * vr - p128i * vi; hi += p128r * vi + p128i * vr; }
            }
            unsigned long long* ap = &g_agg[ti * D_DIM + cw * 512 + cg * 32 + w4 * 8 + g];
            if (t4 == 3) asm volatile("{\n.reg .b64 a;\nmov.b64 a, {%1, %2};\nst.relaxed.gpu.global.u64 [%0], a;\n}\n" ::"l"(ap),
                                      "r"((__float_as_uint(hr) & ~1u) | (tag & 1u)), "r"((__float_as_uint(hi) & ~1u) | (tag >> 1)) : "memory");
            float exr = __shfl_up_sync(0xffffffffu, hr, 1, 4), exi = __shfl_up_sync(0xffffffffu, hi, 1, 4);
            if (t4 == 0) { exr = 0.f; exi = 0.f; }
            if (t == 0) STAMP(1, 3 + 6 * cw);
            if (BWAIT == 2 && cw == 1) mbar_wait(bar_ascan, 0);
            ci = after(ci, exr);
#pragma unroll
            for (int j = 0; j < 16; ++j)
#pragma unroll
                for (int e = 0; e < 2; ++e) {
                    map(a0[4 * j + e], a0[4 * j + 2 + e], a0[4 * j + e], a0[4 * j + 2 + e]);
                    map(a1[4 * j + e], a1[4 * j + 2 + e], a1[4 * j + e], a1[4 * j + 2 + e]);
                }
            float qr = 1.f, qi = 0.f, ur = 1.f, ui = 0.f;
            if (t4 & 1) { qr = p64r; qi = p64i; }
            if (t4 & 2) cmul(qr, qi, qr, qi, p128r, p128i);
            csqr(p128r, p128i);
            if (t4 & 1) { ur = p128r; ui = p128i; }
            csqr(p128r, p128i);
            if (t4 & 2) cmul(ur, ui, ur, ui, p128r, p128i);
            csqr(p128r, p128i);
            fence_regs(a0); fence_regs(a1);
            if (t == 0) STAMP(1, 7 + 6 * cw);
            if (ti > 0) {
                const unsigned long long tmask = 0x0000000100000001ull, tval = ((unsigned long long)(tag >> 1) << 32) | (tag & 1u);
                unsigned long long u0 = tval, u1 = tval;
                ap -= D_DIM * (1 + t4);
                int it = 0;
                do {
                    asm volatile("{\n.reg .pred p, q;\nsetp.gt.s32 p, %3, 0;\nsetp.gt.s32 q, %3, 4;\n@p ld.relaxed.gpu.global.u64 %0, [%2];\n"
                                 "@q ld.relaxed.gpu.global.u64 %1, [%2+-32768];\n}\n" : "+l"(u0), "+l"(u1) : "l"(ap), "r"(ti - t4) : "memory");
                } while (__any_sync(0xffffffffu, (((u0 ^ tval) | (u1 ^ tval)) & tmask) != 0) && ++it < (1 << 22));
                float Pr = __uint_as_float((unsigned)u1 & ~1u), Pi = __uint_as_float((unsigned)(u1 >> 32) & ~1u);
                cmul(Pr, Pi, Pr, Pi, p128r, p128i);
                Pr += __uint_as_float((unsigned)u0 & ~1u); Pi += __uint_as_float((unsigned)(u0 >> 32) & ~1u);
                cmul(Pr, Pi, Pr, Pi, ur, ui);
                Pr += __shfl_xor_sync(0xffffffffu, Pr, 1); Pi += __shfl_xor_sync(0xffffffffu, Pi, 1);
                Pr += __shfl_xor_sync(0xffffffffu, Pr, 2); Pi += __shfl_xor_sync(0xffffffffu, Pi, 2);
                exr += qr * Pr - qi * Pi;
                exi += qr * Pi + qi * Pr;
            }
            if (t == 0) STAMP(1, 4 + 6 * cw);
            char* hp = reinterpret_cast<char*>(g_H) + (size_t)((2 * ti) * 16 + (cg >> 1)) * 16384 + ((cg & 1) * 32 + w4 * 8 + g) * 64 + ((t4 ^ (g >> 1)) << 4);
            float fxr = ar + p32r * exr - p32i * exi, fxi = ai + p32r * exi + p32i * exr;
            const uint32_t hs = sbase + OFF_BB + (w4 * 8 + g) * 64 + ((t4 ^ (g >> 1)) << 4);
            if (cw == 1) named_bar(2, 128);
            uint32_t im[32];
#pragma unroll
            for (int jj = 0; jj < 4; ++jj) {
                uint32_t pr[4], qq[4];
#pragma unroll
                for (int j4 = 0; j4 < 4; ++j4) {
                    const int j = jj * 4 + j4;
                    const float r0 = fmaf(mr, exr, fmaf(-mi, exi, a0[4 * j])), i0 = fmaf(mr, exi, fmaf(mi, exr, a0[4 * j + 2]));
                    const float r1 = fmaf(mr, fxr, fmaf(-mi, fxi, a1[4 * j])), i1 = fmaf(mr, fxi, fmaf(mi, fxr, a1[2 + 4 * j]));
                    exr = fmaf(mr, r0, fmaf(-mi, i0, a0[4 * j + 1]));
                    exi = fmaf(mr, i0, fmaf(mi, r0, a0[4 * j + 3]));
                    fxr = fmaf(mr, r1, fmaf(-mi, i1, a1[1 + 4 * j]));
                    fxi = fmaf(mr, i1, fmaf(mi, r1, a1[3 + 4 * j]));
                    pr[j4] = pack_bf16(r0, exr); im[j] = pack_bf16(i0, exi);
                    qq[j4] = pack_bf16(r1, fxr); im[16 + j] = pack_bf16(i1, fxi);
                }
                if (cw == 0) {
                    stg128(hp + jj * 4096, pr[0], pr[1], pr[2], pr[3]);
                    stg128(hp + jj * 4096 + 262144, qq[0], qq[1], qq[2], qq[3]);
                } else {
                    sts128(hs + jj * 2048, pr[0], pr[1], pr[2], pr[3]);
                    sts128(hs + jj * 2048 + 8192, qq[0], qq[1], qq[2], qq[3]);
                }
            }
            if (t == 0) STAMP(1, 5 + 6 * cw);
            if (cw == 0) {
                if (lane == 0) mbar_arrive(bar_ascan);
                named_bar(1, 128);
                if (t == 0) { red_release(&g_cnt[(4 * ti) * 32], 4); mbar_arrive(bar_rel); }
                named_bar(1, 128);
                if (t == 0) STAMP(1, 6);
#pragma unroll
                for (int jj = 0; jj < 8; ++jj) stg128(hp + 131072 + (jj & 3) * 4096 + (jj >> 2) * 262144, im[4 * jj], im[4 * jj + 1], im[4 * jj + 2], im[4 * jj + 3]);
            } else {
#pragma unroll
                for (int jj = 0; jj < 8; ++jj) sts128(hs + 16384 + jj * 2048, im[4 * jj], im[4 * jj + 1], im[4 * jj + 2], im[4 * jj + 3]);
                fence_async_smem();
            }
            __syncwarp();
            if (lane == 0) mbar_arrive(bar_hw + 8 * cw + 8);
            if (t == 0) STAMP(1, 50 + cw);
        }
        if (cw == 1) {
            const int t = fresh_tid() & 127, lane = t & 31, w4 = t >> 5;
            Twiddle tw;
            load_twiddle(tw, reinterpret_cast<const uint4*>(g_tw_tab.w) + t);
            const uint32_t lo = (uint32_t)((16 * w4 + (lane & 7)) * 64 + (((lane >> 3) ^ ((lane >> 1) & 3)) << 4));
            const uint32_t tlo = desc_lo(sbase + OFF_CT, 16);
            float dE[32], dO[32];
            mbar_wait(bar_stg, 0);
            mbar_wait(bar_tab, 0);
            mbar_wait(bar_k + 16, 0);
            if (t == 0) STAMP(0, 50);
            wgmma_fence();
            conv_s1(dE, dO, tlo, desc_lo(sbase + conv_buf(2), 8192));
            wgmma_commit();
            wgmma_wait<0>();
            fence_regs(dE); fence_regs(dO);
            named_bar(2, 128);
            conv_pair<false>(dE, dO, tw, lds32(w_dsk + ((lane & 3) ? 16 : 8)), tlo, sbase + conv_buf(2), 0, lo, 2, []() {});
            if (lane == 0) mbar_arrive(bar_stg + 32);
            {
            const int t = fresh_tid() & 127, lane = t & 31, w4 = t >> 5, g = lane >> 2, t4 = lane & 3;
            const int bid = lds32(w_bid), dt = bid & 7;
            const int trow = (bid >> 4) * 256 + 4 * (bid & 8) + 128 * (w4 & 1) + 8 * (w4 >> 1) + g;
            uint4 xv[16], dk[4];
            const __nv_bfloat16* xp = x + (size_t)trow * D_DIM + dt * 128 + 8 * t4;
#pragma unroll
            for (int i = 0; i < 16; ++i) {
                xv[i] = ldg128(xp + (size_t)(16 * (i >> 3) + 64 * ((i >> 2) & 1)) * D_DIM + 32 * (i & 3));
                if (i & 1) __nanosleep(GAP_X);
            }
#pragma unroll
            for (int jq = 0; jq < 4; ++jq) dk[jq] = ldg128(dskip + dt * 128 + 32 * jq + 8 * t4);
            mbar_wait(bar_fh, 0);
            uint32_t omg[4], g2[4];
#pragma unroll
            for (int i = 0; i < 4; ++i) {
                const float gt = __ldcg(g_gate + trow + 16 * (i >> 1) + 64 * (i & 1));
                if (t4 == 0) asm volatile("st.shared.f32 [%0], %1;" ::"r"(sbase + OFF_PAR + (64 * (i >> 1) + 16 * w4 + 8 * (i & 1) + g) * 4), "f"(gt) : "memory");
                omg[i] = pack_bf16(2.f - 2.f * gt, 2.f - 2.f * gt); g2[i] = pack_bf16(gt, gt);
            }
            if (t == 0) {
                mbar_wait(bar_yrel, 0);
                wait_counter(&g_cnt[(48 + dt) * 32], lds32(w_bid + 4));
                STAMP(0, 16);
                mbar_expect_tx(bar_y1, 24576);
#pragma unroll 1
                for (int i = 0; i < 6; ++i) {
                    tma_load_5d(sbase + OFF_CU + i * 4096, &maps.yt, bar_y1, (bid & 8) * 128 + (bid >> 4) * 128 + (i & 1) * 64, 0, 0, i >> 1, dt * 4);
                    if (GAP_Y1) __nanosleep(GAP_Y1);
                }
            }
            __syncwarp();
            const uint32_t ya = sbase + OFF_CU + (w4 & 1) * 4096 + lane * 128 + ((((w4 >> 1) ^ ((bid >> 3 & 2) + (w4 & 1))) ^ (lane & 7)) << 4);
#pragma unroll
            for (int p = 0; p < 4; ++p) {
                if (p == 0) mbar_wait(bar_y1, 0);
                if (p == 3) {
                    if (t == 0) STAMP(0, 17);
                    mbar_wait(bar_y, 0);
                    if (t == 0) STAMP(0, 6);
                }
#pragma unroll
                for (int i = 0; i < 4; ++i) {
                    uint32_t yw[4];
                    ldsm_x4_t(yw[0], yw[1], yw[2], yw[3], (ya ^ ((i & 1) << 6) ^ ((i & 2) << 4)) + p * 8192);
#pragma unroll
                    for (int jq = 0; jq < 4; ++jq) {
                        uint32_t& w = (&xv[4 * i + jq].x)[p];
                        w = hfma(g2[i], hmul(w, (&dk[jq].x)[p]), hmul(omg[i], hmul(w, yw[jq])));
                    }
                }
            }
            named_bar(2, 128);
#pragma unroll
            for (int i = 0; i < 16; ++i) {
                sts128(sbase + (i & 8 ? OFF_CT : OFF_CU) + (i & 3) * 8192 + (w4 * 16 + g + (i & 4) * 2) * 128 + (((2 * t4) ^ g) << 4), xv[i].x, xv[i].y, xv[i].z, xv[i].w);
                if ((i & 7) == 7) {
                    __syncwarp();
                    if (lane == 0) mbar_arrive(bar_bias + (i & 8));
                }
            }
            if (t == 0) STAMP(0, 7);
            }
        }
        if (cw == 0) {
            float c0[64], c1[64];
            int st = 0, pst = 0;
            uint32_t ph = 0;
            auto kblock = [&](int kb, auto shallow) {
                const int t = fresh_tid() & 127, lane = t & 31;
                mbar_wait(bar_full2 + 8 * st, st == 4 ? ph ^ PH4 : ph);
                if (kb == 0 && t == 0) STAMP(2, 6);
                if (kb == G2SIG && lane == 0) mbar_arrive(bar_g2);
                const uint32_t alo = desc_lo(sbase + st * 32768, 4096), blo = desc_lo(sbase + st * 32768 + 16384, 16);
                constexpr int Q = decltype(shallow)::value;
#pragma unroll
                for (int j = 0; j < 8; ++j) {
                    wgmma_fence();
                    if (j & 1) wgmma_n128<1>(c1, alo + 512 + 64 * (j >> 1), blo + 2 * (j >> 1), j >> 1 ? 1 : kb);
                    else wgmma_n128<1>(c0, alo + 64 * (j >> 1), blo + 2 * (j >> 1), j >> 1 ? 1 : kb);
                    wgmma_commit();
                    wgmma_wait<Q>();
                    if (j == Q - 1 && kb > 0 && t == 0) mbar_arrive(bar_empty2 + 8 * pst);
                }
                pst = st;
                if (++st == (kb < SLOT4 - 1 ? 4 : 5)) { st = 0; ph ^= 1; }
            };
#pragma unroll 1
            for (int kb = 0; kb < QKB; ++kb) kblock(kb, std::integral_constant<int, QD>());
#pragma unroll 1
            for (int kb = QKB; kb < 32 - SKEW2; ++kb) kblock(kb, std::integral_constant<int, QD2>());
            static_assert(SKEW2 <= 4, "slot release");
            const uint32_t alo = desc_lo(sbase, 4096), blo = desc_lo(sbase + 16384, 16);
#pragma unroll
            for (int kb = 32 - SKEW2; kb < 32; ++kb) {
                mbar_wait(bar_full2 + 8 * ring_slot(kb), ring_par(kb));
                wgmma_fence();
#pragma unroll
                for (int k = 0; k < 4; ++k) wgmma_n128<1>(c0, alo + ring_slot(kb) * 2048 + 64 * k, blo + ring_slot(kb) * 2048 + 2 * k, 1);
                wgmma_commit();
            }
            auto late = [&](int kb) {
                wgmma_fence();
#pragma unroll
                for (int k = 0; k < 4; ++k) wgmma_n128<1>(c1, alo + 512 + ring_slot(kb) * 2048 + 64 * k, blo + ring_slot(kb) * 2048 + 2 * k, 1);
                wgmma_commit();
            };
            late(32 - SKEW2);
            const int t = fresh_tid() & 127, lane = t & 31, w4 = t >> 5, g = lane >> 2, t4 = lane & 3;
            auto epilogue = [&](const float (&a)[64], int b) {
                const uint32_t ad0 = sbase + (b ? OFF_CT : OFF_CU) + (w4 * 16 + g) * 128 + (((2 * t4) ^ g) << 4);
                float gt[2];
                uint32_t bv[4][4];
#pragma unroll
                for (int h = 0; h < 2; ++h) gt[h] = __uint_as_float(lds32(sbase + OFF_PAR + (64 * b + 16 * w4 + 8 * h + g) * 4));
#pragma unroll
                for (int i = 0; i < 4; ++i)
                    asm volatile("ld.shared.v4.b32 {%0,%1,%2,%3}, [%4];" : "=r"(bv[i][0]), "=r"(bv[i][1]), "=r"(bv[i][2]), "=r"(bv[i][3])
                                 : "r"(ad0 + (i & 1) * 1024 + (i >> 1) * 8192) : "memory");
                if (b == 0) wgmma_wait<1>(); else wgmma_wait<0>();
                if (b == 0) fence_regs(c0); else fence_regs(c1);
                if (t == 0) STAMP(2, b ? 2 : 5);
#pragma unroll
                for (int jq = 0; jq < 4; ++jq) {
                    if (b == 0 && jq < SKEW2 - 1) late(33 - SKEW2 + jq);
#pragma unroll
                    for (int h = 0; h < 2; ++h) {
                        const uint32_t ad = ad0 + h * 1024 + jq * 8192;
                        uint32_t (&w)[4] = bv[2 * (jq & 1) + h];
                        const int r = 16 * jq + 2 * h;
                        sts128(ad, __float_as_uint(fmaf(gt[h], a[r], bf_lo(w[0]))), __float_as_uint(fmaf(gt[h], a[r + 1], bf_hi(w[0]))),
                               __float_as_uint(fmaf(gt[h], a[r + 4], bf_lo(w[1]))), __float_as_uint(fmaf(gt[h], a[r + 5], bf_hi(w[1]))));
                        sts128(ad ^ 16, __float_as_uint(fmaf(gt[h], a[r + 8], bf_lo(w[2]))), __float_as_uint(fmaf(gt[h], a[r + 9], bf_hi(w[2]))),
                               __float_as_uint(fmaf(gt[h], a[r + 12], bf_lo(w[3]))), __float_as_uint(fmaf(gt[h], a[r + 13], bf_hi(w[3]))));
                        if (jq < 2) asm volatile("ld.shared.v4.b32 {%0,%1,%2,%3}, [%4];" : "=r"(w[0]), "=r"(w[1]), "=r"(w[2]), "=r"(w[3]) : "r"(ad + 16384) : "memory");
                    }
                    fence_async_smem();
                    __syncwarp();
                    if (lane == 0) mbar_arrive(bar_stg + 48 + 32 * b + 8 * jq);
                }
            };
            mbar_wait(bar_bias, 0);
            if (t == 0) STAMP(2, 4);
            epilogue(c0, 0);
            mbar_wait(bar_bias + 8, 0);
            epilogue(c1, 1);
            if (t == 0) STAMP(2, 7);
        }
    }
}

void make_map(CUtensorMap* m, const void* ptr, int rank, const cuuint64_t* dims, const cuuint64_t* strides, const cuuint32_t* box,
              CUtensorMapSwizzle swz, bool f32 = false) {
    cuuint32_t es[5] = {1, 1, 1, 1, 1};
    get_encode()(m, f32 ? CU_TENSOR_MAP_DATA_TYPE_FLOAT32 : CU_TENSOR_MAP_DATA_TYPE_BFLOAT16, rank, const_cast<void*>(ptr), dims, strides, box, es,
                 CU_TENSOR_MAP_INTERLEAVE_NONE, swz, CU_TENSOR_MAP_L2_PROMOTION_L2_256B, CU_TENSOR_MAP_FLOAT_OOB_FILL_NONE);
}
void make_map_2d(CUtensorMap* m, const void* ptr, uint64_t inner, uint64_t outer, uint32_t box_in, uint32_t box_out) {
    cuuint64_t dims[2] = {inner, outer};
    cuuint64_t strides[1] = {inner * 2};
    cuuint32_t box[2] = {box_in, box_out};
    make_map(m, ptr, 2, dims, strides, box, CU_TENSOR_MAP_SWIZZLE_128B);
}
void make_map_conv(CUtensorMap* m, const void* p, uint32_t nch = 2) {
    cuuint64_t dims[4] = {32, 32, 2, 1024};
    cuuint64_t strides[3] = {128, 64, 4096};
    cuuint32_t box[4] = {32, 32, 2, nch};
    make_map(m, p, 4, dims, strides, box, CU_TENSOR_MAP_SWIZZLE_64B);
}

}

extern "C" void kernel_launch(void* const* d_in, const int* in_sizes, int n_in, void* d_out, int out_size) {
    const __nv_bfloat16* x = (const __nv_bfloat16*)d_in[0];
    const __nv_bfloat16* lam_re = (const __nv_bfloat16*)d_in[1];
    const __nv_bfloat16* lam_im = (const __nv_bfloat16*)d_in[2];
    const __nv_bfloat16* b_re = (const __nv_bfloat16*)d_in[3];
    const __nv_bfloat16* b_im = (const __nv_bfloat16*)d_in[4];
    const __nv_bfloat16* c_re = (const __nv_bfloat16*)d_in[5];
    const __nv_bfloat16* c_im = (const __nv_bfloat16*)d_in[6];
    const __nv_bfloat16* log_dt = (const __nv_bfloat16*)d_in[7];
    const __nv_bfloat16* dskip = (const __nv_bfloat16*)d_in[8];
    const __nv_bfloat16* kin = (const __nv_bfloat16*)d_in[10];
    const __nv_bfloat16* vin = (const __nv_bfloat16*)d_in[11];
    const __nv_bfloat16* shift_k = (const __nv_bfloat16*)d_in[12];
    const __nv_bfloat16* ssm_k = (const __nv_bfloat16*)d_in[13];
    const __nv_bfloat16* ssm_D = (const __nv_bfloat16*)d_in[14];
    const __nv_bfloat16* gate_w = (const __nv_bfloat16*)d_in[15];
    float* out = (float*)d_out;

    void *yptr = nullptr, *kvtptr = nullptr;
    cudaGetSymbolAddress(&yptr, g_y2);
    cudaGetSymbolAddress(&kvtptr, g_kvT);

    Maps maps;
    {
        cuuint64_t dims[5] = {1024, 2, 4, 32, 8};
        cuuint64_t strides[4] = {2048, 64 * 2048, 2 * 2048, 256 * 2048};
        cuuint32_t box[5] = {64, 2, 4, 32, 1};
        make_map(&maps.x5, x, 5, dims, strides, box, CU_TENSOR_MAP_SWIZZLE_128B);
    }
    int bmode = 0;
    {
        const uint64_t a = (uint64_t)b_re, b = (uint64_t)b_im;
        const uint64_t delta = a < b ? b - a : a - b;
        if (delta != 0 && (delta & 15) == 0 && delta < (1ull << 40)) bmode = a < b ? 1 : 2;
        cuuint64_t dims[4] = {1024, 8, 2, 128};
        cuuint64_t strides[3] = {2048, bmode ? delta : 16, 16384};
        cuuint32_t box[4] = {64, 8, 2, 4};
        make_map(&maps.b4, a < b ? b_re : b_im, 4, dims, strides, box, CU_TENSOR_MAP_SWIZZLE_128B);
    }
    make_map_2d(&maps.bre, b_re, 1024, 1024, 64, 8);
    make_map_2d(&maps.bim, b_im, 1024, 1024, 64, 8);
    {
        cuuint64_t dims[3] = {S_LEN, 128, 8};
        cuuint64_t strides[2] = {8 * 4096, 4096};
        cuuint32_t box[3] = {64, 16, 2};
        make_map(&maps.kvst, kvtptr, 3, dims, strides, box, CU_TENSOR_MAP_SWIZZLE_128B);
    }
    make_map_conv(&maps.sk, ssm_k, 1);
    for (int i = 0; i < 2; ++i) {
        cuuint64_t dims[5] = {1024, 2, 4, 4, 32};
        cuuint64_t strides[4] = {2048, 8 * 2048, 2 * 2048, 32 * 2048};
        cuuint32_t box[5] = {64, 2, 4, 4, 4};
        make_map(i ? &maps.cim : &maps.cre, i ? c_im : c_re, 5, dims, strides, box, CU_TENSOR_MAP_SWIZZLE_128B);
    }
    {
        cuuint64_t dims[5] = {S_LEN, 2, 4, 4, 32};
        cuuint64_t strides[4] = {4096, 8 * 4096, 2 * 4096, 32 * 4096};
        cuuint32_t box[5] = {64, 2, 4, 1, 4};
        make_map(&maps.yt, yptr, 5, dims, strides, box, CU_TENSOR_MAP_SWIZZLE_128B);
    }
    {
        cuuint64_t dims[5] = {D_DIM, 8, 4, 8, 8};
        cuuint64_t strides[4] = {4096, 64 * 4096, 8 * 4096, 256 * 4096};
        cuuint32_t box[5] = {32, 8, 4, 2, 1};
        make_map(&maps.out, out, 5, dims, strides, box, CU_TENSOR_MAP_SWIZZLE_128B, true);
    }

    for (int sm = 0; sm < 132; ++sm) {
        const int tpc = sm >> 1;
        const int gp = tpc < 32 ? tpc & 7 : tpc < 60 ? 1 + (tpc - 32) % 7 : 0, ix = tpc < 32 ? tpc >> 3 : tpc < 60 ? 4 + (tpc - 32) / 7 : tpc - 58;
        maps.tile[sm] = (tpc | 1) == 61 ? 128 : (4 * (gp >> 1) + (ix >> 1)) * 8 + 4 * (gp & 1) + 2 * (ix & 1) + (sm & 1);
    }
    auto kern = bmode == 1 ? fused_kernel<1> : bmode == 2 ? fused_kernel<2> : fused_kernel<0>;
    cudaFuncSetAttribute(kern, cudaFuncAttributeMaxDynamicSharedMemorySize, SMEM_BYTES);
    static int grid = 0;
    if (!grid) {
        int dev = 0, sms = 0;
        cudaGetDevice(&dev);
        cudaDeviceGetAttribute(&sms, cudaDevAttrMultiProcessorCount, dev);
        grid = sms == 132 ? 132 : 128;
    }
    kern<<<grid, 512, SMEM_BYTES>>>(x, kin, vin, ssm_k, shift_k, ssm_D, lam_re, lam_im, log_dt, gate_w, dskip, c_re, c_im, maps);
}
```

```cpp
#include <cuda_runtime.h>
#include <cuda_bf16.h>
#include <cuda.h>
#include <stdint.h>
#include <type_traits>

namespace {
__device__ __forceinline__ uint32_t smem_u32(const void* p) { return (uint32_t)__cvta_generic_to_shared(p); }
__device__ __forceinline__ void mbar_init(uint32_t bar, uint32_t count) {
    asm volatile("mbarrier.init.shared::cta.b64 [%0], %1;" ::"r"(bar), "r"(count) : "memory");
}
__device__ __forceinline__ void mbar_expect_tx(uint32_t bar, uint32_t bytes) {
    asm volatile("mbarrier.arrive.expect_tx.shared::cta.b64 _, [%0], %1;" ::"r"(bar), "r"(bytes) : "memory");
}
__device__ __forceinline__ void mbar_arrive(uint32_t bar) {
    asm volatile("mbarrier.arrive.shared::cta.b64 _, [%0];" ::"r"(bar) : "memory");
}
__device__ __forceinline__ void mbar_wait(uint32_t bar, uint32_t parity) {
    asm volatile(
        "{\n"
        ".reg .pred p;\n"
        ".reg .u32 n;\n"
        "mov.u32 n, 0;\n"
        "LAB_WAIT:\n"
        "mbarrier.try_wait.parity.shared::cta.b64 p, [%0], %1;\n"
        "@p bra LAB_DONE;\n"
        "add.u32 n, n, 1;\n"
        "setp.lt.u32 p, n, 0x400000;\n"
        "@p bra LAB_WAIT;\n"
        "trap;\n"
        "LAB_DONE:\n"
        "}\n" ::"r"(bar), "r"(parity) : "memory");
}
__device__ __forceinline__ void tma_load_2d(uint32_t dst, const CUtensorMap* map, uint32_t bar, int c0, int c1) {
    asm volatile(
        "cp.async.bulk.tensor.2d.shared::cluster.global.mbarrier::complete_tx::bytes [%0], [%1, {%3, %4}], [%2];"
        ::"r"(dst), "l"((uint64_t)map), "r"(bar), "r"(c0), "r"(c1) : "memory");
}
__device__ __forceinline__ void tma_load_4d(uint32_t dst, const CUtensorMap* map, uint32_t bar, int c0, int c1, int c2, int c3) {
    asm volatile(
        "cp.async.bulk.tensor.4d.shared::cluster.global.mbarrier::complete_tx::bytes [%0], [%1, {%3, %4, %5, %6}], [%2];"
        ::"r"(dst), "l"((uint64_t)map), "r"(bar), "r"(c0), "r"(c1), "r"(c2), "r"(c3) : "memory");
}
__device__ __forceinline__ void tma_load_5d(uint32_t dst, const CUtensorMap* map, uint32_t bar, int c0, int c1, int c2, int c3, int c4) {
    asm volatile(
        "cp.async.bulk.tensor.5d.shared::cluster.global.mbarrier::complete_tx::bytes [%0], [%1, {%3, %4, %5, %6, %7}], [%2];"
        ::"r"(dst), "l"((uint64_t)map), "r"(bar), "r"(c0), "r"(c1), "r"(c2), "r"(c3), "r"(c4) : "memory");
}
__device__ __forceinline__ void bulk_load(uint32_t dst, const void* src, uint32_t bytes, uint32_t bar) {
    asm volatile("cp.async.bulk.shared::cluster.global.mbarrier::complete_tx::bytes [%0], [%1], %2, [%3];"
                 ::"r"(dst), "l"(src), "r"(bytes), "r"(bar) : "memory");
}
__device__ __forceinline__ void tma_store_3d(const CUtensorMap* map, uint32_t src, int c0, int c1, int c2) {
    asm volatile("cp.async.bulk.tensor.3d.global.shared::cta.bulk_group [%0, {%2, %3, %4}], [%1];"
                 ::"l"((uint64_t)map), "r"(src), "r"(c0), "r"(c1), "r"(c2) : "memory");
}
__device__ __forceinline__ void bulk_commit() { asm volatile("cp.async.bulk.commit_group;" ::: "memory"); }
__device__ __forceinline__ void bulk_wait0() { asm volatile("cp.async.bulk.wait_group 0;" ::: "memory"); }
__device__ __forceinline__ void bulk_wait_read0() { asm volatile("cp.async.bulk.wait_group.read 0;" ::: "memory"); }
__device__ __forceinline__ void fence_async_smem() { asm volatile("fence.proxy.async.shared::cta;" ::: "memory"); }
__device__ __forceinline__ void named_bar(int id, int n) { asm volatile("bar.sync %0, %1;" ::"r"(id), "r"(n) : "memory"); }
__device__ __forceinline__ void sts128(uint32_t addr, uint32_t a, uint32_t b, uint32_t c, uint32_t d) {
    asm volatile("st.shared.v4.b32 [%0], {%1, %2, %3, %4};" ::"r"(addr), "r"(a), "r"(b), "r"(c), "r"(d) : "memory");
}
__device__ __forceinline__ void prefetch_map(const CUtensorMap* m) {
    asm volatile("prefetch.tensormap [%0];" ::"l"((uint64_t)m) : "memory");
}
__device__ __forceinline__ void wgmma_fence() { asm volatile("wgmma.fence.sync.aligned;" ::: "memory"); }
__device__ __forceinline__ void wgmma_commit() { asm volatile("wgmma.commit_group.sync.aligned;" ::: "memory"); }
template <int N>
__device__ __forceinline__ void wgmma_wait() { asm volatile("wgmma.wait_group.sync.aligned %0;" ::"n"(N) : "memory"); }
template <int N>
__device__ __forceinline__ void fence_regs(float (&a)[N]) {
#pragma unroll
    for (int i = 0; i < N; ++i) asm volatile("" : "+f"(a[i])::"memory");
}
template <int N>
__device__ __forceinline__ void fence_regs(uint32_t (&a)[N]) {
#pragma unroll
    for (int i = 0; i < N; ++i) asm volatile("" : "+r"(a[i])::"memory");
}
#define R8(a, i) "+f"(a[i + 0]), "+f"(a[i + 1]), "+f"(a[i + 2]), "+f"(a[i + 3]), "+f"(a[i + 4]), "+f"(a[i + 5]), "+f"(a[i + 6]), "+f"(a[i + 7])
#define REGS32 "{%0, %1, %2, %3, %4, %5, %6, %7, %8, %9, %10, %11, %12, %13, %14, %15, %16, %17, %18, %19, %20, %21, %22, %23, %24, %25, %26, %27, %28, %29, %30, %31}"
#define REGS16 "{%0, %1, %2, %3, %4, %5, %6, %7, %8, %9, %10, %11, %12, %13, %14, %15}"

__host__ __device__ constexpr uint32_t desc_hi(uint32_t sbo, uint32_t mode) { return (sbo >> 4) | (mode << 30); }
__device__ __forceinline__ uint32_t desc_lo(uint32_t saddr, uint32_t lbo) { return ((saddr & 0x3FFFF) >> 4) | ((lbo >> 4) << 16); }
constexpr uint32_t HI128 = desc_hi(1024, 1), HI64 = desc_hi(512, 2);
#define W8(a, i) "=f"(a[i + 0]), "=f"(a[i + 1]), "=f"(a[i + 2]), "=f"(a[i + 3]), "=f"(a[i + 4]), "=f"(a[i + 5]), "=f"(a[i + 6]), "=f"(a[i + 7])
template <int TA, int TB, int ACC, uint32_t AHI, uint32_t BHI>
__device__ __forceinline__ void wgmma_n64_ss(float (&d)[32], uint32_t alo, uint32_t blo) {
#define N64_TEXT "{\n.reg .pred p;\n.reg .b64 da, db;\nsetp.ne.b32 p, %36, 0;\nmov.b64 da, {%32, %37};\nmov.b64 db, {%33, %38};\n" \
        "wgmma.mma_async.sync.aligned.m64n64k16.f32.bf16.bf16 " REGS32 ", da, db, p, 1, 1, %34, %35;\n}\n"
    if (ACC) asm volatile(N64_TEXT : R8(d, 0), R8(d, 8), R8(d, 16), R8(d, 24) : "r"(alo), "r"(blo), "n"(TA), "n"(TB), "n"(ACC), "n"(AHI), "n"(BHI));
    else asm volatile(N64_TEXT : W8(d, 0), W8(d, 8), W8(d, 16), W8(d, 24) : "r"(alo), "r"(blo), "n"(TA), "n"(TB), "n"(ACC), "n"(AHI), "n"(BHI));
}
template <int ACC, int SA>
__device__ __forceinline__ void wgmma_n32_tt(float (&d)[16], uint32_t alo, uint32_t blo) {
#define N32T_TEXT "{\n.reg .pred p;\n.reg .b64 da, db;\nsetp.ne.b32 p, %18, 0;\nmov.b64 da, {%16, %19};\nmov.b64 db, {%17, %20};\n" \
        "wgmma.mma_async.sync.aligned.m64n32k16.f32.bf16.bf16 " REGS16 ", da, db, p, %21, 1, 1, 1;\n}\n"
    if (ACC) asm volatile(N32T_TEXT : R8(d, 0), R8(d, 8) : "r"(alo), "r"(blo), "n"(ACC), "n"(HI64), "n"(HI128), "n"(SA));
    else asm volatile(N32T_TEXT : W8(d, 0), W8(d, 8) : "r"(alo), "r"(blo), "n"(ACC), "n"(HI64), "n"(HI128), "n"(SA));
}
__device__ __forceinline__ void wgmma_n16_rs(float (&d)[8], const uint32_t (&a)[4], uint32_t blo) {
    asm volatile("{\n.reg .pred p;\n.reg .b64 db;\nsetp.ne.b32 p, 0, 0;\nmov.b64 db, {%12, %13};\n"
        "wgmma.mma_async.sync.aligned.m64n16k16.f32.bf16.bf16 {%0, %1, %2, %3, %4, %5, %6, %7}, {%8, %9, %10, %11}, db, p, 1, 1, 0;\n}\n"
        : W8(d, 0) : "r"(a[0]), "r"(a[1]), "r"(a[2]), "r"(a[3]), "r"(blo), "n"(HI128));
}

__device__ __forceinline__ float bf16r(float x) { return __bfloat162float(__float2bfloat16_rn(x)); }
__device__ __forceinline__ uint32_t pack_bf16(float lo, float hi) {
    __nv_bfloat162 v = __floats2bfloat162_rn(lo, hi);
    return *reinterpret_cast<uint32_t*>(&v);
}
__device__ __forceinline__ __nv_bfloat162 as_bf2(uint32_t w) { return *reinterpret_cast<__nv_bfloat162*>(&w); }
__device__ __forceinline__ uint32_t as_u32(__nv_bfloat162 v) { return *reinterpret_cast<uint32_t*>(&v); }
__device__ __forceinline__ float bf_lo(uint32_t w) { return __uint_as_float(w << 16); }
__device__ __forceinline__ float bf_hi(uint32_t w) { return __uint_as_float(w & 0xFFFF0000u); }
__device__ __forceinline__ void ldsm_x4_t(uint32_t& r0, uint32_t& r1, uint32_t& r2, uint32_t& r3, uint32_t addr) {
    asm volatile("ldmatrix.sync.aligned.m8n8.x4.trans.shared.b16 {%0,%1,%2,%3}, [%4];"
                 : "=r"(r0), "=r"(r1), "=r"(r2), "=r"(r3) : "r"(addr) : "memory");
}
__device__ __forceinline__ void stsm_x4(uint32_t addr, uint32_t r0, uint32_t r1, uint32_t r2, uint32_t r3) {
    asm volatile("stmatrix.sync.aligned.m8n8.x4.shared.b16 [%0], {%1,%2,%3,%4};"
                 ::"r"(addr), "r"(r0), "r"(r1), "r"(r2), "r"(r3) : "memory");
}
__device__ __forceinline__ void stsm_x4_t(uint32_t addr, uint32_t r0, uint32_t r1, uint32_t r2, uint32_t r3) {
    asm volatile("stmatrix.sync.aligned.m8n8.x4.trans.shared.b16 [%0], {%1,%2,%3,%4};"
                 ::"r"(addr), "r"(r0), "r"(r1), "r"(r2), "r"(r3) : "memory");
}
__device__ __forceinline__ uint32_t lds32(uint32_t addr) {
    uint32_t v;
    asm volatile("ld.shared.b32 %0, [%1];" : "=r"(v) : "r"(addr));
    return v;
}

typedef CUresult (*EncodeFn)(CUtensorMap*, CUtensorMapDataType, cuuint32_t, void*, const cuuint64_t*, const cuuint64_t*,
                             const cuuint32_t*, const cuuint32_t*, CUtensorMapInterleave, CUtensorMapSwizzle,
                             CUtensorMapL2promotion, CUtensorMapFloatOOBfill);
EncodeFn get_encode() {
    static EncodeFn fn = nullptr;
    if (!fn) {
        void* p = nullptr;
        cudaDriverEntryPointQueryResult qres;
        cudaGetDriverEntryPoint("cuTensorMapEncodeTiled", &p, cudaEnableDefault, &qres);
        fn = (EncodeFn)p;
    }
    return fn;
}
}
namespace {
constexpr double c_pi = 3.14159265358979323846;
constexpr double c_cos256(int i) {
    i &= 255;
    if (i > 128) i = 256 - i;
    double sgn = 1.0;
    if (i > 64) { i = 128 - i; sgn = -1.0; }
    if (i == 64) return 0.0;
    double x = 2.0 * c_pi * i / 256.0, x2 = x * x, term = 1.0, sum = 1.0;
    for (int k = 1; k < 20; ++k) { term *= -x2 / ((2 * k - 1) * (2 * k)); sum += term; }
    return sgn * sum;
}
constexpr uint32_t c_bf16(double v) {
    if (v == 0.0) return 0u;
    uint32_t s = v < 0 ? 0x8000u : 0u;
    double a = v < 0 ? -v : v;
    int e = 0;
    while (a >= 2.0) { a *= 0.5; ++e; }
    while (a < 1.0) { a *= 2.0; --e; }
    int r = (int)(a * 128.0 + 0.5);
    if (r == 256) { r = 128; ++e; }
    return s | (uint32_t)((e + 127) << 7) | (uint32_t)(r - 128);
}
__host__ __device__ constexpr int conv_k1(int r) { return (r & 8) ? 63 - (((r >> 4) << 3) | (r & 7)) : (((r >> 4) << 3) | (r & 7)); }
struct ConvTab { uint32_t w[96 * 32]; };
constexpr ConvTab make_conv_tab() {
    ConvTab t{};
    uint32_t cs[256] = {};
    for (int i = 0; i < 256; ++i) cs[i] = c_bf16(c_cos256(i));
    for (int n = 0; n < 96; ++n)
        for (int c = 0; c < 64; ++c) {
            int a = 0;
            if (n < 32) {
                const int ro = (n >> 3) & 1, ri = n & 7, co = (c >> 3) & 1, ci = c & 7;
                a = n < 16 ? 8 * ci * (4 * ri + (c >> 4)) : 8 * ri * (4 * ci + (c >> 4));
                a += (ro == co) ? 0 : (ro == 0) ? 192 : 64;
            } else {
                const int r = n - 32, n1 = 2 * (c & 31) + (c >> 5);
                a = n1 * (2 * (((r >> 4) << 3) | (r & 7)) + 1) + ((r & 8) ? 64 : 0);
            }
            const int off = n * 128 + (((c >> 3) ^ (n & 7)) << 4) + (c & 7) * 2;
            t.w[off >> 2] |= cs[a & 255] << ((off & 2) * 8);
        }
    return t;
}
__device__ __align__(128) constexpr ConvTab g_conv_tab = make_conv_tab();

struct Twiddle { uint32_t r[8], i[8], n[8]; };
constexpr double c_cospi(double x) {
    double sgn = 1.0;
    if (x > 0.5) { x = 1.0 - x; sgn = -1.0; }
    const double y = c_pi * x, y2 = y * y;
    double term = 1.0, sum = 1.0;
    for (int k = 1; k < 12; ++k) { term *= -y2 / ((2 * k - 1) * (2 * k)); sum += term; }
    return sgn * sum;
}
struct TwTab { uint32_t w[3072]; };
constexpr TwTab make_tw_tab() {
    TwTab t{};
    for (int th = 0; th < 128; ++th)
        for (int q = 0; q < 8; ++q)
            for (int e = 0; e < 2; ++e) {
                const int k1 = conv_k1(16 * (th >> 5) + 8 * (q & 1) + ((th & 31) >> 2)), n2 = 8 * (q >> 1) + 2 * (th & 3) + e;
                const double x = (double)(n2 * (2 * k1 + 1)) / 4096.0;
                const double cs = c_cospi(x), sn = n2 == 0 ? 0.0 : c_cospi(x > 0.5 ? x - 0.5 : 0.5 - x);
                t.w[((q >> 2) * 128 + th) * 4 + (q & 3)] |= c_bf16(cs * 0.0625) << (16 * e);
                t.w[((2 + (q >> 2)) * 128 + th) * 4 + (q & 3)] |= c_bf16(-sn * 0.0625) << (16 * e);
                t.w[((4 + (q >> 2)) * 128 + th) * 4 + (q & 3)] |= c_bf16(sn * 0.0625) << (16 * e);
            }
    return t;
}
__device__ __align__(128) constexpr TwTab g_tw_tab = make_tw_tab();
__device__ __forceinline__ void load_twiddle(Twiddle& tw, const uint4* p) {
#pragma unroll
    for (int q = 0; q < 2; ++q) {
        const uint4 a = __ldg(p + q * 128);
        const uint4 b = __ldg(p + (2 + q) * 128);
        tw.r[4 * q] = a.x; tw.r[4 * q + 1] = a.y; tw.r[4 * q + 2] = a.z; tw.r[4 * q + 3] = a.w;
        const uint4 n = __ldg(p + (4 + q) * 128);
        tw.n[4 * q] = n.x; tw.n[4 * q + 1] = n.y; tw.n[4 * q + 2] = n.z; tw.n[4 * q + 3] = n.w;
        tw.i[4 * q] = b.x; tw.i[4 * q + 1] = b.y; tw.i[4 * q + 2] = b.z; tw.i[4 * q + 3] = b.w;
    }
}

__device__ __forceinline__ int fresh_tid() { int v; asm volatile("mov.u32 %0, %tid.x;" : "=r"(v)); return v; }
__device__ __forceinline__ uint32_t hmul(uint32_t a, uint32_t b) { return as_u32(__hmul2_rn(as_bf2(a), as_bf2(b))); }
__device__ __forceinline__ uint32_t hadd(uint32_t a, uint32_t b) { return as_u32(__hadd2_rn(as_bf2(a), as_bf2(b))); }
__device__ __forceinline__ uint32_t hsub(uint32_t a, uint32_t b) { return as_u32(__hsub2_rn(as_bf2(a), as_bf2(b))); }
__device__ __forceinline__ uint32_t hfma(uint32_t a, uint32_t b, uint32_t c) { return as_u32(__hfma2(as_bf2(a), as_bf2(b), as_bf2(c))); }

__device__ __forceinline__ void conv_dft8(float (&x)[4][8], const uint32_t (&f)[4][4], uint32_t blo) {
#pragma unroll
    for (int r = 0; r < 4; ++r) wgmma_n16_rs(x[r], f[r], blo + 2 * r);
}
template <class T, int N>
__device__ __forceinline__ void fence_regs4(T (&a)[4][N]) { fence_regs(a[0]); fence_regs(a[1]); fence_regs(a[2]); fence_regs(a[3]); }
__device__ __forceinline__ void conv_s1(float (&dE)[32], float (&dO)[32], uint32_t tlo, uint32_t ulo) {
    wgmma_n64_ss<0, 1, 0, HI128, HI64>(dE, tlo + 256, ulo);
    wgmma_n64_ss<0, 1, 0, HI128, HI64>(dO, tlo + 256 + 4, ulo + 128);
    wgmma_n64_ss<0, 1, 1, HI128, HI64>(dE, tlo + 256 + 2, ulo + 64);
    wgmma_n64_ss<0, 1, 1, HI128, HI64>(dO, tlo + 256 + 6, ulo + 192);
}
template <int S>
__device__ __forceinline__ void conv_t1(const float (&dE)[32], const float (&dO)[32], const Twiddle& tw, float dsk, uint32_t (&f)[4][4]) {
    uint32_t ar[8], ai[8], fs[8], fd[8];
#pragma unroll
    for (int j = 0; j < 4; ++j) {
        const int i = 16 * S + 4 * j;
        const uint32_t e0 = pack_bf16(i == 16 ? dE[i] + dsk : dE[i], dE[i + 1]), e1 = pack_bf16(dE[i + 2], dE[i + 3]);
        const uint32_t o0 = pack_bf16(dO[i], dO[i + 1]), o1 = pack_bf16(dO[i + 2], dO[i + 3]);
        ar[2 * j] = hadd(e0, o0); ai[2 * j] = hadd(e1, o1);
        ar[2 * j + 1] = hsub(e0, o0); ai[2 * j + 1] = hsub(o1, e1);
    }
#pragma unroll
    for (int q = 0; q < 4; ++q) {
        const uint32_t pr = hfma(ar[q], tw.r[q], hmul(ai[q], tw.n[q])), pi = hfma(ar[q], tw.i[q], hmul(ai[q], tw.r[q]));
        fs[q] = hfma(ar[4 + q], tw.r[4 + q], hfma(ai[4 + q], tw.n[4 + q], pr));
        fs[4 + q] = hfma(ar[4 + q], tw.i[4 + q], hfma(ai[4 + q], tw.r[4 + q], pi));
        fd[q] = hfma(pr, 0xC000C000u, fs[q]);
        fd[4 + q] = hfma(pi, 0xC000C000u, fs[4 + q]);
    }
#pragma unroll
    for (int h = 0; h < 2; ++h) {
        f[0][h] = hadd(fs[h], fs[2 + h]); f[0][2 + h] = hadd(fs[4 + h], fs[6 + h]);
        f[2][h] = hsub(fs[h], fs[2 + h]); f[2][2 + h] = hsub(fs[4 + h], fs[6 + h]);
        f[1][h] = hadd(fd[h], fd[6 + h]); f[1][2 + h] = hsub(fd[4 + h], fd[2 + h]);
        f[3][h] = hsub(fd[h], fd[6 + h]); f[3][2 + h] = hadd(fd[4 + h], fd[2 + h]);
    }
}
__device__ __forceinline__ void conv_prod(const float (&xu)[8], const float (&xk)[8], uint32_t (&f)[4]) {
#pragma unroll
    for (int h = 0; h < 2; ++h) {
        float pr[2], pi[2];
#pragma unroll
        for (int e = 0; e < 2; ++e) {
            const float ur = xu[2 * h + e], ui = xu[4 + 2 * h + e], kr = xk[2 * h + e], ki = xk[4 + 2 * h + e];
            pr[e] = fmaf(ur, kr, -ui * ki);
            pi[e] = fmaf(-ur, ki, -ui * kr);
        }
        f[h] = pack_bf16(pr[0], pr[1]);
        f[2 + h] = pack_bf16(pi[0], pi[1]);
    }
}
template <bool SECOND, class G>
__device__ __forceinline__ void conv_channel(float (&dE)[32], float (&dO)[32], const Twiddle& tw, float dsk, uint32_t tlo, uint32_t nxt,
                                             uint32_t wre, uint32_t wim, int bar, G before_next) {
    float xu[4][8], xk[4][8];
    {
        uint32_t fu[4][4], fk[4][4];
        conv_t1<0>(dE, dO, tw, 0.f, fu);
        wgmma_fence();
        conv_dft8(xu, fu, tlo);
        wgmma_commit();
        conv_t1<1>(dE, dO, tw, dsk, fk);
        wgmma_fence();
        conv_dft8(xk, fk, tlo);
        wgmma_commit();
        before_next();
        wgmma_wait<0>();
        fence_regs4(xu); fence_regs4(xk);
        fence_regs4(fu); fence_regs4(fk);
    }
    uint32_t fp[4][4];
#pragma unroll
    for (int r = 0; r < 4; ++r) conv_prod(xu[r], xk[r], fp[r]);
    wgmma_fence();
    conv_dft8(xu, fp, tlo + 128);
    wgmma_commit();
    if (!SECOND || nxt) {
        if (SECOND) wgmma_fence();
        conv_s1(dE, dO, tlo, nxt);
        wgmma_commit();
        wgmma_wait<1>();
    } else {
        wgmma_wait<0>();
#pragma unroll
        for (int i = 0; i < 32; ++i) { dE[i] = 0.f; dO[i] = 0.f; }
        fence_regs(dE); fence_regs(dO);
    }
    fence_regs4(xu);
    fence_regs4(fp);
    uint32_t zr[8], zi[8], wr[8], wi[8];
#pragma unroll
    for (int h = 0; h < 2; ++h) {
        uint32_t yr[4], yi[4];
#pragma unroll
        for (int r = 0; r < 4; ++r) { yr[r] = pack_bf16(xu[r][2 * h], xu[r][2 * h + 1]); yi[r] = pack_bf16(xu[r][4 + 2 * h], xu[r][5 + 2 * h]); }
        const uint32_t u0r = hadd(yr[0], yr[2]), u0i = hadd(yi[0], yi[2]), u1r = hsub(yr[0], yr[2]), u1i = hsub(yi[0], yi[2]);
        const uint32_t v0r = hadd(yr[1], yr[3]), v0i = hadd(yi[1], yi[3]), v1r = hsub(yr[1], yr[3]), v1i = hsub(yi[1], yi[3]);
        zr[h] = hadd(u0r, v0r); zi[h] = hadd(u0i, v0i); zr[4 + h] = hsub(u0r, v0r); zi[4 + h] = hsub(u0i, v0i);
        zr[2 + h] = hadd(u1r, v1i); zi[2 + h] = hsub(u1i, v1r); zr[6 + h] = hsub(u1r, v1i); zi[6 + h] = hadd(u1i, v1r);
    }
#pragma unroll
    for (int q = 0; q < 8; ++q) {
        wr[q] = hfma(zr[q], tw.r[q], hmul(zi[q], tw.n[q]));
        wi[q] = hfma(zr[q], tw.i[q], hmul(zi[q], tw.r[q]));
    }
    if (SECOND) named_bar(bar, 128);
    stsm_x4(wre, hadd(wr[0], wr[1]), hadd(wr[2], wr[3]), hadd(wr[4], wr[5]), hadd(wr[6], wr[7]));
    stsm_x4(wre + 512, hsub(wi[1], wi[0]), hsub(wi[3], wi[2]), hsub(wi[5], wi[4]), hsub(wi[7], wi[6]));
    stsm_x4(wim, hsub(wr[1], wr[0]), hsub(wr[3], wr[2]), hsub(wr[5], wr[4]), hsub(wr[7], wr[6]));
    stsm_x4(wim + 512, hadd(wi[0], wi[1]), hadd(wi[2], wi[3]), hadd(wi[4], wi[5]), hadd(wi[6], wi[7]));
}
template <class G>
__device__ __forceinline__ void conv_pair(float (&dE)[32], float (&dO)[32], const Twiddle& tw, uint32_t dd, uint32_t tlo, uint32_t u0, uint32_t un,
                                          uint32_t lo, int BAR, G before_next) {
    conv_channel<false>(dE, dO, tw, bf_lo(dd), tlo, desc_lo(u0 + 4096, 8192), u0 + lo, u0 + 8192 + lo, BAR, []() {});
    wgmma_wait<0>();
    fence_regs(dE); fence_regs(dO);
    conv_channel<true>(dE, dO, tw, bf_hi(dd), tlo, un == u0 ? 0 : desc_lo(un, 8192), u0 + 4096 + lo, u0 + 12288 + lo, BAR, before_next);
    fence_async_smem();
    named_bar(BAR, 128);
    float ye[16], yo[16];
    wgmma_fence();
    const uint32_t wlo = desc_lo(u0, 4096);
    wgmma_n32_tt<0, 1>(ye, wlo, tlo + 256);
    wgmma_n32_tt<0, -1>(yo, wlo + 512, tlo + 256 + 4);
#pragma unroll
    for (int k = 1; k < 4; ++k) {
        wgmma_n32_tt<1, 1>(ye, wlo + 64 * k, tlo + 256 + 128 * k);
        wgmma_n32_tt<1, -1>(yo, wlo + 512 + 64 * k, tlo + 256 + 4 + 128 * k);
    }
    wgmma_commit();
    wgmma_wait<0>();
    fence_regs(ye); fence_regs(yo);
    fence_regs(dE); fence_regs(dO);
    named_bar(BAR, 128);
    const int t = fresh_tid();
    const uint32_t ya = u0 + (t & 64) * 64 + (t & 31) * 64 + (((((t >> 4) & 2) ^ (t >> 1)) & 3) << 4);
#pragma unroll
    for (int h = 0; h < 2; ++h) {
        stsm_x4_t(ya ^ (16 * h), pack_bf16(ye[2 * h], ye[2 * h + 1]), pack_bf16(ye[4 + 2 * h], ye[5 + 2 * h]),
                  pack_bf16(ye[8 + 2 * h], ye[9 + 2 * h]), pack_bf16(ye[12 + 2 * h], ye[13 + 2 * h]));
        stsm_x4_t((ya ^ (16 * h)) + 2048, pack_bf16(yo[2 * h], yo[2 * h + 1]), pack_bf16(yo[4 + 2 * h], yo[5 + 2 * h]),
                  pack_bf16(yo[8 + 2 * h], yo[9 + 2 * h]), pack_bf16(yo[12 + 2 * h], yo[13 + 2 * h]));
    }
    fence_async_smem();
    __syncwarp();
}
}

namespace {

constexpr int S_LEN = 2048;
constexpr int D_DIM = 1024;

#define REG_P 24
#define REG_AB 168
#define REG_C 152
#define QD 3
#define QKB 18
#define QD2 6
#define ALTMAP 0
#define SKEW1 4
#define TK_PF0 0
#define GAP_PF 300
#define TK_KV0 2
#define TK_KV1 4
#define GAP_KV 50
#define GAP_ST 50
#define GAP_HB 100
#define PFD 7
#define GAP_Y 100
#define GAP_X 100
#define SLOT4 20
#define SKEW2 4
#define GAP_CV 100
#define TK_C 8

__device__ __align__(1024) __nv_bfloat16 g_H[2 * D_DIM * S_LEN];
__device__ __align__(1024) __nv_bfloat16 g_y2[D_DIM * S_LEN];
__device__ __align__(1024) __nv_bfloat16 g_kvT[D_DIM * S_LEN];
__device__ __align__(128) float g_gate[S_LEN];
__device__ __align__(128) unsigned long long g_agg[8 * D_DIM];
__device__ __align__(128) unsigned int g_cnt[56 * 32];

#define STAMP(k, s) do { } while (0)
#define SAMPLE(i) do { } while (0)

__device__ __forceinline__ void tma_store_5d(const CUtensorMap* map, uint32_t src, int c0, int c1, int c2, int c3, int c4) {
    asm volatile("cp.async.bulk.tensor.5d.global.shared::cta.bulk_group [%0, {%2, %3, %4, %5, %6}], [%1];"
                 ::"l"((uint64_t)map), "r"(src), "r"(c0), "r"(c1), "r"(c2), "r"(c3), "r"(c4) : "memory");
}
#define ELECT "{\n.reg .pred p;\nelect.sync _|p, 0xffffffff;\n@p "
__device__ __forceinline__ void e_expect_tx(uint32_t bar, uint32_t bytes) {
    asm volatile(ELECT "mbarrier.arrive.expect_tx.shared::cta.b64 _, [%0], %1;\n}" ::"r"(bar), "r"(bytes) : "memory");
}
__device__ __forceinline__ void e_arrive(uint32_t bar) {
    asm volatile(ELECT "mbarrier.arrive.shared::cta.b64 _, [%0];\n}" ::"r"(bar) : "memory");
}
__device__ __forceinline__ void e_load_4d(uint32_t dst, const CUtensorMap* map, uint32_t bar, int c0, int c1, int c2, int c3) {
    asm volatile(ELECT "cp.async.bulk.tensor.4d.shared::cluster.global.mbarrier::complete_tx::bytes [%0], [%1, {%3, %4, %5, %6}], [%2];\n}"
        ::"r"(dst), "l"((uint64_t)map), "r"(bar), "r"(c0), "r"(c1), "r"(c2), "r"(c3) : "memory");
}
__device__ __forceinline__ void e_load_5d(uint32_t dst, const CUtensorMap* map, uint32_t bar, int c0, int c1, int c2, int c3, int c4) {
    asm volatile(ELECT "cp.async.bulk.tensor.5d.shared::cluster.global.mbarrier::complete_tx::bytes [%0], [%1, {%3, %4, %5, %6, %7}], [%2];\n}"
        ::"r"(dst), "l"((uint64_t)map), "r"(bar), "r"(c0), "r"(c1), "r"(c2), "r"(c3), "r"(c4) : "memory");
}
__device__ __forceinline__ void e_bulk_load(uint32_t dst, const void* src, uint32_t bytes, uint32_t bar) {
    asm volatile(ELECT "cp.async.bulk.shared::cluster.global.mbarrier::complete_tx::bytes [%0], [%1], %2, [%3];\n}"
                 ::"r"(dst), "l"(src), "r"(bytes), "r"(bar) : "memory");
}
__device__ __forceinline__ void l2_prefetch(const void* p, uint32_t bytes) {
    asm volatile("cp.async.bulk.prefetch.L2.global [%0], %1;" ::"l"(p), "r"(bytes) : "memory");
}
__device__ __forceinline__ void l2_prefetch_4d(const CUtensorMap* map, int c0, int c1, int c2, int c3) {
    asm volatile("cp.async.bulk.prefetch.tensor.4d.L2.global [%0, {%1, %2, %3, %4}];" ::"l"((uint64_t)map), "r"(c0), "r"(c1), "r"(c2), "r"(c3) : "memory");
}
__device__ __forceinline__ void l2_prefetch_5d(const CUtensorMap* map, int c0, int c1, int c2, int c3, int c4) {
    asm volatile("cp.async.bulk.prefetch.tensor.5d.L2.global [%0, {%1, %2, %3, %4, %5}];" ::"l"((uint64_t)map), "r"(c0), "r"(c1), "r"(c2), "r"(c3), "r"(c4) : "memory");
}
__device__ __forceinline__ unsigned int ld_relaxed(const unsigned int* p) {
    unsigned int v;
    asm volatile("ld.relaxed.gpu.global.u32 %0, [%1];" : "=r"(v) : "l"(p) : "memory");
    return v;
}
__device__ __forceinline__ void fence_async_global() { asm volatile("fence.proxy.async.global;" ::: "memory"); }
__device__ __forceinline__ void wait_counter(const unsigned int* p, unsigned int target) {
    unsigned int v;
    int it = 0;
    do { asm volatile("ld.acquire.gpu.global.u32 %0, [%1];" : "=r"(v) : "l"(p) : "memory"); } while (v != target && ++it < (1 << 22));
    fence_async_global();
}
__device__ __forceinline__ void red_release(unsigned int* p, unsigned int n) {
    asm volatile("red.release.gpu.global.add.u32 [%0], %1;" ::"l"(p), "r"(n) : "memory");
}
__device__ __forceinline__ uint4 ldg128(const void* p) {
    uint4 v;
    asm volatile("ld.global.nc.v4.u32 {%0,%1,%2,%3}, [%4];" : "=r"(v.x), "=r"(v.y), "=r"(v.z), "=r"(v.w) : "l"(p));
    return v;
}
__device__ __forceinline__ void stg128(void* p, uint32_t a, uint32_t b, uint32_t c, uint32_t d) {
    asm volatile("st.global.v4.b32 [%0], {%1, %2, %3, %4};" ::"l"(p), "r"(a), "r"(b), "r"(c), "r"(d) : "memory");
}

template <int TA>
__device__ __forceinline__ void wgmma_n128(float (&d)[64], uint32_t alo, uint32_t blo, int acc) {
    asm volatile(
        "{\n.reg .pred p;\n.reg .b64 da, db;\nsetp.ne.b32 p, %67, 0;\nmov.b64 da, {%64, %69};\nmov.b64 db, {%65, %66};\n"
        "wgmma.mma_async.sync.aligned.m64n128k16.f32.bf16.bf16 "
        "{%0, %1, %2, %3, %4, %5, %6, %7, %8, %9, %10, %11, %12, %13, %14, %15, "
        "%16, %17, %18, %19, %20, %21, %22, %23, %24, %25, %26, %27, %28, %29, %30, %31, "
        "%32, %33, %34, %35, %36, %37, %38, %39, %40, %41, %42, %43, %44, %45, %46, %47, "
        "%48, %49, %50, %51, %52, %53, %54, %55, %56, %57, %58, %59, %60, %61, %62, %63}, "
        "da, db, p, 1, 1, %68, 0;\n"
        "}\n"
        : R8(d, 0), R8(d, 8), R8(d, 16), R8(d, 24), R8(d, 32), R8(d, 40), R8(d, 48), R8(d, 56)
        : "r"(alo), "r"(blo), "n"(HI128), "r"(acc), "n"(TA), "n"(TA ? HI64 : HI128));
}

constexpr int NST = 5;
constexpr int XTRA = SKEW1 - 4;
static_assert(SKEW1 >= 4 && SKEW1 <= 12, "skew");
constexpr int OFF_BB = 4 * 32768;
constexpr int OFF_CT = 5 * 32768;
constexpr int OFF_CU = OFF_CT + 32768;
__host__ __device__ constexpr uint32_t conv_buf(int p) { return OFF_CT + 16384 + (p == 3 ? 0 : p) * 16384; }
constexpr int OFF_PAR = OFF_CU + 32768;
constexpr int OFF_BAR = OFF_PAR + 2048;
constexpr int SMEM_BYTES = OFF_BAR + 896;
static_assert(SMEM_BYTES <= 232448, "smem layout");

static_assert(SLOT4 % 4 == 0 && SLOT4 <= 24, "ring");
constexpr uint32_t PH4 = (SLOT4 / 4 - 1) & 1;
__host__ __device__ constexpr int ring_slot(int kb) { return (kb - SLOT4 + 4) % 5; }
__host__ __device__ constexpr uint32_t ring_par(int kb) { return ((SLOT4 / 4 - 1 + (kb - SLOT4 + 4) / 5) & 1) ^ (ring_slot(kb) == 4 ? PH4 : 0); }

struct Maps {
    CUtensorMap x5, b4, cre, cim, sk, yt, yt3, out, kvst, bre, bim;
};

__device__ __forceinline__ void cmul(float& r, float& i, float ar, float ai, float br, float bi) {
    const float a = ar * br - ai * bi, b = ar * bi + ai * br;
    r = a; i = b;
}
__device__ __forceinline__ void csqr(float& r, float& i) { const float a = r * r - i * i, b = 2.f * r * i; r = a; i = b; }
__device__ __forceinline__ float after(float v, float dep) { return __float_as_uint(dep) == 0x7fedcba9u ? dep : v; }

template <int BMODE>
__global__ void __launch_bounds__(512, 1)
fused_kernel(const __nv_bfloat16* __restrict__ x,
             const __nv_bfloat16* __restrict__ kin, const __nv_bfloat16* __restrict__ vin, const __nv_bfloat16* __restrict__ ssm_k,
             const __nv_bfloat16* __restrict__ shift_k, const __nv_bfloat16* __restrict__ ssm_D,
             const __nv_bfloat16* __restrict__ lam_re, const __nv_bfloat16* __restrict__ lam_im,
             const __nv_bfloat16* __restrict__ log_dt, const __nv_bfloat16* __restrict__ gate_w,
             const __nv_bfloat16* __restrict__ dskip,
             const __nv_bfloat16* __restrict__ c_re, const __nv_bfloat16* __restrict__ c_im,
             const __grid_constant__ Maps maps) {
    constexpr bool MERGED = BMODE != 0, SW = BMODE == 2;
    extern __shared__ __align__(1024) unsigned char smem_raw[];
    const uint32_t sbase = smem_u32(smem_raw);
    const uint32_t bar_full = sbase + OFF_BAR;
    const uint32_t bar_empty = bar_full + 32;
    const uint32_t bar_full2 = bar_empty + 32;
    const uint32_t bar_empty2 = bar_full2 + 40;
    const uint32_t bar_k = bar_empty2 + 40;
    const uint32_t bar_tab = bar_k + 32;
    const uint32_t bar_ab = bar_tab + 8;
    const uint32_t bar_adone = bar_ab + 8;
    const uint32_t bar_par = bar_adone + 8;
    const uint32_t bar_y = bar_par + 8;
    const uint32_t bar_rel = bar_y + 8;
    const uint32_t bar_kvrel = bar_rel + 8;
    const uint32_t bar_yrel = bar_kvrel + 8;
    const uint32_t bar_y1 = bar_yrel + 8;
    const uint32_t bar_fh = bar_y1 + 8;
    const uint32_t bar_tick = bar_fh + 24;
    const uint32_t bar_stg = bar_tick + 104;
    const uint32_t bar_bias = bar_stg + 112;
    const uint32_t bar_hw = bar_bias + 16;
    const uint32_t bar_gate = bar_hw + 32;
    const uint32_t bar_g2 = bar_hw;
    const uint32_t w_bid = bar_full + 600, w_dsk = bar_full + 608, w_ones = bar_full + 640;
    const int tid = threadIdx.x ^ (((threadIdx.x + 128) & 256) ? 0 : 384);
    if (tid == 384) { prefetch_map(&maps.x5); prefetch_map(&maps.b4); }
    int bid;
    {
        unsigned int sm, nsm;
        asm volatile("mov.u32 %0, %smid;" : "=r"(sm));
        asm volatile("mov.u32 %0, %nsmid;" : "=r"(nsm));
        const int tpc = sm >> 1, q7 = ((tpc - 32) * 37) >> 8;
        const int gp = tpc < 32 ? tpc & 7 : tpc < 60 ? tpc - 31 - 7 * q7 : 0;
        const int ix = tpc < 32 ? tpc >> 3 : tpc < 60 ? q7 + 4 : ALTMAP ? (tpc - 56) ^ 2 : tpc - 58;
        bid = (ALTMAP ? tpc >= 64 : (tpc | 1) == 61) ? 128 : (4 * (gp >> 1) + (ix >> 1)) * 8 + 4 * (gp & 1) + 2 * (ix & 1) + (sm & 1);
        if (gridDim.x != 132 || nsm != 132) bid = blockIdx.x;
    }
    const int tt = bid >> 3, dt = bid & 7;
    const int ti = tt >> 1;
    const int cg = (dt >> 2) * 8 + (tt & 1) * 4 + (dt & 3);
    if (MERGED && threadIdx.x == 0 && bid < 128) {
        mbar_init(bar_full, 1);
        asm volatile("fence.mbarrier_init.release.cluster;" ::: "memory");
        mbar_expect_tx(bar_full, 49152);
        tma_load_4d(sbase + OFF_CU, &maps.b4, bar_full, 0, 0, 0, cg * 4);
        tma_load_5d(sbase + ((0 - XTRA) & 3) * 32768, &maps.x5, bar_full, 0, 0, 0, 0, ti);
        tma_load_4d(sbase + OFF_BB, &maps.b4, bar_full, 0, 0, 0, 64 + cg * 4);
    }
    __syncwarp();
    const int warp = __shfl_sync(0xffffffffu, tid >> 5, 0), wg = warp >> 2, lane = tid & 31;
    if (warp == 12 && bid < 128) {
        if (lane == 0) {
#pragma unroll
            for (int s = MERGED; s < 4; ++s) mbar_init(bar_full + 8 * s, 1);
            asm volatile("fence.mbarrier_init.release.cluster;" ::: "memory");
        }
        __syncwarp();
        asm volatile("bar.arrive 4, 512;" ::: "memory");
        if (MERGED) {
#pragma unroll 1
            for (int it = 1; it < 4; ++it) {
                e_expect_tx(bar_full + 8 * it, 49152);
                e_load_4d(sbase + OFF_CU + it * 8192, &maps.b4, bar_full + 8 * it, it * 64, 0, 0, cg * 4);
                e_load_5d(sbase + ((it - XTRA) & 3) * 32768, &maps.x5, bar_full + 8 * it, it * 64, 0, 0, 0, ti);
                e_load_4d(sbase + OFF_BB + it * 8192, &maps.b4, bar_full + 8 * it, it * 64, 0, 0, 64 + cg * 4);
            }
        }
    }
    if (bid >= 128) {
        if (tid == 0) {
            __nanosleep(2000);
            const unsigned int target = (ld_relaxed(&g_cnt[32 * 32]) & ~63u) + 64u;
            for (int i = 0; i < 8; ++i)
                for (int it = 0; ld_relaxed(&g_cnt[(40 + i) * 32]) != target && it < (1 << 12); ++it) __nanosleep(500);
        }
        return;
    }
    if (wg == 0) {
        asm volatile("setmaxnreg.dec.sync.aligned.u32 %0;" ::"n"(REG_P));
        if (tid == 32) {
            if (sbase & 1023) __trap();
#pragma unroll
            for (int s = 0; s < 4; ++s) mbar_init(bar_empty + 8 * s, 2);
#pragma unroll
            for (int s = 0; s < NST; ++s) { mbar_init(bar_full2 + 8 * s, 1); mbar_init(bar_empty2 + 8 * s, 1); }
            mbar_init(bar_k, 1); mbar_init(bar_k + 8, 1); mbar_init(bar_k + 16, 1); mbar_init(bar_k + 24, 1);
            mbar_init(bar_tab, 1);
            mbar_init(bar_ab, 1);
            mbar_init(bar_adone, 4);
            mbar_init(bar_par, 2);
            asm volatile("fence.mbarrier_init.release.cluster;" ::: "memory");
        } else if (tid == 64) {
#pragma unroll
            for (int s = 0; s < 21; ++s) mbar_init(bar_y + 8 * s, 1);
        } else if (tid == 96) {
#pragma unroll
            for (int s = 0; s < 11; ++s) mbar_init(bar_stg + 8 * s, 4);
        } else if (tid == 0) {
#pragma unroll
            for (int s = 11; s < 21; ++s) mbar_init(bar_stg + 8 * s, 4);
            asm volatile("st.shared.b32 [%0], %1;" ::"r"(w_bid), "r"(bid) : "memory");
        }
        __syncwarp();
        asm volatile("bar.sync 4, 512;" ::: "memory");
        if (warp == 0) {
#pragma unroll 1
            for (int it = MERGED ? 4 : 0; it < 16 + XTRA; ++it) {
                const int st = it & 3, kb = it < 16 ? it : it - SKEW1;
                const bool fa = it < 16, fb = it < 16 - SKEW1 || it >= 12;
                const uint32_t bf = bar_full + 8 * st;
                mbar_wait(bar_empty + 8 * st, ((it >> 2) & 1) ^ 1);
                e_expect_tx(bf, fa && fb ? 49152 : 40960);
                e_load_5d(sbase + ((it - XTRA) & 3) * 32768, &maps.x5, bf, kb * 64, 0, 0, 0, ti);
                if (MERGED) {
                    if (fa) e_load_4d(sbase + OFF_CU + st * 8192, &maps.b4, bf, kb * 64, 0, 0, cg * 4);
                    if (fb) e_load_4d(sbase + OFF_BB + st * 8192, &maps.b4, bf, kb * 64, 0, 0, 64 + cg * 4);
                } else {
                    if (lane < 16 && ((lane & 8) ? fb : fa))
                        tma_load_2d(sbase + ((lane & 8) ? OFF_BB : OFF_CU) + st * 8192 + (lane & 7) * 1024, (lane & 1) ? &maps.bim : &maps.bre, bf,
                                    kb * 64, (lane >> 3) * 512 + cg * 32 + ((lane & 7) >> 1) * 8);
                    __syncwarp();
                }
                if (it >= 4 && it < 16) e_arrive(bar_tick + 8 * (it - 3));
                if (lane == 0) STAMP(1, 16 + it);
                if (lane == 0 && it < 16) SAMPLE(it - 3);
            }
            int st = 0;
            uint32_t ph = 0;
#pragma unroll 1
            for (int kb = 0; kb < 32; ++kb) {
                const uint32_t bf = bar_full2 + 8 * st;
                mbar_wait(bar_empty2 + 8 * st, st == 4 ? ph ^ PH4 : ph);
                e_expect_tx(bf, 32768);
                e_load_5d(sbase + st * 32768 + 16384, &maps.cre + ((kb >> 3) & 1), bf, ((kb >> 4) * 8 + (kb & 7)) * 64, 0, 0, 0, dt * 4);
                if (lane == 0) STAMP(2, 16 + kb);
                if (lane == 0 && (kb & 3) == 0) SAMPLE(13 + (kb >> 2));
                if (++st == (kb < SLOT4 - 1 ? 4 : 5)) { st = 0; ph ^= 1; }
            }
        } else if (warp == 1) {
            if (MERGED && PFD && lane == 0) {
#pragma unroll 1
                for (int n = 0; n + PFD < 16; ++n) {
                    mbar_wait(bar_tick + 8 * n, 0);
                    if (cg >= 4 && max(cg - PFD, 0) == n) l2_prefetch_5d(&maps.x5, cg * 64, 0, 0, 0, ti);
                    if (ti >= 2 && max(2 * ti - PFD, 0) == n) {
#pragma unroll 1
                        for (int i = 0; i < 4; ++i) l2_prefetch_4d(&maps.b4, (2 * ti + (i >> 1)) * 64, 0, 0, (i & 1) * 64 + cg * 4);
                    }
                }
            }
            __syncwarp();
            const char* hp = reinterpret_cast<const char*>(g_H) + (size_t)tt * 262144;
            mbar_wait(bar_adone, 0);
            e_expect_tx(bar_k + 8, 16384);
            e_expect_tx(bar_k + 16, 16384);
#pragma unroll 1
            for (int c = 2; c < 6; ++c) {
                e_load_4d(sbase + conv_buf(0) + (c >> 1) * 16384 + (c & 1) * 4096 + 8192, &maps.sk, bar_k + 8 * (c >> 1), 0, 0, 0, bid * 8 + c);
                if (GAP_CV) __nanosleep(GAP_CV);
            }
            mbar_wait(bar_kvrel, 0);
            const unsigned int target = lds32(w_bid + 4);
            mbar_wait(bar_rel, 0);
            int st = 0;
            uint32_t ph = 0;
#pragma unroll 1
            for (int q = 0; q < 4; ++q) {
                if (lane == 0) STAMP(0, 8 + 2 * q);
                if (q == 0) wait_counter(&g_cnt[(4 * ti) * 32], target);
                else { mbar_wait(bar_fh + 8 * q - 8, 0); fence_async_global(); }
                if (lane == 0) STAMP(0, 9 + 2 * q);
#pragma unroll 1
                for (int kb = 0; kb < 8; ++kb) {
                    mbar_wait(bar_empty2 + 8 * st, st == 4 ? ph ^ PH4 : ph);
                    e_bulk_load(sbase + st * 32768, hp + kb * 16384, 16384, bar_full2 + 8 * st);
                    if (++st == (8 * q + kb < SLOT4 - 1 ? 4 : 5)) { st = 0; ph ^= 1; }
                }
                hp += (q & 1) ? 4194304 - 131072 : 131072;
            }
        } else if (warp == 2) {
            if (lane == 0) {
                mbar_wait(bar_tick + 8, 0);
                const unsigned int target = (ld_relaxed(&g_cnt[(40 + dt) * 32]) & ~63u) + 64u;
                asm volatile("st.shared.b32 [%0], %1;" ::"r"(w_bid + 4), "r"(target) : "memory");
                prefetch_map(&maps.kvst); prefetch_map(&maps.sk);
#pragma unroll 1
                for (int bt = 0; bt < 2; ++bt) {
                    mbar_wait(bar_stg + 8 * bt, 0);
#pragma unroll 1
                    for (int i = 0; i < 4; ++i) {
                        if (i) __nanosleep(GAP_ST);
                        tma_store_3d(&maps.kvst, sbase + OFF_CT + bt * 16384 + i * 4096, (tt & 1) * 1024 + ti * 128 + 64 * bt, dt * 16, 2 * i);
                    }
                    bulk_commit();
                }
                bulk_wait0();
                fence_async_global();
                red_release(&g_cnt[(40 + dt) * 32], 4);
                mbar_arrive(bar_kvrel);
                STAMP(0, 23);
                mbar_expect_tx(bar_tab, 12288);
                bulk_load(sbase + OFF_CT, &g_conv_tab, 12288, bar_tab);
                mbar_expect_tx(bar_k, 16384);
                tma_load_4d(sbase + conv_buf(0) + 8192, &maps.sk, bar_k, 0, 0, 0, bid * 8);
                tma_load_4d(sbase + conv_buf(0) + 12288, &maps.sk, bar_k, 0, 0, 0, bid * 8 + 1);
                wait_counter(&g_cnt[(40 + (bid >> 4)) * 32], target);
                STAMP(0, 19);
#pragma unroll 1
                for (int p = 0; p < 3; ++p) {
                    if (p == 1) mbar_wait(bar_adone, 0);
                    bulk_load(sbase + conv_buf(p), g_kvT + (size_t)(bid * 8 + 2 * p) * 2048, 8192, bar_k + 8 * p);
                    if (GAP_CV) __nanosleep(GAP_CV);
                }
                prefetch_map(&maps.out); prefetch_map(&maps.yt); prefetch_map(&maps.yt3);
#pragma unroll 1
                for (int p = 0; p < 4; ++p) {
                    mbar_wait(bar_stg + 16 + 8 * p, 0);
                    if (p == 0) {
                        mbar_expect_tx(bar_k + 24, 16384);
                        tma_load_4d(sbase + conv_buf(3) + 8192, &maps.sk, bar_k + 24, 0, 0, 0, bid * 8 + 6);
                        mbar_wait(bar_g2, 0);
                        tma_load_4d(sbase + conv_buf(3) + 12288, &maps.sk, bar_k + 24, 0, 0, 0, bid * 8 + 7);
                    }
#pragma unroll 1
                    for (int i = 0; i < 2; ++i) {
                        if (i) __nanosleep(GAP_Y);
                        asm volatile("cp.async.bulk.global.shared::cta.bulk_group [%0], [%1], 4096;"
                                     ::"l"(g_y2 + (size_t)(bid * 8 + 2 * p + i) * 2048), "r"(sbase + conv_buf(p) + i * 4096) : "memory");
                    }
                    bulk_commit();
                    STAMP(0, 24 + p);
                    if (p == 0) {
                        bulk_wait_read0();
                        bulk_load(sbase + conv_buf(3), g_kvT + (size_t)(bid * 8 + 6) * 2048, 8192, bar_k + 24);
                    }
                    if (p == 2) {
                        bulk_wait0();
                        fence_async_global();
                        red_release(&g_cnt[(48 + (bid >> 4)) * 32], 4);
                        mbar_arrive(bar_yrel);
                        STAMP(0, 3);
                    }
                }
                bulk_wait0();
                fence_async_global();
                red_release(&g_cnt[(32 + (bid >> 4)) * 32], 4);
                STAMP(0, 2);
                wait_counter(&g_cnt[(32 + dt) * 32], target);
                STAMP(0, 5);
                mbar_expect_tx(bar_y, 8192);
#pragma unroll 1
                for (int i = 6; i < 8; ++i)
                    tma_load_5d(sbase + OFF_CU + i * 4096, &maps.yt, bar_y, (tt & 1) * 1024 + ti * 128 + (i & 1) * 64, 0, 0, i >> 1, dt * 4);
#pragma unroll 1
                for (int i = 0; i < 8; ++i) {
                    mbar_wait(bar_stg + 48 + 8 * i, 0);
                    tma_store_5d(&maps.out, sbase + ((i & 4) ? OFF_CT : OFF_CU) + (i & 3) * 8192, dt * 128 + (i & 3) * 32, 0, 0, (tt & 1) * 4 + ((i & 4) >> 1), ti);
                    bulk_commit();
                }
                bulk_wait_read0();
                STAMP(2, 3);
                SAMPLE(21);
            }
        } else if (lane == 0) {
            mbar_wait(bar_tick + 8 * TK_PF0, 0);
#pragma unroll 1
            for (int i = 0; i < 8; ++i) {
                l2_prefetch(((i & 1) ? vin : kin) + (size_t)(ti * 256 + 32 * (i & 4) + (bid & 15) * 8 + 2 * (i & 2)) * D_DIM, 8192);
                __nanosleep(GAP_PF);
            }
            if (bid < 3) l2_prefetch(reinterpret_cast<const char*>(&g_conv_tab) + bid * 4096, 4096);
            prefetch_map(&maps.cre); prefetch_map(&maps.cim);
            mbar_wait(bar_tick + 8 * TK_C, 0);
#pragma unroll 1
            for (int i = 0; i < 8; ++i) {
                l2_prefetch((i & 1) ? ((i & 4) ? c_im : c_re) + (size_t)bid * 8192 + (i & 2) * 2048 : ssm_k + (size_t)bid * 16384 + (i >> 1) * 4096, 8192);
                __nanosleep(GAP_PF);
            }
            const unsigned int target = (ld_relaxed(&g_cnt[(4 * ti + 1) * 32]) & ~63u) + 64u;
            mbar_wait(bar_gate, 0);
#pragma unroll 1
            for (int q = 1; q < 4; ++q) {
                if (q < 3) mbar_wait(bar_hw + 8 * q, 0);
                if (q > 1) {
                    mbar_wait(bar_g2, 0);
                    char* hp = reinterpret_cast<char*>(g_H) + (size_t)((16 + 2 * ti) * 16 + (q & 1) * 8 + (cg >> 1)) * 16384 + (cg & 1) * 2048;
#pragma unroll 1
                    for (int i = 0; i < 8; ++i) {
                        asm volatile("cp.async.bulk.global.shared::cta.bulk_group [%0], [%1], 2048;"
                                     ::"l"(hp + (i & 3) * 4096 + (i >> 2) * 262144), "r"(sbase + OFF_BB + (q & 1) * 16384 + i * 2048) : "memory");
                        __nanosleep(GAP_HB);
                    }
                    bulk_commit();
                    wait_counter(&g_cnt[(4 * ti + q - 1) * 32], target);
                    mbar_arrive(bar_fh + 8 * q - 16);
                    bulk_wait0();
                    if (q == 3) mbar_arrive(bar_empty2 + 32);
                    fence_async_global();
                }
                red_release(&g_cnt[(4 * ti + q) * 32], 4);
                STAMP(0, 36 + q);
                if (q == 3) {
                    wait_counter(&g_cnt[(4 * ti + q) * 32], target);
                    mbar_arrive(bar_fh + 8 * q - 8);
                }
            }
        }
    } else {
    if (wg == 3) {
        if (warp != 12) asm volatile("bar.sync 4, 512;" ::: "memory");
        named_bar(3, 128);
        asm volatile("setmaxnreg.inc.sync.aligned.u32 %0;" ::"n"(REG_C));
        const int t = tid & 127, w4 = t >> 5;
        if (t == 0) SAMPLE(0);
        mbar_wait(bar_tick, 0);
        if (t < 64) {
            const int ch = (t >> 5) * 512 + cg * 32 + (t & 31);
            unsigned long long oldagg;
            asm volatile("ld.relaxed.gpu.global.u64 %0, [%1];" : "=l"(oldagg) : "l"(&g_agg[ti * D_DIM + ch]) : "memory");
            const float Lr = __bfloat162float(lam_re[ch]), Li = __bfloat162float(lam_im[ch]);
            const float dtv = bf16r(expf(__bfloat162float(log_dt[ch])));
            const unsigned int tag = ((((unsigned int)oldagg & 1u) | ((unsigned int)(oldagg >> 31) & 2u)) + 1u) & 3u;
            const float er = expf(dtv * Lr);
            float s, c;
            sincosf(dtv * Li, &s, &c);
            const float lr = er * c, li = er * s;
            const float nr = lr - 1.f, ni = li;
            const float den = Lr * Lr + Li * Li;
            const float cr = 2.f * (nr * Lr + ni * Li) / den, ci = 2.f * (ni * Lr - nr * Li) / den;
            float pr = lr, pi = -li;
#pragma unroll
            for (int i = 0; i < 5; ++i) csqr(pr, pi);
            sts128(sbase + OFF_PAR + t * 32, __float_as_uint(lr), __float_as_uint(-li), __float_as_uint(cr), __float_as_uint(ci));
            sts128(sbase + OFF_PAR + t * 32 + 16, __float_as_uint(pr), __float_as_uint(pi), tag, 0);
            __syncwarp();
            if (lane == 0) mbar_arrive(bar_par);
        }
        if (t >= 120) asm volatile("st.shared.b32 [%0], %1;" ::"r"(w_dsk - 480 + 4 * t),
                                   "r"(t < 124 ? __ldg(reinterpret_cast<const uint32_t*>(ssm_D + bid * 8) + (t & 3)) : 0u) : "memory");
        if (t < 64) asm volatile("st.shared.b32 [%0], %1;" ::"r"(w_ones + 4 * t), "r"(0x3F803F80u) : "memory");
        {
            const int cq = lane & 15, rg = (lane >> 4) + 2 * w4;
            uint32_t sk[4][4];
#pragma unroll
            for (int c = 0; c < 4; ++c) {
                const uint4 w = ldg128(shift_k + (size_t)(dt * 128 + 8 * cq + 2 * c) * 4);
                sk[0][c] = __byte_perm(w.x, w.z, 0x5410); sk[1][c] = __byte_perm(w.x, w.z, 0x7632);
                sk[2][c] = __byte_perm(w.y, w.w, 0x5410); sk[3][c] = __byte_perm(w.y, w.w, 0x7632);
            }
#pragma unroll 1
            for (int bt = 0; bt < 2; ++bt) {
                const int t0 = ti * 256 + 128 * bt + 16 * (rg & 4) + 32 * (tt & 1) + 8 * (rg & 3);
                mbar_wait(bar_tick + 8 * (bt ? TK_KV1 : TK_KV0), 0);
                if (t == 0) STAMP(0, 30 + 3 * bt);
                uint4 kk[11], vv[8];
                const __nv_bfloat16* kp = kin + (size_t)t0 * D_DIM + dt * 128 + 8 * cq;
                const __nv_bfloat16* vp = vin + (size_t)t0 * D_DIM + dt * 128 + 8 * cq;
#pragma unroll
                for (int i = 0; i < 11; ++i) {
                    if (i < 3 && t0 == 0) kk[i] = make_uint4(0, 0, 0, 0);
                    else kk[i] = ldg128(kp + (i - 3) * D_DIM);
                    if (i == 6 || i == 10) __nanosleep(GAP_KV);
                }
#pragma unroll
                for (int i = 0; i < 8; ++i) { vv[i] = ldg128(vp + i * D_DIM); if (i == 3) __nanosleep(GAP_KV); }
                const uint32_t ua = sbase + OFF_CT + bt * 16384 + cq * 128 + ((rg ^ ((2 * ti + bt) & 3) ^ (cq & 7)) << 4);
#pragma unroll
                for (int c = 0; c < 4; ++c) {
                    uint32_t res[8];
#pragma unroll
                    for (int i = 0; i < 8; ++i) {
                        uint32_t ks = hmul((&kk[i].x)[c], sk[3][c]);
                        ks = hadd(ks, hmul((&kk[i + 1].x)[c], sk[2][c]));
                        ks = hadd(ks, hmul((&kk[i + 2].x)[c], sk[1][c]));
                        ks = hadd(ks, hmul((&kk[i + 3].x)[c], sk[0][c]));
                        res[i] = hmul(ks, (&vv[i].x)[c]);
                    }
                    sts128(ua + (2 * c) * 2048, __byte_perm(res[0], res[1], 0x5410), __byte_perm(res[2], res[3], 0x5410),
                           __byte_perm(res[4], res[5], 0x5410), __byte_perm(res[6], res[7], 0x5410));
                    sts128(ua + (2 * c + 1) * 2048, __byte_perm(res[0], res[1], 0x7632), __byte_perm(res[2], res[3], 0x7632),
                           __byte_perm(res[4], res[5], 0x7632), __byte_perm(res[6], res[7], 0x7632));
                }
                fence_async_smem();
                __syncwarp();
                if (lane == 0) mbar_arrive(bar_stg + 8 * bt);
                if (t == 0) STAMP(0, 21 + bt);
            }
        }
        {
            const int row = bid * 16 + (t >> 3);
            uint4 xv[16];
#pragma unroll
            for (int n = 0; n < 16; ++n) {
                xv[n] = ldg128(x + (size_t)row * D_DIM + ((t & 7) + 8 * n) * 8);
                if ((n & 3) == 3) __nanosleep(GAP_KV);
            }
#pragma unroll
            for (int n8 = 0; n8 < 16; n8 += 8) {
                uint4 wv[8];
#pragma unroll
                for (int n = 0; n < 8; ++n) wv[n] = ldg128(gate_w + ((t & 7) + 8 * (n8 + n)) * 8);
#pragma unroll
                for (int n = 0; n < 8; ++n) {
                    uint4& p = xv[n8 + n];
                    p.x = hmul(p.x, wv[n].x); p.y = hmul(p.y, wv[n].y); p.z = hmul(p.z, wv[n].z); p.w = hmul(p.w, wv[n].w);
                }
            }
            float d[4] = {0.f, 0.f, 0.f, 0.f};
            fence_regs(d);
            named_bar(3, 128);
            wgmma_fence();
#pragma unroll
            for (int n = 0; n < 16; ++n)
                asm volatile("{\n.reg .b64 db;\nmov.b64 db, {%8, 8};\n"
                             "wgmma.mma_async.sync.aligned.m64n8k16.f32.bf16.bf16 {%0, %1, %2, %3}, {%4, %5, %6, %7}, db, 1, 1, 1, 0;\n}\n"
                             : "+f"(d[0]), "+f"(d[1]), "+f"(d[2]), "+f"(d[3]) : "r"(xv[n].x), "r"(xv[n].y), "r"(xv[n].z), "r"(xv[n].w), "r"(desc_lo(w_ones, 128)));
            wgmma_commit();
            wgmma_wait<0>();
            fence_regs(d);
#pragma unroll
            for (int n = 0; n < 16; ++n) asm volatile("" ::"r"(xv[n].x), "r"(xv[n].y), "r"(xv[n].z), "r"(xv[n].w) : "memory");
            float sum = d[0] + d[2];
            sum += __shfl_xor_sync(0xffffffffu, sum, 4);
            if ((t & 7) == 0) g_gate[row] = bf16r(1.f / (1.f + expf(-bf16r(sum))));
            if (t == 0) STAMP(0, 4);
            __syncwarp();
            if (lane == 0) mbar_arrive(bar_gate);
        }
    } else {
        asm volatile("setmaxnreg.inc.sync.aligned.u32 %0;" ::"n"(REG_AB));
        if (tid == 128) STAMP(1, 54);
        asm volatile("bar.sync 4, 512;" ::: "memory");
        if (tid == 128) STAMP(1, 55);
        const int cw = wg - 1;
        const int t = tid & 127, w4 = t >> 5, g = lane >> 2, t4 = lane & 3;
        {
            float a0[64], a1[64];
            auto release = [&](int it) {
                if (it < 12 + XTRA && t <= ((it >= 16 - SKEW1 && it < 12) || it >= 16)) mbar_arrive(bar_empty + 8 * (it & 3));
            };
#pragma unroll 1
            for (int kb = 0; kb < 16; ++kb) {
                const int it = cw == 1 && kb >= 16 - SKEW1 ? kb + XTRA : kb, st = it & 3;
                if (cw == 1 && kb == 16 - SKEW1) mbar_wait(bar_ab, 0);
                mbar_wait(bar_full + 8 * st, (it >> 2) & 1);
                if (kb == 0 && tid == 288) mbar_arrive(bar_tick);
                if (kb == 0 && t == 0) STAMP(1, 14 + cw);
                const uint32_t alo = desc_lo(sbase + (cw ? OFF_BB : OFF_CU) + st * 8192, 16), blo = desc_lo(sbase + ((it - XTRA) & 3) * 32768, 16);
                wgmma_fence();
#pragma unroll
                for (int k = 0; k < 4; ++k) {
                    wgmma_n128<0>(a0, alo + 2 * k, blo + 2 * k, k ? 1 : kb);
                    wgmma_n128<0>(a1, alo + 2 * k, blo + 1024 + 2 * k, k ? 1 : kb);
                }
                wgmma_commit();
                wgmma_wait<1>();
                if (kb > 0 && !(cw == 1 && kb == 16 - SKEW1)) release(it - 1);
                if (cw == 1 && kb == 15 - SKEW1) {
                    wgmma_wait<0>();
                    release(it);
                }
                if (cw == 1 && kb > 12) {
                    if (kb == 13) mbar_wait(bar_adone, 0);
                    if (t == 0) mbar_arrive(bar_empty2 + 8 * (kb - 13));
                }
            }
            if (tid == 192) mbar_arrive(bar_ab);
            float mr, mi, cr, ci, p32r, p32i;
            uint32_t tag;
            mbar_wait(bar_par, 0);
            {
                const uint32_t par = sbase + OFF_PAR + (cw * 32 + w4 * 8 + g) * 32;
                uint32_t dummy;
                asm volatile("ld.shared.v4.f32 {%0,%1,%2,%3}, [%4];" : "=f"(mr), "=f"(mi), "=f"(cr), "=f"(ci) : "r"(par));
                asm volatile("ld.shared.v4.b32 {%0,%1,%2,%3}, [%4];" : "=f"(p32r), "=f"(p32i), "=r"(tag), "=r"(dummy) : "r"(par + 16));
            }
            const float l1i = SW ? mi : -mi;
            auto map = [&](float p, float q, float& r, float& i) {
                if (SW) { r = fmaf(cr, q, -ci * p); i = fmaf(-cr, p, -ci * q); }
                else { r = fmaf(cr, p, -ci * q); i = fmaf(-cr, q, -ci * p); }
            };
            float p64r = p32r, p64i = p32i;
            csqr(p64r, p64i);
            float p128r = p64r, p128i = p64i;
            csqr(p128r, p128i);
            wgmma_wait<0>();
            fence_regs(a0); fence_regs(a1);
            if (cw == 0) { release(15); if (lane == 0) mbar_arrive(bar_adone); }
            else if (t == 0) mbar_arrive(bar_empty2 + 24);
            if (t == 0) STAMP(1, 2 + 6 * cw);
            float hr = 0.f, hi = 0.f, ar = 0.f, ai = 0.f;
#pragma unroll
            for (int j = 0; j < 16; ++j)
#pragma unroll
                for (int e = 0; e < 2; ++e) {
                    const float nr = fmaf(mr, ar, fmaf(-l1i, ai, a0[4 * j + e])), ni = fmaf(mr, ai, fmaf(l1i, ar, a0[4 * j + 2 + e]));
                    const float or_ = fmaf(mr, hr, fmaf(-l1i, hi, a1[4 * j + e])), oi = fmaf(mr, hi, fmaf(l1i, hr, a1[2 + 4 * j + e]));
                    ar = nr; ai = ni; hr = or_; hi = oi;
                }
            map(ar, ai, ar, ai);
            map(hr, hi, hr, hi);
            hr += p32r * ar - p32i * ai; hi += p32r * ai + p32i * ar;
            {
                float vr = __shfl_up_sync(0xffffffffu, hr, 1, 4), vi = __shfl_up_sync(0xffffffffu, hi, 1, 4);
                if (t4 >= 1) { hr += p64r * vr - p64i * vi; hi += p64r * vi + p64i * vr; }
                vr = __shfl_up_sync(0xffffffffu, hr, 2, 4); vi = __shfl_up_sync(0xffffffffu, hi, 2, 4);
                if (t4 >= 2) { hr += p128r * vr - p128i * vi; hi += p128r * vi + p128i * vr; }
            }
            unsigned long long* ap = &g_agg[ti * D_DIM + cw * 512 + cg * 32 + w4 * 8 + g];
            if (t4 == 3) asm volatile("{\n.reg .b64 a;\nmov.b64 a, {%1, %2};\nst.relaxed.gpu.global.u64 [%0], a;\n}\n" ::"l"(ap),
                                      "r"((__float_as_uint(hr) & ~1u) | (tag & 1u)), "r"((__float_as_uint(hi) & ~1u) | (tag >> 1)) : "memory");
            float exr = __shfl_up_sync(0xffffffffu, hr, 1, 4), exi = __shfl_up_sync(0xffffffffu, hi, 1, 4);
            if (t4 == 0) { exr = 0.f; exi = 0.f; }
            if (t == 0) STAMP(1, 3 + 6 * cw);
            ci = after(ci, exr);
#pragma unroll
            for (int j = 0; j < 16; ++j)
#pragma unroll
                for (int e = 0; e < 2; ++e) {
                    map(a0[4 * j + e], a0[4 * j + 2 + e], a0[4 * j + e], a0[4 * j + 2 + e]);
                    map(a1[4 * j + e], a1[4 * j + 2 + e], a1[4 * j + e], a1[4 * j + 2 + e]);
                }
            float qr = 1.f, qi = 0.f, ur = 1.f, ui = 0.f;
            if (t4 & 1) { qr = p64r; qi = p64i; }
            if (t4 & 2) cmul(qr, qi, qr, qi, p128r, p128i);
            csqr(p128r, p128i);
            if (t4 & 1) { ur = p128r; ui = p128i; }
            csqr(p128r, p128i);
            if (t4 & 2) cmul(ur, ui, ur, ui, p128r, p128i);
            csqr(p128r, p128i);
            fence_regs(a0); fence_regs(a1);
            if (t == 0) STAMP(1, 7 + 6 * cw);
            if (ti > 0) {
                const unsigned long long tmask = 0x0000000100000001ull, tval = ((unsigned long long)(tag >> 1) << 32) | (tag & 1u);
                unsigned long long u0 = tval, u1 = tval;
                ap -= D_DIM * (1 + t4);
                int it = 0;
                do {
                    asm volatile("{\n.reg .pred p, q;\nsetp.gt.s32 p, %3, 0;\nsetp.gt.s32 q, %3, 4;\n@p ld.relaxed.gpu.global.u64 %0, [%2];\n"
                                 "@q ld.relaxed.gpu.global.u64 %1, [%2+-32768];\n}\n" : "+l"(u0), "+l"(u1) : "l"(ap), "r"(ti - t4) : "memory");
                } while (__any_sync(0xffffffffu, (((u0 ^ tval) | (u1 ^ tval)) & tmask) != 0) && ++it < (1 << 22));
                float Pr = __uint_as_float((unsigned)u1 & ~1u), Pi = __uint_as_float((unsigned)(u1 >> 32) & ~1u);
                cmul(Pr, Pi, Pr, Pi, p128r, p128i);
                Pr += __uint_as_float((unsigned)u0 & ~1u); Pi += __uint_as_float((unsigned)(u0 >> 32) & ~1u);
                cmul(Pr, Pi, Pr, Pi, ur, ui);
                Pr += __shfl_xor_sync(0xffffffffu, Pr, 1); Pi += __shfl_xor_sync(0xffffffffu, Pi, 1);
                Pr += __shfl_xor_sync(0xffffffffu, Pr, 2); Pi += __shfl_xor_sync(0xffffffffu, Pi, 2);
                exr += qr * Pr - qi * Pi;
                exi += qr * Pi + qi * Pr;
            }
            if (t == 0) STAMP(1, 4 + 6 * cw);
            char* hp = reinterpret_cast<char*>(g_H) + (size_t)((2 * ti) * 16 + (cg >> 1)) * 16384 + ((cg & 1) * 32 + w4 * 8 + g) * 64 + ((t4 ^ (g >> 1)) << 4);
            float fxr = ar + p32r * exr - p32i * exi, fxi = ai + p32r * exi + p32i * exr;
            const uint32_t hs = sbase + OFF_BB + (w4 * 8 + g) * 64 + ((t4 ^ (g >> 1)) << 4);
            if (cw == 1) named_bar(2, 128);
            uint32_t im[32];
#pragma unroll
            for (int jj = 0; jj < 4; ++jj) {
                uint32_t pr[4], qq[4];
#pragma unroll
                for (int j4 = 0; j4 < 4; ++j4) {
                    const int j = jj * 4 + j4;
                    const float r0 = fmaf(mr, exr, fmaf(-mi, exi, a0[4 * j])), i0 = fmaf(mr, exi, fmaf(mi, exr, a0[4 * j + 2]));
                    const float r1 = fmaf(mr, fxr, fmaf(-mi, fxi, a1[4 * j])), i1 = fmaf(mr, fxi, fmaf(mi, fxr, a1[2 + 4 * j]));
                    exr = fmaf(mr, r0, fmaf(-mi, i0, a0[4 * j + 1]));
                    exi = fmaf(mr, i0, fmaf(mi, r0, a0[4 * j + 3]));
                    fxr = fmaf(mr, r1, fmaf(-mi, i1, a1[1 + 4 * j]));
                    fxi = fmaf(mr, i1, fmaf(mi, r1, a1[3 + 4 * j]));
                    pr[j4] = pack_bf16(r0, exr); im[j] = pack_bf16(i0, exi);
                    qq[j4] = pack_bf16(r1, fxr); im[16 + j] = pack_bf16(i1, fxi);
                }
                if (cw == 0) {
                    stg128(hp + jj * 4096, pr[0], pr[1], pr[2], pr[3]);
                    stg128(hp + jj * 4096 + 262144, qq[0], qq[1], qq[2], qq[3]);
                } else {
                    sts128(hs + jj * 2048, pr[0], pr[1], pr[2], pr[3]);
                    sts128(hs + jj * 2048 + 8192, qq[0], qq[1], qq[2], qq[3]);
                }
            }
            if (t == 0) STAMP(1, 5 + 6 * cw);
            if (cw == 0) {
                named_bar(1, 128);
                if (t == 0) { red_release(&g_cnt[(4 * ti) * 32], 4); mbar_arrive(bar_rel); }
                named_bar(1, 128);
                if (t == 0) STAMP(1, 6);
#pragma unroll
                for (int jj = 0; jj < 8; ++jj) stg128(hp + 131072 + (jj & 3) * 4096 + (jj >> 2) * 262144, im[4 * jj], im[4 * jj + 1], im[4 * jj + 2], im[4 * jj + 3]);
            } else {
#pragma unroll
                for (int jj = 0; jj < 8; ++jj) sts128(hs + 16384 + jj * 2048, im[4 * jj], im[4 * jj + 1], im[4 * jj + 2], im[4 * jj + 3]);
                fence_async_smem();
            }
            __syncwarp();
            if (lane == 0) mbar_arrive(bar_hw + 8 * cw + 8);
            if (t == 0) STAMP(1, 50 + cw);
        }
        if (cw == 0) {
            float c0[64], c1[64];
            int st = 0, pst = 0;
            uint32_t ph = 0;
            auto kblock = [&](int kb, auto shallow) {
                const int t = fresh_tid() & 127, lane = t & 31;
                mbar_wait(bar_full2 + 8 * st, st == 4 ? ph ^ PH4 : ph);
                if (kb == 0 && t == 0) STAMP(2, 6);
                if (kb == 0 && lane == 0) mbar_arrive(bar_g2);
                const uint32_t alo = desc_lo(sbase + st * 32768, 4096), blo = desc_lo(sbase + st * 32768 + 16384, 16);
                constexpr int Q = decltype(shallow)::value;
#pragma unroll
                for (int j = 0; j < 8; ++j) {
                    wgmma_fence();
                    if (j & 1) wgmma_n128<1>(c1, alo + 512 + 64 * (j >> 1), blo + 2 * (j >> 1), j >> 1 ? 1 : kb);
                    else wgmma_n128<1>(c0, alo + 64 * (j >> 1), blo + 2 * (j >> 1), j >> 1 ? 1 : kb);
                    wgmma_commit();
                    wgmma_wait<Q>();
                    if (j == Q - 1 && kb > 0 && t == 0) mbar_arrive(bar_empty2 + 8 * pst);
                }
                pst = st;
                if (++st == (kb < SLOT4 - 1 ? 4 : 5)) { st = 0; ph ^= 1; }
            };
#pragma unroll 1
            for (int kb = 0; kb < QKB; ++kb) kblock(kb, std::integral_constant<int, QD>());
#pragma unroll 1
            for (int kb = QKB; kb < 32 - SKEW2; ++kb) kblock(kb, std::integral_constant<int, QD2>());
            static_assert(SKEW2 <= 4, "slot release");
            const uint32_t alo = desc_lo(sbase, 4096), blo = desc_lo(sbase + 16384, 16);
#pragma unroll
            for (int kb = 32 - SKEW2; kb < 32; ++kb) {
                mbar_wait(bar_full2 + 8 * ring_slot(kb), ring_par(kb));
                wgmma_fence();
#pragma unroll
                for (int k = 0; k < 4; ++k) wgmma_n128<1>(c0, alo + ring_slot(kb) * 2048 + 64 * k, blo + ring_slot(kb) * 2048 + 2 * k, 1);
                wgmma_commit();
            }
            auto late = [&](int kb) {
                wgmma_fence();
#pragma unroll
                for (int k = 0; k < 4; ++k) wgmma_n128<1>(c1, alo + 512 + ring_slot(kb) * 2048 + 64 * k, blo + ring_slot(kb) * 2048 + 2 * k, 1);
                wgmma_commit();
            };
            late(32 - SKEW2);
            const int t = fresh_tid() & 127, lane = t & 31, w4 = t >> 5, g = lane >> 2, t4 = lane & 3;
            auto epilogue = [&](const float (&a)[64], int b) {
                const uint32_t ad0 = sbase + (b ? OFF_CT : OFF_CU) + (w4 * 16 + g) * 128 + (((2 * t4) ^ g) << 4);
                float gt[2];
                uint32_t bv[4][4];
#pragma unroll
                for (int h = 0; h < 2; ++h) gt[h] = __uint_as_float(lds32(sbase + OFF_PAR + (64 * b + 16 * w4 + 8 * h + g) * 4));
#pragma unroll
                for (int i = 0; i < 4; ++i)
                    asm volatile("ld.shared.v4.b32 {%0,%1,%2,%3}, [%4];" : "=r"(bv[i][0]), "=r"(bv[i][1]), "=r"(bv[i][2]), "=r"(bv[i][3])
                                 : "r"(ad0 + (i & 1) * 1024 + (i >> 1) * 8192) : "memory");
                if (b == 0) wgmma_wait<1>(); else wgmma_wait<0>();
                if (b == 0) fence_regs(c0); else fence_regs(c1);
                if (t == 0) STAMP(2, b ? 2 : 5);
#pragma unroll
                for (int jq = 0; jq < 4; ++jq) {
                    if (b == 0 && jq < SKEW2 - 1) late(33 - SKEW2 + jq);
#pragma unroll
                    for (int h = 0; h < 2; ++h) {
                        const uint32_t ad = ad0 + h * 1024 + jq * 8192;
                        uint32_t (&w)[4] = bv[2 * (jq & 1) + h];
                        const int r = 16 * jq + 2 * h;
                        sts128(ad, __float_as_uint(fmaf(gt[h], a[r], bf_lo(w[0]))), __float_as_uint(fmaf(gt[h], a[r + 1], bf_hi(w[0]))),
                               __float_as_uint(fmaf(gt[h], a[r + 4], bf_lo(w[1]))), __float_as_uint(fmaf(gt[h], a[r + 5], bf_hi(w[1]))));
                        sts128(ad ^ 16, __float_as_uint(fmaf(gt[h], a[r + 8], bf_lo(w[2]))), __float_as_uint(fmaf(gt[h], a[r + 9], bf_hi(w[2]))),
                               __float_as_uint(fmaf(gt[h], a[r + 12], bf_lo(w[3]))), __float_as_uint(fmaf(gt[h], a[r + 13], bf_hi(w[3]))));
                        if (jq < 2) asm volatile("ld.shared.v4.b32 {%0,%1,%2,%3}, [%4];" : "=r"(w[0]), "=r"(w[1]), "=r"(w[2]), "=r"(w[3]) : "r"(ad + 16384) : "memory");
                    }
                    fence_async_smem();
                    __syncwarp();
                    if (lane == 0) mbar_arrive(bar_stg + 48 + 32 * b + 8 * jq);
                }
            };
            mbar_wait(bar_bias, 0);
            if (t == 0) STAMP(2, 4);
            epilogue(c0, 0);
            mbar_wait(bar_bias + 8, 0);
            epilogue(c1, 1);
            if (t == 0) STAMP(2, 7);
            return;
        }
        asm volatile("setmaxnreg.dec.sync.aligned.u32 %0;" ::"n"(REG_C));
    }
    {
        {
            const int t = fresh_tid() & 127, lane = t & 31, w4 = t >> 5;
            Twiddle tw;
            load_twiddle(tw, reinterpret_cast<const uint4*>(g_tw_tab.w) + t);
            const uint32_t lo = (uint32_t)((16 * w4 + (lane & 7)) * 64 + (((lane >> 3) ^ ((lane >> 1) & 3)) << 4));
            const uint32_t tlo = desc_lo(sbase + OFF_CT, 16);
            float dE[32], dO[32];
            int p = wg == 2 ? 2 : 0;
            mbar_wait(bar_stg, 0);
            mbar_wait(bar_tab, 0);
            mbar_wait(bar_k + 8 * p, 0);
            if (t == 0) STAMP(0, wg == 2 ? 50 : 1);
            wgmma_fence();
            conv_s1(dE, dO, tlo, desc_lo(sbase + conv_buf(0) + p * 16384, 8192));
            wgmma_commit();
            wgmma_wait<0>();
            fence_regs(dE); fence_regs(dO);
            named_bar(wg, 128);
#pragma unroll 1
            for (; p < 4; p = 2 * p + 1) {
                const int pn = p < 2 ? 2 * p + 1 : p;
                if (t == 0) STAMP(0, 40 + 2 * p);
                conv_pair(dE, dO, tw, lds32(w_dsk + ((lane & 3) ? 16 : 4 * p)), tlo, sbase + conv_buf(p), sbase + conv_buf(pn), lo, wg,
                                [&]() { mbar_wait(bar_k + 8 * pn, 0); });
                if (lane == 0) mbar_arrive(bar_stg + 16 + 8 * p);
            }
            if (t == 0) STAMP(0, 57 + wg);
            __syncwarp();
        }
        if (wg == 2) {
            {
            const int t = fresh_tid() & 127, lane = t & 31, w4 = t >> 5, g = lane >> 2, t4 = lane & 3;
            const int bid = lds32(w_bid), dt = bid & 7;
            const int trow = (bid >> 4) * 256 + 4 * (bid & 8) + 128 * (w4 & 1) + 8 * (w4 >> 1) + g;
            uint4 xv[16], dk[4];
            const __nv_bfloat16* xp = x + (size_t)trow * D_DIM + dt * 128 + 8 * t4;
#pragma unroll
            for (int i = 0; i < 16; ++i) {
                xv[i] = ldg128(xp + (size_t)(16 * (i >> 3) + 64 * ((i >> 2) & 1)) * D_DIM + 32 * (i & 3));
                if (i & 1) __nanosleep(GAP_X);
            }
#pragma unroll
            for (int jq = 0; jq < 4; ++jq) dk[jq] = ldg128(dskip + dt * 128 + 32 * jq + 8 * t4);
            mbar_wait(bar_fh, 0);
            uint32_t omg[4], g2[4];
#pragma unroll
            for (int i = 0; i < 4; ++i) {
                const float gt = __ldcg(g_gate + trow + 16 * (i >> 1) + 64 * (i & 1));
                if (t4 == 0) asm volatile("st.shared.f32 [%0], %1;" ::"r"(sbase + OFF_PAR + (64 * (i >> 1) + 16 * w4 + 8 * (i & 1) + g) * 4), "f"(gt) : "memory");
                omg[i] = pack_bf16(2.f - 2.f * gt, 2.f - 2.f * gt); g2[i] = pack_bf16(gt, gt);
            }
            if (t == 0) {
                mbar_wait(bar_yrel, 0);
                wait_counter(&g_cnt[(48 + dt) * 32], lds32(w_bid + 4));
                STAMP(0, 16);
                mbar_expect_tx(bar_y1, 24576);
                tma_load_5d(sbase + OFF_CU, &maps.yt3, bar_y1, (bid & 8) * 128 + (bid >> 4) * 128, 0, 0, 0, dt * 4);
                tma_load_5d(sbase + OFF_CU + 12288, &maps.yt3, bar_y1, (bid & 8) * 128 + (bid >> 4) * 128 + 64, 0, 0, 0, dt * 4);
            }
            __syncwarp();
            uint32_t ya = sbase + OFF_CU + (w4 & 1) * 12288 + (lane >> 3) * 3072 + (lane & 7) * 128 + ((((w4 >> 1) ^ ((bid >> 3 & 2) + (w4 & 1))) ^ (lane & 7)) << 4);
#pragma unroll
            for (int p = 0; p < 4; ++p) {
                if (p == 0) { mbar_wait(bar_y1, 0); if (t == 0) STAMP(0, 18); }
                if (p == 3) {
                    if (t == 0) STAMP(0, 17);
                    ya += 21504 - (w4 & 1) * 8192 - (lane >> 3) * 2048;
                    mbar_wait(bar_y, 0);
                    if (t == 0) STAMP(0, 6);
                }
#pragma unroll
                for (int i = 0; i < 4; ++i) {
                    uint32_t yw[4];
                    ldsm_x4_t(yw[0], yw[1], yw[2], yw[3], (ya ^ ((i & 1) << 6) ^ ((i & 2) << 4)) + p * 1024);
#pragma unroll
                    for (int jq = 0; jq < 4; ++jq) {
                        uint32_t& w = (&xv[4 * i + jq].x)[p];
                        w = hfma(g2[i], hmul(w, (&dk[jq].x)[p]), hmul(omg[i], hmul(w, yw[jq])));
                    }
                }
            }
            named_bar(2, 128);
#pragma unroll
            for (int i = 0; i < 16; ++i) {
                sts128(sbase + (i & 8 ? OFF_CT : OFF_CU) + (i & 3) * 8192 + (w4 * 16 + g + (i & 4) * 2) * 128 + (((2 * t4) ^ g) << 4), xv[i].x, xv[i].y, xv[i].z, xv[i].w);
                if ((i & 7) == 7) {
                    __syncwarp();
                    if (lane == 0) mbar_arrive(bar_bias + (i & 8));
                }
            }
            if (t == 0) STAMP(0, 7);
            }
        }
    }
    }
}

void make_map(CUtensorMap* m, const void* ptr, int rank, const cuuint64_t* dims, const cuuint64_t* strides, const cuuint32_t* box,
              CUtensorMapSwizzle swz, bool f32 = false) {
    cuuint32_t es[5] = {1, 1, 1, 1, 1};
    get_encode()(m, f32 ? CU_TENSOR_MAP_DATA_TYPE_FLOAT32 : CU_TENSOR_MAP_DATA_TYPE_BFLOAT16, rank, const_cast<void*>(ptr), dims, strides, box, es,
                 CU_TENSOR_MAP_INTERLEAVE_NONE, swz, CU_TENSOR_MAP_L2_PROMOTION_L2_256B, CU_TENSOR_MAP_FLOAT_OOB_FILL_NONE);
}
void make_map_2d(CUtensorMap* m, const void* ptr, uint64_t inner, uint64_t outer, uint32_t box_in, uint32_t box_out) {
    cuuint64_t dims[2] = {inner, outer};
    cuuint64_t strides[1] = {inner * 2};
    cuuint32_t box[2] = {box_in, box_out};
    make_map(m, ptr, 2, dims, strides, box, CU_TENSOR_MAP_SWIZZLE_128B);
}
void make_map_conv(CUtensorMap* m, const void* p, uint32_t nch = 2) {
    cuuint64_t dims[4] = {32, 32, 2, 1024};
    cuuint64_t strides[3] = {128, 64, 4096};
    cuuint32_t box[4] = {32, 32, 2, nch};
    make_map(m, p, 4, dims, strides, box, CU_TENSOR_MAP_SWIZZLE_64B);
}

}

extern "C" void kernel_launch(void* const* d_in, const int* in_sizes, int n_in, void* d_out, int out_size) {
    const __nv_bfloat16* x = (const __nv_bfloat16*)d_in[0];
    const __nv_bfloat16* lam_re = (const __nv_bfloat16*)d_in[1];
    const __nv_bfloat16* lam_im = (const __nv_bfloat16*)d_in[2];
    const __nv_bfloat16* b_re = (const __nv_bfloat16*)d_in[3];
    const __nv_bfloat16* b_im = (const __nv_bfloat16*)d_in[4];
    const __nv_bfloat16* c_re = (const __nv_bfloat16*)d_in[5];
    const __nv_bfloat16* c_im = (const __nv_bfloat16*)d_in[6];
    const __nv_bfloat16* log_dt = (const __nv_bfloat16*)d_in[7];
    const __nv_bfloat16* dskip = (const __nv_bfloat16*)d_in[8];
    const __nv_bfloat16* kin = (const __nv_bfloat16*)d_in[10];
    const __nv_bfloat16* vin = (const __nv_bfloat16*)d_in[11];
    const __nv_bfloat16* shift_k = (const __nv_bfloat16*)d_in[12];
    const __nv_bfloat16* ssm_k = (const __nv_bfloat16*)d_in[13];
    const __nv_bfloat16* ssm_D = (const __nv_bfloat16*)d_in[14];
    const __nv_bfloat16* gate_w = (const __nv_bfloat16*)d_in[15];
    float* out = (float*)d_out;

    void *yptr = nullptr, *kvtptr = nullptr;
    cudaGetSymbolAddress(&yptr, g_y2);
    cudaGetSymbolAddress(&kvtptr, g_kvT);

    Maps maps;
    {
        cuuint64_t dims[5] = {1024, 2, 4, 32, 8};
        cuuint64_t strides[4] = {2048, 64 * 2048, 2 * 2048, 256 * 2048};
        cuuint32_t box[5] = {64, 2, 4, 32, 1};
        make_map(&maps.x5, x, 5, dims, strides, box, CU_TENSOR_MAP_SWIZZLE_128B);
    }
    int bmode = 0;
    {
        const uint64_t a = (uint64_t)b_re, b = (uint64_t)b_im;
        const uint64_t delta = a < b ? b - a : a - b;
        if (delta != 0 && (delta & 15) == 0 && delta < (1ull << 40)) bmode = a < b ? 1 : 2;
        cuuint64_t dims[4] = {1024, 8, 2, 128};
        cuuint64_t strides[3] = {2048, bmode ? delta : 16, 16384};
        cuuint32_t box[4] = {64, 8, 2, 4};
        make_map(&maps.b4, a < b ? b_re : b_im, 4, dims, strides, box, CU_TENSOR_MAP_SWIZZLE_128B);
    }
    make_map_2d(&maps.bre, b_re, 1024, 1024, 64, 8);
    make_map_2d(&maps.bim, b_im, 1024, 1024, 64, 8);
    {
        cuuint64_t dims[3] = {S_LEN, 128, 8};
        cuuint64_t strides[2] = {8 * 4096, 4096};
        cuuint32_t box[3] = {64, 16, 2};
        make_map(&maps.kvst, kvtptr, 3, dims, strides, box, CU_TENSOR_MAP_SWIZZLE_128B);
    }
    make_map_conv(&maps.sk, ssm_k, 1);
    for (int i = 0; i < 2; ++i) {
        cuuint64_t dims[5] = {1024, 2, 4, 4, 32};
        cuuint64_t strides[4] = {2048, 8 * 2048, 2 * 2048, 32 * 2048};
        cuuint32_t box[5] = {64, 2, 4, 4, 4};
        make_map(i ? &maps.cim : &maps.cre, i ? c_im : c_re, 5, dims, strides, box, CU_TENSOR_MAP_SWIZZLE_128B);
    }
    {
        cuuint64_t dims[5] = {S_LEN, 2, 4, 4, 32};
        cuuint64_t strides[4] = {4096, 8 * 4096, 2 * 4096, 32 * 4096};
        cuuint32_t box[5] = {64, 2, 4, 1, 4};
        make_map(&maps.yt, yptr, 5, dims, strides, box, CU_TENSOR_MAP_SWIZZLE_128B);
        box[3] = 3;
        make_map(&maps.yt3, yptr, 5, dims, strides, box, CU_TENSOR_MAP_SWIZZLE_128B);
    }
    {
        cuuint64_t dims[5] = {D_DIM, 8, 4, 8, 8};
        cuuint64_t strides[4] = {4096, 64 * 4096, 8 * 4096, 256 * 4096};
        cuuint32_t box[5] = {32, 8, 4, 2, 1};
        make_map(&maps.out, out, 5, dims, strides, box, CU_TENSOR_MAP_SWIZZLE_128B, true);
    }

    auto kern = bmode == 1 ? fused_kernel<1> : bmode == 2 ? fused_kernel<2> : fused_kernel<0>;
    cudaFuncSetAttribute(kern, cudaFuncAttributeMaxDynamicSharedMemorySize, SMEM_BYTES);
    static int grid = 0;
    if (!grid) {
        int dev = 0, sms = 0;
        cudaGetDevice(&dev);
        cudaDeviceGetAttribute(&sms, cudaDevAttrMultiProcessorCount, dev);
        grid = sms == 132 ? 132 : 128;
    }
    kern<<<grid, 512, SMEM_BYTES>>>(x, kin, vin, ssm_k, shift_k, ssm_D, lam_re, lam_im, log_dt, gate_w, dskip, c_re, c_im, maps);
}
```

```cpp
#include <cuda_runtime.h>
#include <cuda_bf16.h>
#include <cuda.h>
#include <stdint.h>
#include <type_traits>

namespace {
__device__ __forceinline__ uint32_t smem_u32(const void* p) { return (uint32_t)__cvta_generic_to_shared(p); }
__device__ __forceinline__ void mbar_init(uint32_t bar, uint32_t count) {
    asm volatile("mbarrier.init.shared::cta.b64 [%0], %1;" ::"r"(bar), "r"(count) : "memory");
}
__device__ __forceinline__ void mbar_expect_tx(uint32_t bar, uint32_t bytes) {
    asm volatile("mbarrier.arrive.expect_tx.shared::cta.b64 _, [%0], %1;" ::"r"(bar), "r"(bytes) : "memory");
}
__device__ __forceinline__ void mbar_arrive(uint32_t bar) {
    asm volatile("mbarrier.arrive.shared::cta.b64 _, [%0];" ::"r"(bar) : "memory");
}
__device__ __forceinline__ void mbar_wait(uint32_t bar, uint32_t parity) {
    asm volatile(
        "{\n"
        ".reg .pred p;\n"
        ".reg .u32 n;\n"
        "mov.u32 n, 0;\n"
        "LAB_WAIT:\n"
        "mbarrier.try_wait.parity.shared::cta.b64 p, [%0], %1;\n"
        "@p bra LAB_DONE;\n"
        "add.u32 n, n, 1;\n"
        "setp.lt.u32 p, n, 0x400000;\n"
        "@p bra LAB_WAIT;\n"
        "trap;\n"
        "LAB_DONE:\n"
        "}\n" ::"r"(bar), "r"(parity) : "memory");
}
__device__ __forceinline__ void tma_load_2d(uint32_t dst, const CUtensorMap* map, uint32_t bar, int c0, int c1) {
    asm volatile(
        "cp.async.bulk.tensor.2d.shared::cluster.global.mbarrier::complete_tx::bytes [%0], [%1, {%3, %4}], [%2];"
        ::"r"(dst), "l"((uint64_t)map), "r"(bar), "r"(c0), "r"(c1) : "memory");
}
__device__ __forceinline__ void tma_load_4d(uint32_t dst, const CUtensorMap* map, uint32_t bar, int c0, int c1, int c2, int c3) {
    asm volatile(
        "cp.async.bulk.tensor.4d.shared::cluster.global.mbarrier::complete_tx::bytes [%0], [%1, {%3, %4, %5, %6}], [%2];"
        ::"r"(dst), "l"((uint64_t)map), "r"(bar), "r"(c0), "r"(c1), "r"(c2), "r"(c3) : "memory");
}
__device__ __forceinline__ void tma_load_5d(uint32_t dst, const CUtensorMap* map, uint32_t bar, int c0, int c1, int c2, int c3, int c4) {
    asm volatile(
        "cp.async.bulk.tensor.5d.shared::cluster.global.mbarrier::complete_tx::bytes [%0], [%1, {%3, %4, %5, %6, %7}], [%2];"
        ::"r"(dst), "l"((uint64_t)map), "r"(bar), "r"(c0), "r"(c1), "r"(c2), "r"(c3), "r"(c4) : "memory");
}
__device__ __forceinline__ void bulk_load(uint32_t dst, const void* src, uint32_t bytes, uint32_t bar) {
    asm volatile("cp.async.bulk.shared::cluster.global.mbarrier::complete_tx::bytes [%0], [%1], %2, [%3];"
                 ::"r"(dst), "l"(src), "r"(bytes), "r"(bar) : "memory");
}
__device__ __forceinline__ void tma_store_3d(const CUtensorMap* map, uint32_t src, int c0, int c1, int c2) {
    asm volatile("cp.async.bulk.tensor.3d.global.shared::cta.bulk_group [%0, {%2, %3, %4}], [%1];"
                 ::"l"((uint64_t)map), "r"(src), "r"(c0), "r"(c1), "r"(c2) : "memory");
}
__device__ __forceinline__ void bulk_commit() { asm volatile("cp.async.bulk.commit_group;" ::: "memory"); }
__device__ __forceinline__ void bulk_wait0() { asm volatile("cp.async.bulk.wait_group 0;" ::: "memory"); }
__device__ __forceinline__ void bulk_wait_read0() { asm volatile("cp.async.bulk.wait_group.read 0;" ::: "memory"); }
__device__ __forceinline__ void fence_async_smem() { asm volatile("fence.proxy.async.shared::cta;" ::: "memory"); }
__device__ __forceinline__ void named_bar(int id, int n) { asm volatile("bar.sync %0, %1;" ::"r"(id), "r"(n) : "memory"); }
__device__ __forceinline__ void sts128(uint32_t addr, uint32_t a, uint32_t b, uint32_t c, uint32_t d) {
    asm volatile("st.shared.v4.b32 [%0], {%1, %2, %3, %4};" ::"r"(addr), "r"(a), "r"(b), "r"(c), "r"(d) : "memory");
}
__device__ __forceinline__ void prefetch_map(const CUtensorMap* m) {
    asm volatile("prefetch.tensormap [%0];" ::"l"((uint64_t)m) : "memory");
}
__device__ __forceinline__ void wgmma_fence() { asm volatile("wgmma.fence.sync.aligned;" ::: "memory"); }
__device__ __forceinline__ void wgmma_commit() { asm volatile("wgmma.commit_group.sync.aligned;" ::: "memory"); }
template <int N>
__device__ __forceinline__ void wgmma_wait() { asm volatile("wgmma.wait_group.sync.aligned %0;" ::"n"(N) : "memory"); }
template <int N>
__device__ __forceinline__ void fence_regs(float (&a)[N]) {
#pragma unroll
    for (int i = 0; i < N; ++i) asm volatile("" : "+f"(a[i])::"memory");
}
template <int N>
__device__ __forceinline__ void fence_regs(uint32_t (&a)[N]) {
#pragma unroll
    for (int i = 0; i < N; ++i) asm volatile("" : "+r"(a[i])::"memory");
}
#define R8(a, i) "+f"(a[i + 0]), "+f"(a[i + 1]), "+f"(a[i + 2]), "+f"(a[i + 3]), "+f"(a[i + 4]), "+f"(a[i + 5]), "+f"(a[i + 6]), "+f"(a[i + 7])
#define REGS32 "{%0, %1, %2, %3, %4, %5, %6, %7, %8, %9, %10, %11, %12, %13, %14, %15, %16, %17, %18, %19, %20, %21, %22, %23, %24, %25, %26, %27, %28, %29, %30, %31}"
#define REGS16 "{%0, %1, %2, %3, %4, %5, %6, %7, %8, %9, %10, %11, %12, %13, %14, %15}"

__host__ __device__ constexpr uint32_t desc_hi(uint32_t sbo, uint32_t mode) { return (sbo >> 4) | (mode << 30); }
__device__ __forceinline__ uint32_t desc_lo(uint32_t saddr, uint32_t lbo) { return ((saddr & 0x3FFFF) >> 4) | ((lbo >> 4) << 16); }
constexpr uint32_t HI128 = desc_hi(1024, 1), HI64 = desc_hi(512, 2);
#define W8(a, i) "=f"(a[i + 0]), "=f"(a[i + 1]), "=f"(a[i + 2]), "=f"(a[i + 3]), "=f"(a[i + 4]), "=f"(a[i + 5]), "=f"(a[i + 6]), "=f"(a[i + 7])
template <int TA, int TB, int ACC, uint32_t AHI, uint32_t BHI>
__device__ __forceinline__ void wgmma_n64_ss(float (&d)[32], uint32_t alo, uint32_t blo) {
#define N64_TEXT "{\n.reg .pred p;\n.reg .b64 da, db;\nsetp.ne.b32 p, %36, 0;\nmov.b64 da, {%32, %37};\nmov.b64 db, {%33, %38};\n" \
        "wgmma.mma_async.sync.aligned.m64n64k16.f32.bf16.bf16 " REGS32 ", da, db, p, 1, 1, %34, %35;\n}\n"
    if (ACC) asm volatile(N64_TEXT : R8(d, 0), R8(d, 8), R8(d, 16), R8(d, 24) : "r"(alo), "r"(blo), "n"(TA), "n"(TB), "n"(ACC), "n"(AHI), "n"(BHI));
    else asm volatile(N64_TEXT : W8(d, 0), W8(d, 8), W8(d, 16), W8(d, 24) : "r"(alo), "r"(blo), "n"(TA), "n"(TB), "n"(ACC), "n"(AHI), "n"(BHI));
}
template <int ACC, int SA>
__device__ __forceinline__ void wgmma_n32_tt(float (&d)[16], uint32_t alo, uint32_t blo) {
#define N32T_TEXT "{\n.reg .pred p;\n.reg .b64 da, db;\nsetp.ne.b32 p, %18, 0;\nmov.b64 da, {%16, %19};\nmov.b64 db, {%17, %20};\n" \
        "wgmma.mma_async.sync.aligned.m64n32k16.f32.bf16.bf16 " REGS16 ", da, db, p, %21, 1, 1, 1;\n}\n"
    if (ACC) asm volatile(N32T_TEXT : R8(d, 0), R8(d, 8) : "r"(alo), "r"(blo), "n"(ACC), "n"(HI64), "n"(HI128), "n"(SA));
    else asm volatile(N32T_TEXT : W8(d, 0), W8(d, 8) : "r"(alo), "r"(blo), "n"(ACC), "n"(HI64), "n"(HI128), "n"(SA));
}
__device__ __forceinline__ void wgmma_n16_rs(float (&d)[8], const uint32_t (&a)[4], uint32_t blo) {
    asm volatile("{\n.reg .pred p;\n.reg .b64 db;\nsetp.ne.b32 p, 0, 0;\nmov.b64 db, {%12, %13};\n"
        "wgmma.mma_async.sync.aligned.m64n16k16.f32.bf16.bf16 {%0, %1, %2, %3, %4, %5, %6, %7}, {%8, %9, %10, %11}, db, p, 1, 1, 0;\n}\n"
        : W8(d, 0) : "r"(a[0]), "r"(a[1]), "r"(a[2]), "r"(a[3]), "r"(blo), "n"(HI128));
}

__device__ __forceinline__ float bf16r(float x) { return __bfloat162float(__float2bfloat16_rn(x)); }
__device__ __forceinline__ uint32_t pack_bf16(float lo, float hi) {
    __nv_bfloat162 v = __floats2bfloat162_rn(lo, hi);
    return *reinterpret_cast<uint32_t*>(&v);
}
__device__ __forceinline__ __nv_bfloat162 as_bf2(uint32_t w) { return *reinterpret_cast<__nv_bfloat162*>(&w); }
__device__ __forceinline__ uint32_t as_u32(__nv_bfloat162 v) { return *reinterpret_cast<uint32_t*>(&v); }
__device__ __forceinline__ float bf_lo(uint32_t w) { return __uint_as_float(w << 16); }
__device__ __forceinline__ float bf_hi(uint32_t w) { return __uint_as_float(w & 0xFFFF0000u); }
__device__ __forceinline__ void ldsm_x4_t(uint32_t& r0, uint32_t& r1, uint32_t& r2, uint32_t& r3, uint32_t addr) {
    asm volatile("ldmatrix.sync.aligned.m8n8.x4.trans.shared.b16 {%0,%1,%2,%3}, [%4];"
                 : "=r"(r0), "=r"(r1), "=r"(r2), "=r"(r3) : "r"(addr) : "memory");
}
__device__ __forceinline__ void stsm_x4(uint32_t addr, uint32_t r0, uint32_t r1, uint32_t r2, uint32_t r3) {
    asm volatile("stmatrix.sync.aligned.m8n8.x4.shared.b16 [%0], {%1,%2,%3,%4};"
                 ::"r"(addr), "r"(r0), "r"(r1), "r"(r2), "r"(r3) : "memory");
}
__device__ __forceinline__ void stsm_x4_t(uint32_t addr, uint32_t r0, uint32_t r1, uint32_t r2, uint32_t r3) {
    asm volatile("stmatrix.sync.aligned.m8n8.x4.trans.shared.b16 [%0], {%1,%2,%3,%4};"
                 ::"r"(addr), "r"(r0), "r"(r1), "r"(r2), "r"(r3) : "memory");
}
__device__ __forceinline__ uint32_t lds32(uint32_t addr) {
    uint32_t v;
    asm volatile("ld.shared.b32 %0, [%1];" : "=r"(v) : "r"(addr));
    return v;
}

typedef CUresult (*EncodeFn)(CUtensorMap*, CUtensorMapDataType, cuuint32_t, void*, const cuuint64_t*, const cuuint64_t*,
                             const cuuint32_t*, const cuuint32_t*, CUtensorMapInterleave, CUtensorMapSwizzle,
                             CUtensorMapL2promotion, CUtensorMapFloatOOBfill);
EncodeFn get_encode() {
    static EncodeFn fn = nullptr;
    if (!fn) {
        void* p = nullptr;
        cudaDriverEntryPointQueryResult qres;
        cudaGetDriverEntryPoint("cuTensorMapEncodeTiled", &p, cudaEnableDefault, &qres);
        fn = (EncodeFn)p;
    }
    return fn;
}
}
namespace {
constexpr double c_pi = 3.14159265358979323846;
constexpr double c_cos256(int i) {
    i &= 255;
    if (i > 128) i = 256 - i;
    double sgn = 1.0;
    if (i > 64) { i = 128 - i; sgn = -1.0; }
    if (i == 64) return 0.0;
    double x = 2.0 * c_pi * i / 256.0, x2 = x * x, term = 1.0, sum = 1.0;
    for (int k = 1; k < 20; ++k) { term *= -x2 / ((2 * k - 1) * (2 * k)); sum += term; }
    return sgn * sum;
}
constexpr uint32_t c_bf16(double v) {
    if (v == 0.0) return 0u;
    uint32_t s = v < 0 ? 0x8000u : 0u;
    double a = v < 0 ? -v : v;
    int e = 0;
    while (a >= 2.0) { a *= 0.5; ++e; }
    while (a < 1.0) { a *= 2.0; --e; }
    int r = (int)(a * 128.0 + 0.5);
    if (r == 256) { r = 128; ++e; }
    return s | (uint32_t)((e + 127) << 7) | (uint32_t)(r - 128);
}
__host__ __device__ constexpr int conv_k1(int r) { return (r & 8) ? 63 - (((r >> 4) << 3) | (r & 7)) : (((r >> 4) << 3) | (r & 7)); }
struct ConvTab { uint32_t w[96 * 32]; };
constexpr ConvTab make_conv_tab() {
    ConvTab t{};
    uint32_t cs[256] = {};
    for (int i = 0; i < 256; ++i) cs[i] = c_bf16(c_cos256(i));
    for (int n = 0; n < 96; ++n)
        for (int c = 0; c < 64; ++c) {
            int a = 0;
            if (n < 32) {
                const int ro = (n >> 3) & 1, ri = n & 7, co = (c >> 3) & 1, ci = c & 7;
                a = n < 16 ? 8 * ci * (4 * ri + (c >> 4)) : 8 * ri * (4 * ci + (c >> 4));
                a += (ro == co) ? 0 : (ro == 0) ? 192 : 64;
            } else {
                const int r = n - 32, n1 = 2 * (c & 31) + (c >> 5);
                a = n1 * (2 * (((r >> 4) << 3) | (r & 7)) + 1) + ((r & 8) ? 64 : 0);
            }
            const int off = n * 128 + (((c >> 3) ^ (n & 7)) << 4) + (c & 7) * 2;
            t.w[off >> 2] |= cs[a & 255] << ((off & 2) * 8);
        }
    return t;
}
__device__ __align__(128) constexpr ConvTab g_conv_tab = make_conv_tab();

struct Twiddle { uint32_t r[8], i[8], n[8]; };
constexpr double c_cospi(double x) {
    double sgn = 1.0;
    if (x > 0.5) { x = 1.0 - x; sgn = -1.0; }
    const double y = c_pi * x, y2 = y * y;
    double term = 1.0, sum = 1.0;
    for (int k = 1; k < 12; ++k) { term *= -y2 / ((2 * k - 1) * (2 * k)); sum += term; }
    return sgn * sum;
}
struct TwTab { uint32_t w[3072]; };
constexpr TwTab make_tw_tab() {
    TwTab t{};
    for (int th = 0; th < 128; ++th)
        for (int q = 0; q < 8; ++q)
            for (int e = 0; e < 2; ++e) {
                const int k1 = conv_k1(16 * (th >> 5) + 8 * (q & 1) + ((th & 31) >> 2)), n2 = 8 * (q >> 1) + 2 * (th & 3) + e;
                const double x = (double)(n2 * (2 * k1 + 1)) / 4096.0;
                const double cs = c_cospi(x), sn = n2 == 0 ? 0.0 : c_cospi(x > 0.5 ? x - 0.5 : 0.5 - x);
                t.w[((q >> 2) * 128 + th) * 4 + (q & 3)] |= c_bf16(cs * 0.0625) << (16 * e);
                t.w[((2 + (q >> 2)) * 128 + th) * 4 + (q & 3)] |= c_bf16(-sn * 0.0625) << (16 * e);
                t.w[((4 + (q >> 2)) * 128 + th) * 4 + (q & 3)] |= c_bf16(sn * 0.0625) << (16 * e);
            }
    return t;
}
__device__ __align__(128) constexpr TwTab g_tw_tab = make_tw_tab();
__device__ __forceinline__ void load_twiddle(Twiddle& tw, const uint4* p) {
#pragma unroll
    for (int q = 0; q < 2; ++q) {
        const uint4 a = __ldg(p + q * 128);
        const uint4 b = __ldg(p + (2 + q) * 128);
        tw.r[4 * q] = a.x; tw.r[4 * q + 1] = a.y; tw.r[4 * q + 2] = a.z; tw.r[4 * q + 3] = a.w;
        const uint4 n = __ldg(p + (4 + q) * 128);
        tw.n[4 * q] = n.x; tw.n[4 * q + 1] = n.y; tw.n[4 * q + 2] = n.z; tw.n[4 * q + 3] = n.w;
        tw.i[4 * q] = b.x; tw.i[4 * q + 1] = b.y; tw.i[4 * q + 2] = b.z; tw.i[4 * q + 3] = b.w;
    }
}

__device__ __forceinline__ int fresh_tid() { int v; asm volatile("mov.u32 %0, %tid.x;" : "=r"(v)); return v; }
__device__ __forceinline__ uint32_t hmul(uint32_t a, uint32_t b) { return as_u32(__hmul2_rn(as_bf2(a), as_bf2(b))); }
__device__ __forceinline__ uint32_t hadd(uint32_t a, uint32_t b) { return as_u32(__hadd2_rn(as_bf2(a), as_bf2(b))); }
__device__ __forceinline__ uint32_t hsub(uint32_t a, uint32_t b) { return as_u32(__hsub2_rn(as_bf2(a), as_bf2(b))); }
__device__ __forceinline__ uint32_t hfma(uint32_t a, uint32_t b, uint32_t c) { return as_u32(__hfma2(as_bf2(a), as_bf2(b), as_bf2(c))); }

__device__ __forceinline__ void conv_dft8(float (&x)[4][8], const uint32_t (&f)[4][4], uint32_t blo) {
#pragma unroll
    for (int r = 0; r < 4; ++r) wgmma_n16_rs(x[r], f[r], blo + 2 * r);
}
template <class T, int N>
__device__ __forceinline__ void fence_regs4(T (&a)[4][N]) { fence_regs(a[0]); fence_regs(a[1]); fence_regs(a[2]); fence_regs(a[3]); }
__device__ __forceinline__ void conv_s1(float (&dE)[32], float (&dO)[32], uint32_t tlo, uint32_t ulo) {
    wgmma_n64_ss<0, 1, 0, HI128, HI64>(dE, tlo + 256, ulo);
    wgmma_n64_ss<0, 1, 0, HI128, HI64>(dO, tlo + 256 + 4, ulo + 128);
    wgmma_n64_ss<0, 1, 1, HI128, HI64>(dE, tlo + 256 + 2, ulo + 64);
    wgmma_n64_ss<0, 1, 1, HI128, HI64>(dO, tlo + 256 + 6, ulo + 192);
}
template <int S>
__device__ __forceinline__ void conv_t1(const float (&dE)[32], const float (&dO)[32], const Twiddle& tw, float dsk, uint32_t (&f)[4][4]) {
    uint32_t ar[8], ai[8], fs[8], fd[8];
#pragma unroll
    for (int j = 0; j < 4; ++j) {
        const int i = 16 * S + 4 * j;
        const uint32_t e0 = pack_bf16(i == 16 ? dE[i] + dsk : dE[i], dE[i + 1]), e1 = pack_bf16(dE[i + 2], dE[i + 3]);
        const uint32_t o0 = pack_bf16(dO[i], dO[i + 1]), o1 = pack_bf16(dO[i + 2], dO[i + 3]);
        ar[2 * j] = hadd(e0, o0); ai[2 * j] = hadd(e1, o1);
        ar[2 * j + 1] = hsub(e0, o0); ai[2 * j + 1] = hsub(o1, e1);
    }
#pragma unroll
    for (int q = 0; q < 4; ++q) {
        const uint32_t pr = hfma(ar[q], tw.r[q], hmul(ai[q], tw.n[q])), pi = hfma(ar[q], tw.i[q], hmul(ai[q], tw.r[q]));
        fs[q] = hfma(ar[4 + q], tw.r[4 + q], hfma(ai[4 + q], tw.n[4 + q], pr));
        fs[4 + q] = hfma(ar[4 + q], tw.i[4 + q], hfma(ai[4 + q], tw.r[4 + q], pi));
        fd[q] = hfma(pr, 0xC000C000u, fs[q]);
        fd[4 + q] = hfma(pi, 0xC000C000u, fs[4 + q]);
    }
#pragma unroll
    for (int h = 0; h < 2; ++h) {
        f[0][h] = hadd(fs[h], fs[2 + h]); f[0][2 + h] = hadd(fs[4 + h], fs[6 + h]);
        f[2][h] = hsub(fs[h], fs[2 + h]); f[2][2 + h] = hsub(fs[4 + h], fs[6 + h]);
        f[1][h] = hadd(fd[h], fd[6 + h]); f[1][2 + h] = hsub(fd[4 + h], fd[2 + h]);
        f[3][h] = hsub(fd[h], fd[6 + h]); f[3][2 + h] = hadd(fd[4 + h], fd[2 + h]);
    }
}
__device__ __forceinline__ void conv_prod(const float (&xu)[8], const float (&xk)[8], uint32_t (&f)[4]) {
#pragma unroll
    for (int h = 0; h < 2; ++h) {
        float pr[2], pi[2];
#pragma unroll
        for (int e = 0; e < 2; ++e) {
            const float ur = xu[2 * h + e], ui = xu[4 + 2 * h + e], kr = xk[2 * h + e], ki = xk[4 + 2 * h + e];
            pr[e] = fmaf(ur, kr, -ui * ki);
            pi[e] = fmaf(-ur, ki, -ui * kr);
        }
        f[h] = pack_bf16(pr[0], pr[1]);
        f[2 + h] = pack_bf16(pi[0], pi[1]);
    }
}
template <bool SECOND, class G>
__device__ __forceinline__ void conv_channel(float (&dE)[32], float (&dO)[32], const Twiddle& tw, float dsk, uint32_t tlo, uint32_t nxt,
                                             uint32_t wre, uint32_t wim, int bar, G before_next) {
    float xu[4][8], xk[4][8];
    {
        uint32_t fu[4][4], fk[4][4];
        conv_t1<0>(dE, dO, tw, 0.f, fu);
        wgmma_fence();
        conv_dft8(xu, fu, tlo);
        wgmma_commit();
        conv_t1<1>(dE, dO, tw, dsk, fk);
        wgmma_fence();
        conv_dft8(xk, fk, tlo);
        wgmma_commit();
        before_next();
        wgmma_wait<0>();
        fence_regs4(xu); fence_regs4(xk);
        fence_regs4(fu); fence_regs4(fk);
    }
    uint32_t fp[4][4];
#pragma unroll
    for (int r = 0; r < 4; ++r) conv_prod(xu[r], xk[r], fp[r]);
    wgmma_fence();
    conv_dft8(xu, fp, tlo + 128);
    wgmma_commit();
    if (!SECOND || nxt) {
        if (SECOND) wgmma_fence();
        conv_s1(dE, dO, tlo, nxt);
        wgmma_commit();
        wgmma_wait<1>();
    } else {
        wgmma_wait<0>();
#pragma unroll
        for (int i = 0; i < 32; ++i) { dE[i] = 0.f; dO[i] = 0.f; }
        fence_regs(dE); fence_regs(dO);
    }
    fence_regs4(xu);
    fence_regs4(fp);
    uint32_t zr[8], zi[8], wr[8], wi[8];
#pragma unroll
    for (int h = 0; h < 2; ++h) {
        uint32_t yr[4], yi[4];
#pragma unroll
        for (int r = 0; r < 4; ++r) { yr[r] = pack_bf16(xu[r][2 * h], xu[r][2 * h + 1]); yi[r] = pack_bf16(xu[r][4 + 2 * h], xu[r][5 + 2 * h]); }
        const uint32_t u0r = hadd(yr[0], yr[2]), u0i = hadd(yi[0], yi[2]), u1r = hsub(yr[0], yr[2]), u1i = hsub(yi[0], yi[2]);
        const uint32_t v0r = hadd(yr[1], yr[3]), v0i = hadd(yi[1], yi[3]), v1r = hsub(yr[1], yr[3]), v1i = hsub(yi[1], yi[3]);
        zr[h] = hadd(u0r, v0r); zi[h] = hadd(u0i, v0i); zr[4 + h] = hsub(u0r, v0r); zi[4 + h] = hsub(u0i, v0i);
        zr[2 + h] = hadd(u1r, v1i); zi[2 + h] = hsub(u1i, v1r); zr[6 + h] = hsub(u1r, v1i); zi[6 + h] = hadd(u1i, v1r);
    }
#pragma unroll
    for (int q = 0; q < 8; ++q) {
        wr[q] = hfma(zr[q], tw.r[q], hmul(zi[q], tw.n[q]));
        wi[q] = hfma(zr[q], tw.i[q], hmul(zi[q], tw.r[q]));
    }
    if (SECOND) named_bar(bar, 128);
    stsm_x4(wre, hadd(wr[0], wr[1]), hadd(wr[2], wr[3]), hadd(wr[4], wr[5]), hadd(wr[6], wr[7]));
    stsm_x4(wre + 512, hsub(wi[1], wi[0]), hsub(wi[3], wi[2]), hsub(wi[5], wi[4]), hsub(wi[7], wi[6]));
    stsm_x4(wim, hsub(wr[1], wr[0]), hsub(wr[3], wr[2]), hsub(wr[5], wr[4]), hsub(wr[7], wr[6]));
    stsm_x4(wim + 512, hadd(wi[0], wi[1]), hadd(wi[2], wi[3]), hadd(wi[4], wi[5]), hadd(wi[6], wi[7]));
}
template <class G>
__device__ __forceinline__ void conv_pair(float (&dE)[32], float (&dO)[32], const Twiddle& tw, uint32_t dd, uint32_t tlo, uint32_t u0, uint32_t un,
                                          uint32_t lo, int BAR, G before_next) {
    conv_channel<false>(dE, dO, tw, bf_lo(dd), tlo, desc_lo(u0 + 4096, 8192), u0 + lo, u0 + 8192 + lo, BAR, []() {});
    wgmma_wait<0>();
    fence_regs(dE); fence_regs(dO);
    conv_channel<true>(dE, dO, tw, bf_hi(dd), tlo, un == u0 ? 0 : desc_lo(un, 8192), u0 + 4096 + lo, u0 + 12288 + lo, BAR, before_next);
    fence_async_smem();
    named_bar(BAR, 128);
    float ye[16], yo[16];
    wgmma_fence();
    const uint32_t wlo = desc_lo(u0, 4096);
    wgmma_n32_tt<0, 1>(ye, wlo, tlo + 256);
    wgmma_n32_tt<0, -1>(yo, wlo + 512, tlo + 256 + 4);
#pragma unroll
    for (int k = 1; k < 4; ++k) {
        wgmma_n32_tt<1, 1>(ye, wlo + 64 * k, tlo + 256 + 128 * k);
        wgmma_n32_tt<1, -1>(yo, wlo + 512 + 64 * k, tlo + 256 + 4 + 128 * k);
    }
    wgmma_commit();
    wgmma_wait<0>();
    fence_regs(ye); fence_regs(yo);
    fence_regs(dE); fence_regs(dO);
    named_bar(BAR, 128);
    const int t = fresh_tid();
    const uint32_t ya = u0 + (t & 64) * 64 + (t & 31) * 64 + (((((t >> 4) & 2) ^ (t >> 1)) & 3) << 4);
#pragma unroll
    for (int h = 0; h < 2; ++h) {
        stsm_x4_t(ya ^ (16 * h), pack_bf16(ye[2 * h], ye[2 * h + 1]), pack_bf16(ye[4 + 2 * h], ye[5 + 2 * h]),
                  pack_bf16(ye[8 + 2 * h], ye[9 + 2 * h]), pack_bf16(ye[12 + 2 * h], ye[13 + 2 * h]));
        stsm_x4_t((ya ^ (16 * h)) + 2048, pack_bf16(yo[2 * h], yo[2 * h + 1]), pack_bf16(yo[4 + 2 * h], yo[5 + 2 * h]),
                  pack_bf16(yo[8 + 2 * h], yo[9 + 2 * h]), pack_bf16(yo[12 + 2 * h], yo[13 + 2 * h]));
    }
    fence_async_smem();
    __syncwarp();
}
}

namespace {

constexpr int S_LEN = 2048;
constexpr int D_DIM = 1024;

#define REG_P 24
#define REG_AB 168
#define REG_C 152
#define QD 3
#define QKB 18
#define QD2 6
#define ALTMAP 0
#define EPF 2
#define LORD 1
#define SKEW1 4
#define TK_PF0 0
#define GAP_PF 300
#define TK_KV0 2
#define TK_KV1 4
#define GAP_KV 50
#define GAP_ST 50
#define GAP_HB 100
#define PFD 7
#define GAP_Y 100
#define GAP_X 100
#define SLOT4 20
#define SKEW2 4
#define GAP_CV 100
#define TK_C 8

__device__ __align__(1024) __nv_bfloat16 g_H[2 * D_DIM * S_LEN];
__device__ __align__(1024) __nv_bfloat16 g_y2[D_DIM * S_LEN];
__device__ __align__(1024) __nv_bfloat16 g_kvT[D_DIM * S_LEN];
__device__ __align__(128) float g_gate[S_LEN];
__device__ __align__(128) unsigned long long g_agg[8 * D_DIM];
__device__ __align__(128) unsigned int g_cnt[56 * 32];

#define STAMP(k, s) do { } while (0)
#define SAMPLE(i) do { } while (0)

__device__ __forceinline__ void tma_store_5d(const CUtensorMap* map, uint32_t src, int c0, int c1, int c2, int c3, int c4) {
    asm volatile("cp.async.bulk.tensor.5d.global.shared::cta.bulk_group [%0, {%2, %3, %4, %5, %6}], [%1];"
                 ::"l"((uint64_t)map), "r"(src), "r"(c0), "r"(c1), "r"(c2), "r"(c3), "r"(c4) : "memory");
}
#define ELECT "{\n.reg .pred p;\nelect.sync _|p, 0xffffffff;\n@p "
__device__ __forceinline__ void e_expect_tx(uint32_t bar, uint32_t bytes) {
    asm volatile(ELECT "mbarrier.arrive.expect_tx.shared::cta.b64 _, [%0], %1;\n}" ::"r"(bar), "r"(bytes) : "memory");
}
__device__ __forceinline__ void e_arrive(uint32_t bar) {
    asm volatile(ELECT "mbarrier.arrive.shared::cta.b64 _, [%0];\n}" ::"r"(bar) : "memory");
}
__device__ __forceinline__ void e_load_4d(uint32_t dst, const CUtensorMap* map, uint32_t bar, int c0, int c1, int c2, int c3) {
    asm volatile(ELECT "cp.async.bulk.tensor.4d.shared::cluster.global.mbarrier::complete_tx::bytes [%0], [%1, {%3, %4, %5, %6}], [%2];\n}"
        ::"r"(dst), "l"((uint64_t)map), "r"(bar), "r"(c0), "r"(c1), "r"(c2), "r"(c3) : "memory");
}
__device__ __forceinline__ void e_load_5d(uint32_t dst, const CUtensorMap* map, uint32_t bar, int c0, int c1, int c2, int c3, int c4) {
    asm volatile(ELECT "cp.async.bulk.tensor.5d.shared::cluster.global.mbarrier::complete_tx::bytes [%0], [%1, {%3, %4, %5, %6, %7}], [%2];\n}"
        ::"r"(dst), "l"((uint64_t)map), "r"(bar), "r"(c0), "r"(c1), "r"(c2), "r"(c3), "r"(c4) : "memory");
}
__device__ __forceinline__ void e_bulk_load(uint32_t dst, const void* src, uint32_t bytes, uint32_t bar) {
    asm volatile(ELECT "cp.async.bulk.shared::cluster.global.mbarrier::complete_tx::bytes [%0], [%1], %2, [%3];\n}"
                 ::"r"(dst), "l"(src), "r"(bytes), "r"(bar) : "memory");
}
__device__ __forceinline__ void l2_prefetch(const void* p, uint32_t bytes) {
    asm volatile("cp.async.bulk.prefetch.L2.global [%0], %1;" ::"l"(p), "r"(bytes) : "memory");
}
__device__ __forceinline__ void l2_prefetch_4d(const CUtensorMap* map, int c0, int c1, int c2, int c3) {
    asm volatile("cp.async.bulk.prefetch.tensor.4d.L2.global [%0, {%1, %2, %3, %4}];" ::"l"((uint64_t)map), "r"(c0), "r"(c1), "r"(c2), "r"(c3) : "memory");
}
__device__ __forceinline__ void l2_prefetch_5d(const CUtensorMap* map, int c0, int c1, int c2, int c3, int c4) {
    asm volatile("cp.async.bulk.prefetch.tensor.5d.L2.global [%0, {%1, %2, %3, %4, %5}];" ::"l"((uint64_t)map), "r"(c0), "r"(c1), "r"(c2), "r"(c3), "r"(c4) : "memory");
}
__device__ __forceinline__ unsigned int ld_relaxed(const unsigned int* p) {
    unsigned int v;
    asm volatile("ld.relaxed.gpu.global.u32 %0, [%1];" : "=r"(v) : "l"(p) : "memory");
    return v;
}
__device__ __forceinline__ void fence_async_global() { asm volatile("fence.proxy.async.global;" ::: "memory"); }
__device__ __forceinline__ void wait_counter(const unsigned int* p, unsigned int target) {
    unsigned int v;
    int it = 0;
    do { asm volatile("ld.acquire.gpu.global.u32 %0, [%1];" : "=r"(v) : "l"(p) : "memory"); } while (v != target && ++it < (1 << 22));
    fence_async_global();
}
__device__ __forceinline__ void red_release(unsigned int* p, unsigned int n) {
    asm volatile("red.release.gpu.global.add.u32 [%0], %1;" ::"l"(p), "r"(n) : "memory");
}
__device__ __forceinline__ uint4 ldg128(const void* p) {
    uint4 v;
    asm volatile("ld.global.nc.v4.u32 {%0,%1,%2,%3}, [%4];" : "=r"(v.x), "=r"(v.y), "=r"(v.z), "=r"(v.w) : "l"(p));
    return v;
}
__device__ __forceinline__ void stg128(void* p, uint32_t a, uint32_t b, uint32_t c, uint32_t d) {
    asm volatile("st.global.v4.b32 [%0], {%1, %2, %3, %4};" ::"l"(p), "r"(a), "r"(b), "r"(c), "r"(d) : "memory");
}

template <int TA>
__device__ __forceinline__ void wgmma_n128(float (&d)[64], uint32_t alo, uint32_t blo, int acc) {
    asm volatile(
        "{\n.reg .pred p;\n.reg .b64 da, db;\nsetp.ne.b32 p, %67, 0;\nmov.b64 da, {%64, %69};\nmov.b64 db, {%65, %66};\n"
        "wgmma.mma_async.sync.aligned.m64n128k16.f32.bf16.bf16 "
        "{%0, %1, %2, %3, %4, %5, %6, %7, %8, %9, %10, %11, %12, %13, %14, %15, "
        "%16, %17, %18, %19, %20, %21, %22, %23, %24, %25, %26, %27, %28, %29, %30, %31, "
        "%32, %33, %34, %35, %36, %37, %38, %39, %40, %41, %42, %43, %44, %45, %46, %47, "
        "%48, %49, %50, %51, %52, %53, %54, %55, %56, %57, %58, %59, %60, %61, %62, %63}, "
        "da, db, p, 1, 1, %68, 0;\n"
        "}\n"
        : R8(d, 0), R8(d, 8), R8(d, 16), R8(d, 24), R8(d, 32), R8(d, 40), R8(d, 48), R8(d, 56)
        : "r"(alo), "r"(blo), "n"(HI128), "r"(acc), "n"(TA), "n"(TA ? HI64 : HI128));
}

constexpr int NST = 5;
constexpr int XTRA = SKEW1 - 4;
static_assert(SKEW1 >= 4 && SKEW1 <= 12, "skew");
constexpr int OFF_BB = 4 * 32768;
constexpr int OFF_CT = 5 * 32768;
constexpr int OFF_CU = OFF_CT + 32768;
__host__ __device__ constexpr uint32_t conv_buf(int p) { return OFF_CT + 16384 + (p == 3 ? 0 : p) * 16384; }
constexpr int OFF_PAR = OFF_CU + 32768;
constexpr int OFF_BAR = OFF_PAR + 2048;
constexpr int SMEM_BYTES = OFF_BAR + 896;
static_assert(SMEM_BYTES <= 232448, "smem layout");

static_assert(SLOT4 % 4 == 0 && SLOT4 <= 24, "ring");
constexpr uint32_t PH4 = (SLOT4 / 4 - 1) & 1;
__host__ __device__ constexpr int ring_slot(int kb) { return (kb - SLOT4 + 4) % 5; }
__host__ __device__ constexpr uint32_t ring_par(int kb) { return ((SLOT4 / 4 - 1 + (kb - SLOT4 + 4) / 5) & 1) ^ (ring_slot(kb) == 4 ? PH4 : 0); }

struct Maps {
    CUtensorMap x5, b4, cre, cim, sk, yt, yt3, out, kvst, bre, bim;
};

__device__ __forceinline__ void cmul(float& r, float& i, float ar, float ai, float br, float bi) {
    const float a = ar * br - ai * bi, b = ar * bi + ai * br;
    r = a; i = b;
}
__device__ __forceinline__ void csqr(float& r, float& i) { const float a = r * r - i * i, b = 2.f * r * i; r = a; i = b; }
__device__ __forceinline__ float after(float v, float dep) { return __float_as_uint(dep) == 0x7fedcba9u ? dep : v; }

template <int BMODE>
__global__ void __launch_bounds__(512, 1)
fused_kernel(const __nv_bfloat16* __restrict__ x, const __nv_bfloat16* __restrict__ b_re, const __nv_bfloat16* __restrict__ b_im,
             const __nv_bfloat16* __restrict__ kin, const __nv_bfloat16* __restrict__ vin, const __nv_bfloat16* __restrict__ ssm_k,
             const __nv_bfloat16* __restrict__ shift_k, const __nv_bfloat16* __restrict__ ssm_D,
             const __nv_bfloat16* __restrict__ lam_re, const __nv_bfloat16* __restrict__ lam_im,
             const __nv_bfloat16* __restrict__ log_dt, const __nv_bfloat16* __restrict__ gate_w,
             const __nv_bfloat16* __restrict__ dskip,
             const __nv_bfloat16* __restrict__ c_re, const __nv_bfloat16* __restrict__ c_im,
             const __grid_constant__ Maps maps) {
    constexpr bool MERGED = BMODE != 0, SW = BMODE == 2;
    extern __shared__ __align__(1024) unsigned char smem_raw[];
    const uint32_t sbase = smem_u32(smem_raw);
    const uint32_t bar_full = sbase + OFF_BAR;
    const uint32_t bar_empty = bar_full + 32;
    const uint32_t bar_full2 = bar_empty + 32;
    const uint32_t bar_empty2 = bar_full2 + 40;
    const uint32_t bar_k = bar_empty2 + 40;
    const uint32_t bar_tab = bar_k + 32;
    const uint32_t bar_ab = bar_tab + 8;
    const uint32_t bar_adone = bar_ab + 8;
    const uint32_t bar_par = bar_adone + 8;
    const uint32_t bar_y = bar_par + 8;
    const uint32_t bar_rel = bar_y + 8;
    const uint32_t bar_kvrel = bar_rel + 8;
    const uint32_t bar_yrel = bar_kvrel + 8;
    const uint32_t bar_y1 = bar_yrel + 8;
    const uint32_t bar_fh = bar_y1 + 8;
    const uint32_t bar_tick = bar_fh + 24;
    const uint32_t bar_stg = bar_tick + 104;
    const uint32_t bar_bias = bar_stg + 112;
    const uint32_t bar_hw = bar_bias + 16;
    const uint32_t bar_gate = bar_hw + 32;
    const uint32_t bar_g2 = bar_hw;
    const uint32_t w_bid = bar_full + 600, w_dsk = bar_full + 608, w_ones = bar_full + 640;
    const int tid = threadIdx.x ^ (((threadIdx.x + 128) & 256) ? 0 : 384);
    if (tid == 384) { prefetch_map(&maps.x5); prefetch_map(&maps.b4); }
    if (EPF && (threadIdx.x >> 5) - 1u < EPF && blockIdx.x < 128) {
        const int ln = threadIdx.x & 31;
        const __nv_bfloat16* p = ln < 16 ? x + (size_t)(blockIdx.x * 16 + ln) * D_DIM : ((ln & 8) ? b_im : b_re) + (size_t)(blockIdx.x * 8 + (ln & 7)) * D_DIM;
        asm volatile("prefetch.global.L2 [%0];" ::"l"(p + ((threadIdx.x >> 5) - 1) * 64) : "memory");
    }
    int bid;
    {
        unsigned int sm, nsm;
        asm volatile("mov.u32 %0, %smid;" : "=r"(sm));
        asm volatile("mov.u32 %0, %nsmid;" : "=r"(nsm));
        const int tpc = sm >> 1, q7 = ((tpc - 32) * 37) >> 8;
        const int gp = tpc < 32 ? tpc & 7 : tpc < 60 ? tpc - 31 - 7 * q7 : 0;
        const int ix = tpc < 32 ? tpc >> 3 : tpc < 60 ? q7 + 4 : ALTMAP ? (tpc - 56) ^ 2 : tpc - 58;
        bid = (ALTMAP ? tpc >= 64 : (tpc | 1) == 61) ? 128 : (4 * (gp >> 1) + (ix >> 1)) * 8 + 4 * (gp & 1) + 2 * (ix & 1) + (sm & 1);
        if (gridDim.x != 132 || nsm != 132) bid = blockIdx.x;
    }
    const int tt = bid >> 3, dt = bid & 7;
    const int ti = tt >> 1;
    const int cg = (dt >> 2) * 8 + (tt & 1) * 4 + (dt & 3);
    if (MERGED && threadIdx.x == 0 && bid < 128) {
        mbar_init(bar_full, 1);
        asm volatile("fence.mbarrier_init.release.cluster;" ::: "memory");
        mbar_expect_tx(bar_full, 49152);
        tma_load_4d(sbase + OFF_CU, &maps.b4, bar_full, 0, 0, 0, cg * 4);
        tma_load_5d(sbase + ((0 - XTRA) & 3) * 32768, &maps.x5, bar_full, 0, 0, 0, 0, ti);
        tma_load_4d(sbase + OFF_BB, &maps.b4, bar_full, 0, 0, 0, 64 + cg * 4);
    }
    __syncwarp();
    const int warp = __shfl_sync(0xffffffffu, tid >> 5, 0), wg = warp >> 2, lane = tid & 31;
    if (warp == 12 && bid < 128) {
        if (lane == 0) {
#pragma unroll
            for (int s = MERGED; s < 4; ++s) mbar_init(bar_full + 8 * s, 1);
            asm volatile("fence.mbarrier_init.release.cluster;" ::: "memory");
        }
        __syncwarp();
        asm volatile("bar.arrive 4, 512;" ::: "memory");
        if (MERGED) {
#pragma unroll 1
            for (int it = 1; it < 4; ++it) {
                e_expect_tx(bar_full + 8 * it, 49152);
                e_load_4d(sbase + OFF_CU + it * 8192, &maps.b4, bar_full + 8 * it, it * 64, 0, 0, cg * 4);
                e_load_5d(sbase + ((it - XTRA) & 3) * 32768, &maps.x5, bar_full + 8 * it, it * 64, 0, 0, 0, ti);
                e_load_4d(sbase + OFF_BB + it * 8192, &maps.b4, bar_full + 8 * it, it * 64, 0, 0, 64 + cg * 4);
            }
        }
    }
    if (bid >= 128) {
        if (tid == 0) {
            __nanosleep(2000);
            const unsigned int target = (ld_relaxed(&g_cnt[32 * 32]) & ~63u) + 64u;
            for (int i = 0; i < 8; ++i)
                for (int it = 0; ld_relaxed(&g_cnt[(40 + i) * 32]) != target && it < (1 << 12); ++it) __nanosleep(500);
        }
        return;
    }
    if (wg == 0) {
        asm volatile("setmaxnreg.dec.sync.aligned.u32 %0;" ::"n"(REG_P));
        if (tid == 32) {
            if (sbase & 1023) __trap();
#pragma unroll
            for (int s = 0; s < 4; ++s) mbar_init(bar_empty + 8 * s, 2);
#pragma unroll
            for (int s = 0; s < NST; ++s) { mbar_init(bar_full2 + 8 * s, 1); mbar_init(bar_empty2 + 8 * s, 1); }
            mbar_init(bar_k, 1); mbar_init(bar_k + 8, 1); mbar_init(bar_k + 16, 1); mbar_init(bar_k + 24, 1);
            mbar_init(bar_tab, 1);
            mbar_init(bar_ab, 1);
            mbar_init(bar_adone, 4);
            mbar_init(bar_par, 2);
            asm volatile("fence.mbarrier_init.release.cluster;" ::: "memory");
        } else if (tid == 64) {
#pragma unroll
            for (int s = 0; s < 21; ++s) mbar_init(bar_y + 8 * s, 1);
        } else if (tid == 96) {
#pragma unroll
            for (int s = 0; s < 11; ++s) mbar_init(bar_stg + 8 * s, 4);
        } else if (tid == 0) {
#pragma unroll
            for (int s = 11; s < 21; ++s) mbar_init(bar_stg + 8 * s, 4);
            asm volatile("st.shared.b32 [%0], %1;" ::"r"(w_bid), "r"(bid) : "memory");
        }
        __syncwarp();
        asm volatile("bar.sync 4, 512;" ::: "memory");
        if (warp == 0) {
#pragma unroll 1
            for (int it = MERGED ? 4 : 0; it < 16 + XTRA; ++it) {
                const int st = it & 3, kb = it < 16 ? it : it - SKEW1;
                const bool fa = it < 16, fb = it < 16 - SKEW1 || it >= 12;
                const uint32_t bf = bar_full + 8 * st;
                mbar_wait(bar_empty + 8 * st, ((it >> 2) & 1) ^ 1);
                e_expect_tx(bf, fa && fb ? 49152 : 40960);
                e_load_5d(sbase + ((it - XTRA) & 3) * 32768, &maps.x5, bf, kb * 64, 0, 0, 0, ti);
                if (MERGED) {
                    if (fa) e_load_4d(sbase + OFF_CU + st * 8192, &maps.b4, bf, kb * 64, 0, 0, cg * 4);
                    if (fb) e_load_4d(sbase + OFF_BB + st * 8192, &maps.b4, bf, kb * 64, 0, 0, 64 + cg * 4);
                } else {
                    if (lane < 16 && ((lane & 8) ? fb : fa))
                        tma_load_2d(sbase + ((lane & 8) ? OFF_BB : OFF_CU) + st * 8192 + (lane & 7) * 1024, (lane & 1) ? &maps.bim : &maps.bre, bf,
                                    kb * 64, (lane >> 3) * 512 + cg * 32 + ((lane & 7) >> 1) * 8);
                    __syncwarp();
                }
                if (it >= 4 && it < 16) e_arrive(bar_tick + 8 * (it - 3));
                if (lane == 0) STAMP(1, 16 + it);
                if (lane == 0 && it < 16) SAMPLE(it - 3);
            }
            int st = 0;
            uint32_t ph = 0;
#pragma unroll 1
            for (int kb = 0; kb < 32; ++kb) {
                const uint32_t bf = bar_full2 + 8 * st;
                mbar_wait(bar_empty2 + 8 * st, st == 4 ? ph ^ PH4 : ph);
                e_expect_tx(bf, 32768);
                e_load_5d(sbase + st * 32768 + 16384, &maps.cre + ((kb >> 3) & 1), bf, ((kb >> 4) * 8 + (kb & 7)) * 64, 0, 0, 0, dt * 4);
                if (lane == 0) STAMP(2, 16 + kb);
                if (lane == 0 && (kb & 3) == 0) SAMPLE(13 + (kb >> 2));
                if (++st == (kb < SLOT4 - 1 ? 4 : 5)) { st = 0; ph ^= 1; }
            }
        } else if (warp == 1) {
            if (MERGED && PFD && lane == 0) {
#pragma unroll 1
                for (int n = 0; n + PFD < 16; ++n) {
                    mbar_wait(bar_tick + 8 * n, 0);
                    if (cg >= 4 && max(cg - PFD, 0) == n) l2_prefetch_5d(&maps.x5, cg * 64, 0, 0, 0, ti);
                    if (ti >= 2 && max(2 * ti - PFD, 0) == n) {
#pragma unroll 1
                        for (int i = 0; i < 4; ++i) l2_prefetch_4d(&maps.b4, (2 * ti + (i >> 1)) * 64, 0, 0, (i & 1) * 64 + cg * 4);
                    }
                }
            }
            __syncwarp();
            const char* hp = reinterpret_cast<const char*>(g_H) + (size_t)tt * 262144;
            mbar_wait(bar_adone, 0);
            e_expect_tx(bar_k + 8, 16384);
            e_expect_tx(bar_k + 16, 16384);
#pragma unroll 1
            for (int c = 2; c < 6; ++c) {
                e_load_4d(sbase + conv_buf(0) + (c >> 1) * 16384 + (c & 1) * 4096 + 8192, &maps.sk, bar_k + 8 * (c >> 1), 0, 0, 0, bid * 8 + c);
                if (GAP_CV) __nanosleep(GAP_CV);
            }
            mbar_wait(bar_kvrel, 0);
            const unsigned int target = lds32(w_bid + 4);
            mbar_wait(bar_rel, 0);
            int st = 0;
            uint32_t ph = 0;
#pragma unroll 1
            for (int q = 0; q < 4; ++q) {
                if (lane == 0) STAMP(0, 8 + 2 * q);
                if (q == 0) wait_counter(&g_cnt[(4 * ti) * 32], target);
                else { mbar_wait(bar_fh + 8 * q - 8, 0); fence_async_global(); }
                if (lane == 0) STAMP(0, 9 + 2 * q);
#pragma unroll 1
                for (int kb = 0; kb < 8; ++kb) {
                    mbar_wait(bar_empty2 + 8 * st, st == 4 ? ph ^ PH4 : ph);
                    e_bulk_load(sbase + st * 32768, hp + kb * 16384, 16384, bar_full2 + 8 * st);
                    if (++st == (8 * q + kb < SLOT4 - 1 ? 4 : 5)) { st = 0; ph ^= 1; }
                }
                hp += (q & 1) ? 4194304 - 131072 : 131072;
            }
        } else if (warp == 2) {
            if (lane == 0) {
                mbar_wait(bar_tick + 8, 0);
                const unsigned int target = (ld_relaxed(&g_cnt[(40 + dt) * 32]) & ~63u) + 64u;
                asm volatile("st.shared.b32 [%0], %1;" ::"r"(w_bid + 4), "r"(target) : "memory");
                prefetch_map(&maps.kvst); prefetch_map(&maps.sk);
#pragma unroll 1
                for (int bt = 0; bt < 2; ++bt) {
                    mbar_wait(bar_stg + 8 * bt, 0);
#pragma unroll 1
                    for (int i = 0; i < 4; ++i) {
                        if (i) __nanosleep(GAP_ST);
                        tma_store_3d(&maps.kvst, sbase + OFF_CT + bt * 16384 + i * 4096, (tt & 1) * 1024 + ti * 128 + 64 * bt, dt * 16, 2 * i);
                    }
                    bulk_commit();
                }
                bulk_wait0();
                fence_async_global();
                red_release(&g_cnt[(40 + dt) * 32], 4);
                mbar_arrive(bar_kvrel);
                STAMP(0, 23);
                mbar_expect_tx(bar_tab, 12288);
                bulk_load(sbase + OFF_CT, &g_conv_tab, 12288, bar_tab);
                mbar_expect_tx(bar_k, 16384);
                tma_load_4d(sbase + conv_buf(0) + 8192, &maps.sk, bar_k, 0, 0, 0, bid * 8);
                tma_load_4d(sbase + conv_buf(0) + 12288, &maps.sk, bar_k, 0, 0, 0, bid * 8 + 1);
                wait_counter(&g_cnt[(40 + (bid >> 4)) * 32], target);
                STAMP(0, 19);
#pragma unroll 1
                for (int p = 0; p < 3; ++p) {
                    if (p == 1) mbar_wait(bar_adone, 0);
                    bulk_load(sbase + conv_buf(p), g_kvT + (size_t)(bid * 8 + 2 * p) * 2048, 8192, bar_k + 8 * p);
                    if (GAP_CV) __nanosleep(GAP_CV);
                }
                prefetch_map(&maps.out); prefetch_map(&maps.yt); prefetch_map(&maps.yt3);
#pragma unroll 1
                for (int p = 0; p < 4; ++p) {
                    mbar_wait(bar_stg + 16 + 8 * p, 0);
                    if (p == 0) {
                        mbar_expect_tx(bar_k + 24, 16384);
                        tma_load_4d(sbase + conv_buf(3) + 8192, &maps.sk, bar_k + 24, 0, 0, 0, bid * 8 + 6);
                        mbar_wait(bar_g2, 0);
                        tma_load_4d(sbase + conv_buf(3) + 12288, &maps.sk, bar_k + 24, 0, 0, 0, bid * 8 + 7);
                    }
#pragma unroll 1
                    for (int i = 0; i < 2; ++i) {
                        if (i) __nanosleep(GAP_Y);
                        asm volatile("cp.async.bulk.global.shared::cta.bulk_group [%0], [%1], 4096;"
                                     ::"l"(g_y2 + (size_t)(bid * 8 + 2 * p + i) * 2048), "r"(sbase + conv_buf(p) + i * 4096) : "memory");
                    }
                    bulk_commit();
                    STAMP(0, 24 + p);
                    if (p == 0) {
                        bulk_wait_read0();
                        bulk_load(sbase + conv_buf(3), g_kvT + (size_t)(bid * 8 + 6) * 2048, 8192, bar_k + 24);
                    }
                    if (p == 2) {
                        bulk_wait0();
                        fence_async_global();
                        red_release(&g_cnt[(48 + (bid >> 4)) * 32], 4);
                        mbar_arrive(bar_yrel);
                        STAMP(0, 3);
                    }
                }
                bulk_wait0();
                fence_async_global();
                red_release(&g_cnt[(32 + (bid >> 4)) * 32], 4);
                STAMP(0, 2);
                wait_counter(&g_cnt[(32 + dt) * 32], target);
                STAMP(0, 5);
                mbar_expect_tx(bar_y, 8192);
#pragma unroll 1
                for (int i = 6; i < 8; ++i)
                    tma_load_5d(sbase + OFF_CU + i * 4096, &maps.yt, bar_y, (tt & 1) * 1024 + ti * 128 + (i & 1) * 64, 0, 0, i >> 1, dt * 4);
#pragma unroll 1
                for (int i = 0; i < 8; ++i) {
                    mbar_wait(bar_stg + 48 + 8 * i, 0);
                    tma_store_5d(&maps.out, sbase + ((i & 4) ? OFF_CT : OFF_CU) + (i & 3) * 8192, dt * 128 + (i & 3) * 32, 0, 0, (tt & 1) * 4 + ((i & 4) >> 1), ti);
                    bulk_commit();
                }
                bulk_wait_read0();
                STAMP(2, 3);
                SAMPLE(21);
            }
        } else if (lane == 0) {
            mbar_wait(bar_tick + 8 * TK_PF0, 0);
#pragma unroll 1
            for (int i = 0; i < 8; ++i) {
                l2_prefetch(((i & 1) ? vin : kin) + (size_t)(ti * 256 + 32 * (i & 4) + (bid & 15) * 8 + 2 * (i & 2)) * D_DIM, 8192);
                __nanosleep(GAP_PF);
            }
            if (bid < 3) l2_prefetch(reinterpret_cast<const char*>(&g_conv_tab) + bid * 4096, 4096);
            prefetch_map(&maps.cre); prefetch_map(&maps.cim);
            mbar_wait(bar_tick + 8 * TK_C, 0);
#pragma unroll 1
            for (int i = 0; i < 8; ++i) {
                l2_prefetch((i & 1) ? ((i & 4) ? c_im : c_re) + (size_t)bid * 8192 + (i & 2) * 2048 : ssm_k + (size_t)bid * 16384 + (i >> 1) * 4096, 8192);
                __nanosleep(GAP_PF);
            }
            const unsigned int target = (ld_relaxed(&g_cnt[(4 * ti + 1) * 32]) & ~63u) + 64u;
            mbar_wait(bar_gate, 0);
#pragma unroll 1
            for (int q = 1; q < 4; ++q) {
                if (q < 3) mbar_wait(bar_hw + 8 * q, 0);
                if (q > 1) {
                    mbar_wait(bar_g2, 0);
                    char* hp = reinterpret_cast<char*>(g_H) + (size_t)((16 + 2 * ti) * 16 + (q & 1) * 8 + (cg >> 1)) * 16384 + (cg & 1) * 2048;
#pragma unroll 1
                    for (int i = 0; i < 8; ++i) {
                        asm volatile("cp.async.bulk.global.shared::cta.bulk_group [%0], [%1], 2048;"
                                     ::"l"(hp + (i & 3) * 4096 + (i >> 2) * 262144), "r"(sbase + OFF_BB + (q & 1) * 16384 + i * 2048) : "memory");
                        __nanosleep(GAP_HB);
                    }
                    bulk_commit();
                    wait_counter(&g_cnt[(4 * ti + q - 1) * 32], target);
                    mbar_arrive(bar_fh + 8 * q - 16);
                    bulk_wait0();
                    if (q == 3) mbar_arrive(bar_empty2 + 32);
                    fence_async_global();
                }
                red_release(&g_cnt[(4 * ti + q) * 32], 4);
                STAMP(0, 36 + q);
                if (q == 3) {
                    wait_counter(&g_cnt[(4 * ti + q) * 32], target);
                    mbar_arrive(bar_fh + 8 * q - 8);
                }
            }
        }
    } else {
    if (wg == 3) {
        if (warp != 12) asm volatile("bar.sync 4, 512;" ::: "memory");
        named_bar(3, 128);
        asm volatile("setmaxnreg.inc.sync.aligned.u32 %0;" ::"n"(REG_C));
        const int t = tid & 127, w4 = t >> 5;
        if (t == 0) SAMPLE(0);
        mbar_wait(bar_tick, 0);
        if (t < 64) {
            const int ch = (t >> 5) * 512 + cg * 32 + (t & 31);
            unsigned long long oldagg;
            asm volatile("ld.relaxed.gpu.global.u64 %0, [%1];" : "=l"(oldagg) : "l"(&g_agg[ti * D_DIM + ch]) : "memory");
            const float Lr = __bfloat162float(lam_re[ch]), Li = __bfloat162float(lam_im[ch]);
            const float dtv = bf16r(expf(__bfloat162float(log_dt[ch])));
            const unsigned int tag = ((((unsigned int)oldagg & 1u) | ((unsigned int)(oldagg >> 31) & 2u)) + 1u) & 3u;
            const float er = expf(dtv * Lr);
            float s, c;
            sincospif(dtv * Li * 0.318309886183790672f, &s, &c);
            const float lr = er * c, li = er * s;
            const float nr = lr - 1.f, ni = li;
            const float den = Lr * Lr + Li * Li;
            const float cr = 2.f * (nr * Lr + ni * Li) / den, ci = 2.f * (ni * Lr - nr * Li) / den;
            float pr = lr, pi = -li;
#pragma unroll
            for (int i = 0; i < 5; ++i) csqr(pr, pi);
            sts128(sbase + OFF_PAR + t * 32, __float_as_uint(lr), __float_as_uint(-li), __float_as_uint(cr), __float_as_uint(ci));
            sts128(sbase + OFF_PAR + t * 32 + 16, __float_as_uint(pr), __float_as_uint(pi), tag, 0);
            __syncwarp();
            if (lane == 0) mbar_arrive(bar_par);
        }
        if (t >= 120) asm volatile("st.shared.b32 [%0], %1;" ::"r"(w_dsk - 480 + 4 * t),
                                   "r"(t < 124 ? __ldg(reinterpret_cast<const uint32_t*>(ssm_D + bid * 8) + (t & 3)) : 0u) : "memory");
        if (t < 64) asm volatile("st.shared.b32 [%0], %1;" ::"r"(w_ones + 4 * t), "r"(0x3F803F80u) : "memory");
        {
            const int cq = lane & 15, rg = (lane >> 4) + 2 * w4;
            uint32_t sk[4][4];
#pragma unroll
            for (int c = 0; c < 4; ++c) {
                const uint4 w = ldg128(shift_k + (size_t)(dt * 128 + 8 * cq + 2 * c) * 4);
                sk[0][c] = __byte_perm(w.x, w.z, 0x5410); sk[1][c] = __byte_perm(w.x, w.z, 0x7632);
                sk[2][c] = __byte_perm(w.y, w.w, 0x5410); sk[3][c] = __byte_perm(w.y, w.w, 0x7632);
            }
#pragma unroll 1
            for (int bt = 0; bt < 2; ++bt) {
                const int t0 = ti * 256 + 128 * bt + 16 * (rg & 4) + 32 * (tt & 1) + 8 * (rg & 3);
                mbar_wait(bar_tick + 8 * (bt ? TK_KV1 : TK_KV0), 0);
                if (t == 0) STAMP(0, 30 + 3 * bt);
                uint4 kk[11], vv[8];
                const __nv_bfloat16* kp = kin + (size_t)t0 * D_DIM + dt * 128 + 8 * cq;
                const __nv_bfloat16* vp = vin + (size_t)t0 * D_DIM + dt * 128 + 8 * cq;
#pragma unroll
                for (int i = 0; i < 11; ++i) {
                    if (i < 3 && t0 == 0) kk[i] = make_uint4(0, 0, 0, 0);
                    else kk[i] = ldg128(kp + (i - 3) * D_DIM);
                    if (i == 6 || i == 10) __nanosleep(GAP_KV);
                }
#pragma unroll
                for (int i = 0; i < 8; ++i) { vv[i] = ldg128(vp + i * D_DIM); if (i == 3) __nanosleep(GAP_KV); }
                const uint32_t ua = sbase + OFF_CT + bt * 16384 + cq * 128 + ((rg ^ ((2 * ti + bt) & 3) ^ (cq & 7)) << 4);
#pragma unroll
                for (int c = 0; c < 4; ++c) {
                    uint32_t res[8];
#pragma unroll
                    for (int i = 0; i < 8; ++i) {
                        uint32_t ks = hmul((&kk[i].x)[c], sk[3][c]);
                        ks = hadd(ks, hmul((&kk[i + 1].x)[c], sk[2][c]));
                        ks = hadd(ks, hmul((&kk[i + 2].x)[c], sk[1][c]));
                        ks = hadd(ks, hmul((&kk[i + 3].x)[c], sk[0][c]));
                        res[i] = hmul(ks, (&vv[i].x)[c]);
                    }
                    sts128(ua + (2 * c) * 2048, __byte_perm(res[0], res[1], 0x5410), __byte_perm(res[2], res[3], 0x5410),
                           __byte_perm(res[4], res[5], 0x5410), __byte_perm(res[6], res[7], 0x5410));
                    sts128(ua + (2 * c + 1) * 2048, __byte_perm(res[0], res[1], 0x7632), __byte_perm(res[2], res[3], 0x7632),
                           __byte_perm(res[4], res[5], 0x7632), __byte_perm(res[6], res[7], 0x7632));
                }
                fence_async_smem();
                __syncwarp();
                if (lane == 0) mbar_arrive(bar_stg + 8 * bt);
                if (t == 0) STAMP(0, 21 + bt);
            }
        }
        {
            const int row = bid * 16 + (t >> 3);
            uint4 xv[16];
#pragma unroll
            for (int n = 0; n < 16; ++n) {
                xv[n] = ldg128(x + (size_t)row * D_DIM + ((t & 7) + 8 * n) * 8);
                if ((n & 3) == 3) __nanosleep(GAP_KV);
            }
#pragma unroll
            for (int n8 = 0; n8 < 16; n8 += 8) {
                uint4 wv[8];
#pragma unroll
                for (int n = 0; n < 8; ++n) wv[n] = ldg128(gate_w + ((t & 7) + 8 * (n8 + n)) * 8);
#pragma unroll
                for (int n = 0; n < 8; ++n) {
                    uint4& p = xv[n8 + n];
                    p.x = hmul(p.x, wv[n].x); p.y = hmul(p.y, wv[n].y); p.z = hmul(p.z, wv[n].z); p.w = hmul(p.w, wv[n].w);
                }
            }
            float d[4] = {0.f, 0.f, 0.f, 0.f};
            fence_regs(d);
            named_bar(3, 128);
            wgmma_fence();
#pragma unroll
            for (int n = 0; n < 16; ++n)
                asm volatile("{\n.reg .b64 db;\nmov.b64 db, {%8, 8};\n"
                             "wgmma.mma_async.sync.aligned.m64n8k16.f32.bf16.bf16 {%0, %1, %2, %3}, {%4, %5, %6, %7}, db, 1, 1, 1, 0;\n}\n"
                             : "+f"(d[0]), "+f"(d[1]), "+f"(d[2]), "+f"(d[3]) : "r"(xv[n].x), "r"(xv[n].y), "r"(xv[n].z), "r"(xv[n].w), "r"(desc_lo(w_ones, 128)));
            wgmma_commit();
            wgmma_wait<0>();
            fence_regs(d);
#pragma unroll
            for (int n = 0; n < 16; ++n) asm volatile("" ::"r"(xv[n].x), "r"(xv[n].y), "r"(xv[n].z), "r"(xv[n].w) : "memory");
            float sum = d[0] + d[2];
            sum += __shfl_xor_sync(0xffffffffu, sum, 4);
            if ((t & 7) == 0) g_gate[row] = bf16r(1.f / (1.f + expf(-bf16r(sum))));
            if (t == 0) STAMP(0, 4);
            __syncwarp();
            if (lane == 0) mbar_arrive(bar_gate);
        }
    } else {
        asm volatile("setmaxnreg.inc.sync.aligned.u32 %0;" ::"n"(REG_AB));
        if (tid == 128) STAMP(1, 54);
        asm volatile("bar.sync 4, 512;" ::: "memory");
        if (tid == 128) STAMP(1, 55);
        const int cw = wg - 1;
        const int t = tid & 127, w4 = t >> 5, g = lane >> 2, t4 = lane & 3;
        {
            float a0[64], a1[64];
            auto release = [&](int it) {
                if (it < 12 + XTRA && t <= ((it >= 16 - SKEW1 && it < 12) || it >= 16)) mbar_arrive(bar_empty + 8 * (it & 3));
            };
#pragma unroll 1
            for (int kb = 0; kb < 16; ++kb) {
                const int it = cw == 1 && kb >= 16 - SKEW1 ? kb + XTRA : kb, st = it & 3;
                if (cw == 1 && kb == 16 - SKEW1) mbar_wait(bar_ab, 0);
                mbar_wait(bar_full + 8 * st, (it >> 2) & 1);
                if (kb == 0 && tid == 288) mbar_arrive(bar_tick);
                if (kb == 0 && t == 0) STAMP(1, 14 + cw);
                const uint32_t alo = desc_lo(sbase + (cw ? OFF_BB : OFF_CU) + st * 8192, 16), blo = desc_lo(sbase + ((it - XTRA) & 3) * 32768, 16);
                wgmma_fence();
#pragma unroll
                for (int k = 0; k < 4; ++k) {
                    wgmma_n128<0>(a0, alo + 2 * k, blo + 2 * k, k ? 1 : kb);
                    wgmma_n128<0>(a1, alo + 2 * k, blo + 1024 + 2 * k, k ? 1 : kb);
                }
                wgmma_commit();
                wgmma_wait<1>();
                if (kb > 0 && !(cw == 1 && kb == 16 - SKEW1)) release(it - 1);
                if (cw == 1 && kb == 15 - SKEW1) {
                    wgmma_wait<0>();
                    release(it);
                }
                if (cw == 1 && kb > 12) {
                    if (kb == 13) mbar_wait(bar_adone, 0);
                    if (t == 0) mbar_arrive(bar_empty2 + 8 * (kb - 13));
                }
            }
            if (tid == 192) mbar_arrive(bar_ab);
            float mr, mi, cr, ci, p32r, p32i;
            uint32_t tag;
            mbar_wait(bar_par, 0);
            {
                const uint32_t par = sbase + OFF_PAR + (cw * 32 + w4 * 8 + g) * 32;
                uint32_t dummy;
                asm volatile("ld.shared.v4.f32 {%0,%1,%2,%3}, [%4];" : "=f"(mr), "=f"(mi), "=f"(cr), "=f"(ci) : "r"(par));
                asm volatile("ld.shared.v4.b32 {%0,%1,%2,%3}, [%4];" : "=f"(p32r), "=f"(p32i), "=r"(tag), "=r"(dummy) : "r"(par + 16));
            }
            const float l1i = SW ? mi : -mi;
            auto map = [&](float p, float q, float& r, float& i) {
                if (SW) { r = fmaf(cr, q, -ci * p); i = fmaf(-cr, p, -ci * q); }
                else { r = fmaf(cr, p, -ci * q); i = fmaf(-cr, q, -ci * p); }
            };
            float p64r = p32r, p64i = p32i;
            csqr(p64r, p64i);
            float p128r = p64r, p128i = p64i;
            csqr(p128r, p128i);
            wgmma_wait<0>();
            fence_regs(a0); fence_regs(a1);
            if (cw == 0) { release(15); if (lane == 0) mbar_arrive(bar_adone); }
            else if (t == 0) mbar_arrive(bar_empty2 + 24);
            if (t == 0) STAMP(1, 2 + 6 * cw);
            float hr = 0.f, hi = 0.f, ar = 0.f, ai = 0.f;
#pragma unroll
            for (int j = 0; j < 16; ++j)
#pragma unroll
                for (int e = 0; e < 2; ++e) {
                    const float nr = fmaf(mr, ar, fmaf(-l1i, ai, a0[4 * j + e])), ni = fmaf(mr, ai, fmaf(l1i, ar, a0[4 * j + 2 + e]));
                    const float or_ = fmaf(mr, hr, fmaf(-l1i, hi, a1[4 * j + e])), oi = fmaf(mr, hi, fmaf(l1i, hr, a1[2 + 4 * j + e]));
                    ar = nr; ai = ni; hr = or_; hi = oi;
                }
            map(ar, ai, ar, ai);
            map(hr, hi, hr, hi);
            hr += p32r * ar - p32i * ai; hi += p32r * ai + p32i * ar;
            {
                float vr = __shfl_up_sync(0xffffffffu, hr, 1, 4), vi = __shfl_up_sync(0xffffffffu, hi, 1, 4);
                if (t4 >= 1) { hr += p64r * vr - p64i * vi; hi += p64r * vi + p64i * vr; }
                vr = __shfl_up_sync(0xffffffffu, hr, 2, 4); vi = __shfl_up_sync(0xffffffffu, hi, 2, 4);
                if (t4 >= 2) { hr += p128r * vr - p128i * vi; hi += p128r * vi + p128i * vr; }
            }
            unsigned long long* ap = &g_agg[ti * D_DIM + cw * 512 + cg * 32 + w4 * 8 + g];
            if (t4 == 3) asm volatile("{\n.reg .b64 a;\nmov.b64 a, {%1, %2};\nst.relaxed.gpu.global.u64 [%0], a;\n}\n" ::"l"(ap),
                                      "r"((__float_as_uint(hr) & ~1u) | (tag & 1u)), "r"((__float_as_uint(hi) & ~1u) | (tag >> 1)) : "memory");
            float exr = __shfl_up_sync(0xffffffffu, hr, 1, 4), exi = __shfl_up_sync(0xffffffffu, hi, 1, 4);
            if (t4 == 0) { exr = 0.f; exi = 0.f; }
            if (t == 0) STAMP(1, 3 + 6 * cw);
            ci = after(ci, exr);
#pragma unroll
            for (int j = 0; j < 16; ++j)
#pragma unroll
                for (int e = 0; e < 2; ++e) {
                    map(a0[4 * j + e], a0[4 * j + 2 + e], a0[4 * j + e], a0[4 * j + 2 + e]);
                    map(a1[4 * j + e], a1[4 * j + 2 + e], a1[4 * j + e], a1[4 * j + 2 + e]);
                }
            float qr = 1.f, qi = 0.f, ur = 1.f, ui = 0.f;
            if (t4 & 1) { qr = p64r; qi = p64i; }
            if (t4 & 2) cmul(qr, qi, qr, qi, p128r, p128i);
            csqr(p128r, p128i);
            if (t4 & 1) { ur = p128r; ui = p128i; }
            csqr(p128r, p128i);
            if (t4 & 2) cmul(ur, ui, ur, ui, p128r, p128i);
            csqr(p128r, p128i);
            fence_regs(a0); fence_regs(a1);
            if (t == 0) STAMP(1, 7 + 6 * cw);
            if (ti > 0) {
                const unsigned long long tmask = 0x0000000100000001ull, tval = ((unsigned long long)(tag >> 1) << 32) | (tag & 1u);
                unsigned long long u0 = tval, u1 = tval;
                ap -= D_DIM * (1 + t4);
                int it = 0;
                do {
                    asm volatile("{\n.reg .pred p, q;\nsetp.gt.s32 p, %3, 0;\nsetp.gt.s32 q, %3, 4;\n@p ld.relaxed.gpu.global.u64 %0, [%2];\n"
                                 "@q ld.relaxed.gpu.global.u64 %1, [%2+-32768];\n}\n" : "+l"(u0), "+l"(u1) : "l"(ap), "r"(ti - t4) : "memory");
                } while (__any_sync(0xffffffffu, (((u0 ^ tval) | (u1 ^ tval)) & tmask) != 0) && ++it < (1 << 22));
                float Pr = __uint_as_float((unsigned)u1 & ~1u), Pi = __uint_as_float((unsigned)(u1 >> 32) & ~1u);
                cmul(Pr, Pi, Pr, Pi, p128r, p128i);
                Pr += __uint_as_float((unsigned)u0 & ~1u); Pi += __uint_as_float((unsigned)(u0 >> 32) & ~1u);
                cmul(Pr, Pi, Pr, Pi, ur, ui);
                Pr += __shfl_xor_sync(0xffffffffu, Pr, 1); Pi += __shfl_xor_sync(0xffffffffu, Pi, 1);
                Pr += __shfl_xor_sync(0xffffffffu, Pr, 2); Pi += __shfl_xor_sync(0xffffffffu, Pi, 2);
                exr += qr * Pr - qi * Pi;
                exi += qr * Pi + qi * Pr;
            }
            if (t == 0) STAMP(1, 4 + 6 * cw);
            char* hp = reinterpret_cast<char*>(g_H) + (size_t)((2 * ti) * 16 + (cg >> 1)) * 16384 + ((cg & 1) * 32 + w4 * 8 + g) * 64 + ((t4 ^ (g >> 1)) << 4);
            float fxr = ar + p32r * exr - p32i * exi, fxi = ai + p32r * exi + p32i * exr;
            const uint32_t hs = sbase + OFF_BB + (w4 * 8 + g) * 64 + ((t4 ^ (g >> 1)) << 4);
            if (cw == 1) named_bar(2, 128);
            uint32_t im[32];
#pragma unroll
            for (int jj = 0; jj < 4; ++jj) {
                uint32_t pr[4], qq[4];
#pragma unroll
                for (int j4 = 0; j4 < 4; ++j4) {
                    const int j = jj * 4 + j4;
                    const float r0 = fmaf(mr, exr, fmaf(-mi, exi, a0[4 * j])), i0 = fmaf(mr, exi, fmaf(mi, exr, a0[4 * j + 2]));
                    const float r1 = fmaf(mr, fxr, fmaf(-mi, fxi, a1[4 * j])), i1 = fmaf(mr, fxi, fmaf(mi, fxr, a1[2 + 4 * j]));
                    exr = fmaf(mr, r0, fmaf(-mi, i0, a0[4 * j + 1]));
                    exi = fmaf(mr, i0, fmaf(mi, r0, a0[4 * j + 3]));
                    fxr = fmaf(mr, r1, fmaf(-mi, i1, a1[1 + 4 * j]));
                    fxi = fmaf(mr, i1, fmaf(mi, r1, a1[3 + 4 * j]));
                    pr[j4] = pack_bf16(r0, exr); im[j] = pack_bf16(i0, exi);
                    qq[j4] = pack_bf16(r1, fxr); im[16 + j] = pack_bf16(i1, fxi);
                }
                if (cw == 0) {
                    stg128(hp + jj * 4096, pr[0], pr[1], pr[2], pr[3]);
                    stg128(hp + jj * 4096 + 262144, qq[0], qq[1], qq[2], qq[3]);
                } else {
                    sts128(hs + jj * 2048, pr[0], pr[1], pr[2], pr[3]);
                    sts128(hs + jj * 2048 + 8192, qq[0], qq[1], qq[2], qq[3]);
                }
            }
            if (t == 0) STAMP(1, 5 + 6 * cw);
            if (cw == 0) {
                named_bar(1, 128);
                if (t == 0) { red_release(&g_cnt[(4 * ti) * 32], 4); mbar_arrive(bar_rel); }
                named_bar(1, 128);
                if (t == 0) STAMP(1, 6);
#pragma unroll
                for (int jj = 0; jj < 8; ++jj) stg128(hp + 131072 + (jj & 3) * 4096 + (jj >> 2) * 262144, im[4 * jj], im[4 * jj + 1], im[4 * jj + 2], im[4 * jj + 3]);
            } else {
#pragma unroll
                for (int jj = 0; jj < 8; ++jj) sts128(hs + 16384 + jj * 2048, im[4 * jj], im[4 * jj + 1], im[4 * jj + 2], im[4 * jj + 3]);
                fence_async_smem();
            }
            __syncwarp();
            if (lane == 0) mbar_arrive(bar_hw + 8 * cw + 8);
            if (t == 0) STAMP(1, 50 + cw);
        }
        if (cw == 0) {
            float c0[64], c1[64];
            int st = 0, pst = 0;
            uint32_t ph = 0;
            auto kblock = [&](int kb, auto shallow) {
                const int t = fresh_tid() & 127, lane = t & 31;
                mbar_wait(bar_full2 + 8 * st, st == 4 ? ph ^ PH4 : ph);
                if (kb == 0 && t == 0) STAMP(2, 6);
                if (kb == 0 && lane == 0) mbar_arrive(bar_g2);
                const uint32_t alo = desc_lo(sbase + st * 32768, 4096), blo = desc_lo(sbase + st * 32768 + 16384, 16);
                constexpr int Q = decltype(shallow)::value;
#pragma unroll
                for (int j = 0; j < 8; ++j) {
                    wgmma_fence();
                    if (j & 1) wgmma_n128<1>(c1, alo + 512 + 64 * (j >> 1), blo + 2 * (j >> 1), j >> 1 ? 1 : kb);
                    else wgmma_n128<1>(c0, alo + 64 * (j >> 1), blo + 2 * (j >> 1), j >> 1 ? 1 : kb);
                    wgmma_commit();
                    wgmma_wait<Q>();
                    if (j == Q - 1 && kb > 0 && t == 0) mbar_arrive(bar_empty2 + 8 * pst);
                }
                pst = st;
                if (++st == (kb < SLOT4 - 1 ? 4 : 5)) { st = 0; ph ^= 1; }
            };
#pragma unroll 1
            for (int kb = 0; kb < QKB; ++kb) kblock(kb, std::integral_constant<int, QD>());
#pragma unroll 1
            for (int kb = QKB; kb < 32 - SKEW2; ++kb) kblock(kb, std::integral_constant<int, QD2>());
            static_assert(SKEW2 <= 4, "slot release");
            const uint32_t alo = desc_lo(sbase, 4096), blo = desc_lo(sbase + 16384, 16);
#pragma unroll
            for (int kb = 32 - SKEW2; kb < 32; ++kb) {
                mbar_wait(bar_full2 + 8 * ring_slot(kb), ring_par(kb));
                wgmma_fence();
#pragma unroll
                for (int k = 0; k < 4; ++k) wgmma_n128<1>(c0, alo + ring_slot(kb) * 2048 + 64 * k, blo + ring_slot(kb) * 2048 + 2 * k, 1);
                wgmma_commit();
            }
            auto late = [&](int kb) {
                wgmma_fence();
#pragma unroll
                for (int k = 0; k < 4; ++k) wgmma_n128<1>(c1, alo + 512 + ring_slot(kb) * 2048 + 64 * k, blo + ring_slot(kb) * 2048 + 2 * k, 1);
                wgmma_commit();
            };
            late(32 - SKEW2);
            if (LORD == 2) late(33 - SKEW2);
            const int t = fresh_tid() & 127, lane = t & 31, w4 = t >> 5, g = lane >> 2, t4 = lane & 3;
            auto epilogue = [&](const float (&a)[64], int b) {
                const uint32_t ad0 = sbase + (b ? OFF_CT : OFF_CU) + (w4 * 16 + g) * 128 + (((2 * t4) ^ g) << 4);
                float gt[2];
                uint32_t bv[4][4];
#pragma unroll
                for (int h = 0; h < 2; ++h) gt[h] = __uint_as_float(lds32(sbase + OFF_PAR + (64 * b + 16 * w4 + 8 * h + g) * 4));
#pragma unroll
                for (int i = 0; i < 4; ++i)
                    asm volatile("ld.shared.v4.b32 {%0,%1,%2,%3}, [%4];" : "=r"(bv[i][0]), "=r"(bv[i][1]), "=r"(bv[i][2]), "=r"(bv[i][3])
                                 : "r"(ad0 + (i & 1) * 1024 + (i >> 1) * 8192) : "memory");
                if (b == 0) wgmma_wait<LORD == 2 ? 2 : 1>(); else wgmma_wait<0>();
                if (b == 0) fence_regs(c0); else fence_regs(c1);
                if (t == 0) STAMP(2, b ? 2 : 5);
#pragma unroll
                for (int jq = 0; jq < 4; ++jq) {
                    if (!LORD && b == 0 && jq < SKEW2 - 1) late(33 - SKEW2 + jq);
#pragma unroll
                    for (int h = 0; h < 2; ++h) {
                        const uint32_t ad = ad0 + h * 1024 + jq * 8192;
                        uint32_t (&w)[4] = bv[2 * (jq & 1) + h];
                        const int r = 16 * jq + 2 * h;
                        sts128(ad, __float_as_uint(fmaf(gt[h], a[r], bf_lo(w[0]))), __float_as_uint(fmaf(gt[h], a[r + 1], bf_hi(w[0]))),
                               __float_as_uint(fmaf(gt[h], a[r + 4], bf_lo(w[1]))), __float_as_uint(fmaf(gt[h], a[r + 5], bf_hi(w[1]))));
                        sts128(ad ^ 16, __float_as_uint(fmaf(gt[h], a[r + 8], bf_lo(w[2]))), __float_as_uint(fmaf(gt[h], a[r + 9], bf_hi(w[2]))),
                               __float_as_uint(fmaf(gt[h], a[r + 12], bf_lo(w[3]))), __float_as_uint(fmaf(gt[h], a[r + 13], bf_hi(w[3]))));
                        if (jq < 2) asm volatile("ld.shared.v4.b32 {%0,%1,%2,%3}, [%4];" : "=r"(w[0]), "=r"(w[1]), "=r"(w[2]), "=r"(w[3]) : "r"(ad + 16384) : "memory");
                    }
                    fence_async_smem();
                    __syncwarp();
                    if (lane == 0) mbar_arrive(bar_stg + 48 + 32 * b + 8 * jq);
                    if (LORD == 1 && b == 0 && jq < SKEW2 - 1) late(33 - SKEW2 + jq);
                    if (LORD == 2 && b == 0 && jq < SKEW2 - 2) late(34 - SKEW2 + jq);
                }
            };
            mbar_wait(bar_bias, 0);
            if (t == 0) STAMP(2, 4);
            epilogue(c0, 0);
            mbar_wait(bar_bias + 8, 0);
            epilogue(c1, 1);
            if (t == 0) STAMP(2, 7);
            return;
        }
        asm volatile("setmaxnreg.dec.sync.aligned.u32 %0;" ::"n"(REG_C));
    }
    {
        {
            const int t = fresh_tid() & 127, lane = t & 31, w4 = t >> 5;
            Twiddle tw;
            load_twiddle(tw, reinterpret_cast<const uint4*>(g_tw_tab.w) + t);
            const uint32_t lo = (uint32_t)((16 * w4 + (lane & 7)) * 64 + (((lane >> 3) ^ ((lane >> 1) & 3)) << 4));
            const uint32_t tlo = desc_lo(sbase + OFF_CT, 16);
            float dE[32], dO[32];
            int p = wg == 2 ? 2 : 0;
            mbar_wait(bar_stg, 0);
            mbar_wait(bar_tab, 0);
            mbar_wait(bar_k + 8 * p, 0);
            if (t == 0) STAMP(0, wg == 2 ? 50 : 1);
            wgmma_fence();
            conv_s1(dE, dO, tlo, desc_lo(sbase + conv_buf(0) + p * 16384, 8192));
            wgmma_commit();
            wgmma_wait<0>();
            fence_regs(dE); fence_regs(dO);
            named_bar(wg, 128);
#pragma unroll 1
            for (; p < 4; p = 2 * p + 1) {
                const int pn = p < 2 ? 2 * p + 1 : p;
                if (t == 0) STAMP(0, 40 + 2 * p);
                conv_pair(dE, dO, tw, lds32(w_dsk + ((lane & 3) ? 16 : 4 * p)), tlo, sbase + conv_buf(p), sbase + conv_buf(pn), lo, wg,
                                [&]() { mbar_wait(bar_k + 8 * pn, 0); });
                if (lane == 0) mbar_arrive(bar_stg + 16 + 8 * p);
            }
            if (t == 0) STAMP(0, 57 + wg);
            __syncwarp();
        }
        if (wg == 2) {
            {
            const int t = fresh_tid() & 127, lane = t & 31, w4 = t >> 5, g = lane >> 2, t4 = lane & 3;
            const int bid = lds32(w_bid), dt = bid & 7;
            const int trow = (bid >> 4) * 256 + 4 * (bid & 8) + 128 * (w4 & 1) + 8 * (w4 >> 1) + g;
            uint4 xv[16], dk[4];
            const __nv_bfloat16* xp = x + (size_t)trow * D_DIM + dt * 128 + 8 * t4;
#pragma unroll
            for (int i = 0; i < 16; ++i) {
                xv[i] = ldg128(xp + (size_t)(16 * (i >> 3) + 64 * ((i >> 2) & 1)) * D_DIM + 32 * (i & 3));
                if (i & 1) __nanosleep(GAP_X);
            }
#pragma unroll
            for (int jq = 0; jq < 4; ++jq) dk[jq] = ldg128(dskip + dt * 128 + 32 * jq + 8 * t4);
            mbar_wait(bar_fh, 0);
            uint32_t omg[4], g2[4];
#pragma unroll
            for (int i = 0; i < 4; ++i) {
                const float gt = __ldcg(g_gate + trow + 16 * (i >> 1) + 64 * (i & 1));
                if (t4 == 0) asm volatile("st.shared.f32 [%0], %1;" ::"r"(sbase + OFF_PAR + (64 * (i >> 1) + 16 * w4 + 8 * (i & 1) + g) * 4), "f"(gt) : "memory");
                omg[i] = pack_bf16(2.f - 2.f * gt, 2.f - 2.f * gt); g2[i] = pack_bf16(gt, gt);
            }
            if (t == 0) {
                mbar_wait(bar_yrel, 0);
                wait_counter(&g_cnt[(48 + dt) * 32], lds32(w_bid + 4));
                STAMP(0, 16);
                mbar_expect_tx(bar_y1, 24576);
                tma_load_5d(sbase + OFF_CU, &maps.yt3, bar_y1, (bid & 8) * 128 + (bid >> 4) * 128, 0, 0, 0, dt * 4);
                tma_load_5d(sbase + OFF_CU + 12288, &maps.yt3, bar_y1, (bid & 8) * 128 + (bid >> 4) * 128 + 64, 0, 0, 0, dt * 4);
            }
            __syncwarp();
            uint32_t ya = sbase + OFF_CU + (w4 & 1) * 12288 + (lane >> 3) * 3072 + (lane & 7) * 128 + ((((w4 >> 1) ^ ((bid >> 3 & 2) + (w4 & 1))) ^ (lane & 7)) << 4);
#pragma unroll
            for (int p = 0; p < 4; ++p) {
                if (p == 0) { mbar_wait(bar_y1, 0); if (t == 0) STAMP(0, 18); }
                if (p == 3) {
                    if (t == 0) STAMP(0, 17);
                    ya += 21504 - (w4 & 1) * 8192 - (lane >> 3) * 2048;
                    mbar_wait(bar_y, 0);
                    if (t == 0) STAMP(0, 6);
                }
#pragma unroll
                for (int i = 0; i < 4; ++i) {
                    uint32_t yw[4];
                    ldsm_x4_t(yw[0], yw[1], yw[2], yw[3], (ya ^ ((i & 1) << 6) ^ ((i & 2) << 4)) + p * 1024);
#pragma unroll
                    for (int jq = 0; jq < 4; ++jq) {
                        uint32_t& w = (&xv[4 * i + jq].x)[p];
                        w = hfma(g2[i], hmul(w, (&dk[jq].x)[p]), hmul(omg[i], hmul(w, yw[jq])));
                    }
                }
            }
            named_bar(2, 128);
#pragma unroll
            for (int i = 0; i < 16; ++i) {
                sts128(sbase + (i & 8 ? OFF_CT : OFF_CU) + (i & 3) * 8192 + (w4 * 16 + g + (i & 4) * 2) * 128 + (((2 * t4) ^ g) << 4), xv[i].x, xv[i].y, xv[i].z, xv[i].w);
                if ((i & 7) == 7) {
                    __syncwarp();
                    if (lane == 0) mbar_arrive(bar_bias + (i & 8));
                }
            }
            if (t == 0) STAMP(0, 7);
            }
        }
    }
    }
}

void make_map(CUtensorMap* m, const void* ptr, int rank, const cuuint64_t* dims, const cuuint64_t* strides, const cuuint32_t* box,
              CUtensorMapSwizzle swz, bool f32 = false) {
    cuuint32_t es[5] = {1, 1, 1, 1, 1};
    get_encode()(m, f32 ? CU_TENSOR_MAP_DATA_TYPE_FLOAT32 : CU_TENSOR_MAP_DATA_TYPE_BFLOAT16, rank, const_cast<void*>(ptr), dims, strides, box, es,
                 CU_TENSOR_MAP_INTERLEAVE_NONE, swz, CU_TENSOR_MAP_L2_PROMOTION_L2_256B, CU_TENSOR_MAP_FLOAT_OOB_FILL_NONE);
}
void make_map_2d(CUtensorMap* m, const void* ptr, uint64_t inner, uint64_t outer, uint32_t box_in, uint32_t box_out) {
    cuuint64_t dims[2] = {inner, outer};
    cuuint64_t strides[1] = {inner * 2};
    cuuint32_t box[2] = {box_in, box_out};
    make_map(m, ptr, 2, dims, strides, box, CU_TENSOR_MAP_SWIZZLE_128B);
}
void make_map_conv(CUtensorMap* m, const void* p, uint32_t nch = 2) {
    cuuint64_t dims[4] = {32, 32, 2, 1024};
    cuuint64_t strides[3] = {128, 64, 4096};
    cuuint32_t box[4] = {32, 32, 2, nch};
    make_map(m, p, 4, dims, strides, box, CU_TENSOR_MAP_SWIZZLE_64B);
}

}

extern "C" void kernel_launch(void* const* d_in, const int* in_sizes, int n_in, void* d_out, int out_size) {
    const __nv_bfloat16* x = (const __nv_bfloat16*)d_in[0];
    const __nv_bfloat16* lam_re = (const __nv_bfloat16*)d_in[1];
    const __nv_bfloat16* lam_im = (const __nv_bfloat16*)d_in[2];
    const __nv_bfloat16* b_re = (const __nv_bfloat16*)d_in[3];
    const __nv_bfloat16* b_im = (const __nv_bfloat16*)d_in[4];
    const __nv_bfloat16* c_re = (const __nv_bfloat16*)d_in[5];
    const __nv_bfloat16* c_im = (const __nv_bfloat16*)d_in[6];
    const __nv_bfloat16* log_dt = (const __nv_bfloat16*)d_in[7];
    const __nv_bfloat16* dskip = (const __nv_bfloat16*)d_in[8];
    const __nv_bfloat16* kin = (const __nv_bfloat16*)d_in[10];
    const __nv_bfloat16* vin = (const __nv_bfloat16*)d_in[11];
    const __nv_bfloat16* shift_k = (const __nv_bfloat16*)d_in[12];
    const __nv_bfloat16* ssm_k = (const __nv_bfloat16*)d_in[13];
    const __nv_bfloat16* ssm_D = (const __nv_bfloat16*)d_in[14];
    const __nv_bfloat16* gate_w = (const __nv_bfloat16*)d_in[15];
    float* out = (float*)d_out;

    void *yptr = nullptr, *kvtptr = nullptr;
    cudaGetSymbolAddress(&yptr, g_y2);
    cudaGetSymbolAddress(&kvtptr, g_kvT);

    Maps maps;
    {
        cuuint64_t dims[5] = {1024, 2, 4, 32, 8};
        cuuint64_t strides[4] = {2048, 64 * 2048, 2 * 2048, 256 * 2048};
        cuuint32_t box[5] = {64, 2, 4, 32, 1};
        make_map(&maps.x5, x, 5, dims, strides, box, CU_TENSOR_MAP_SWIZZLE_128B);
    }
    int bmode = 0;
    {
        const uint64_t a = (uint64_t)b_re, b = (uint64_t)b_im;
        const uint64_t delta = a < b ? b - a : a - b;
        if (delta != 0 && (delta & 15) == 0 && delta < (1ull << 40)) bmode = a < b ? 1 : 2;
        cuuint64_t dims[4] = {1024, 8, 2, 128};
        cuuint64_t strides[3] = {2048, bmode ? delta : 16, 16384};
        cuuint32_t box[4] = {64, 8, 2, 4};
        make_map(&maps.b4, a < b ? b_re : b_im, 4, dims, strides, box, CU_TENSOR_MAP_SWIZZLE_128B);
    }
    make_map_2d(&maps.bre, b_re, 1024, 1024, 64, 8);
    make_map_2d(&maps.bim, b_im, 1024, 1024, 64, 8);
    {
        cuuint64_t dims[3] = {S_LEN, 128, 8};
        cuuint64_t strides[2] = {8 * 4096, 4096};
        cuuint32_t box[3] = {64, 16, 2};
        make_map(&maps.kvst, kvtptr, 3, dims, strides, box, CU_TENSOR_MAP_SWIZZLE_128B);
    }
    make_map_conv(&maps.sk, ssm_k, 1);
    for (int i = 0; i < 2; ++i) {
        cuuint64_t dims[5] = {1024, 2, 4, 4, 32};
        cuuint64_t strides[4] = {2048, 8 * 2048, 2 * 2048, 32 * 2048};
        cuuint32_t box[5] = {64, 2, 4, 4, 4};
        make_map(i ? &maps.cim : &maps.cre, i ? c_im : c_re, 5, dims, strides, box, CU_TENSOR_MAP_SWIZZLE_128B);
    }
    {
        cuuint64_t dims[5] = {S_LEN, 2, 4, 4, 32};
        cuuint64_t strides[4] = {4096, 8 * 4096, 2 * 4096, 32 * 4096};
        cuuint32_t box[5] = {64, 2, 4, 1, 4};
        make_map(&maps.yt, yptr, 5, dims, strides, box, CU_TENSOR_MAP_SWIZZLE_128B);
        box[3] = 3;
        make_map(&maps.yt3, yptr, 5, dims, strides, box, CU_TENSOR_MAP_SWIZZLE_128B);
    }
    {
        cuuint64_t dims[5] = {D_DIM, 8, 4, 8, 8};
        cuuint64_t strides[4] = {4096, 64 * 4096, 8 * 4096, 256 * 4096};
        cuuint32_t box[5] = {32, 8, 4, 2, 1};
        make_map(&maps.out, out, 5, dims, strides, box, CU_TENSOR_MAP_SWIZZLE_128B, true);
    }

    auto kern = bmode == 1 ? fused_kernel<1> : bmode == 2 ? fused_kernel<2> : fused_kernel<0>;
    cudaFuncSetAttribute(kern, cudaFuncAttributeMaxDynamicSharedMemorySize, SMEM_BYTES);
    static int grid = 0;
    if (!grid) {
        int dev = 0, sms = 0;
        cudaGetDevice(&dev);
        cudaDeviceGetAttribute(&sms, cudaDevAttrMultiProcessorCount, dev);
        grid = sms == 132 ? 132 : 128;
    }
    kern<<<grid, 512, SMEM_BYTES>>>(x, b_re, b_im, kin, vin, ssm_k, shift_k, ssm_D, lam_re, lam_im, log_dt, gate_w, dskip, c_re, c_im, maps);
}
```

```cpp
#include <cuda_runtime.h>
#include <cuda_bf16.h>
#include <cuda.h>
#include <stdint.h>
#include <type_traits>

namespace {
__device__ __forceinline__ uint32_t smem_u32(const void* p) { return (uint32_t)__cvta_generic_to_shared(p); }
__device__ __forceinline__ void mbar_init(uint32_t bar, uint32_t count) {
    asm volatile("mbarrier.init.shared::cta.b64 [%0], %1;" ::"r"(bar), "r"(count) : "memory");
}
__device__ __forceinline__ void mbar_expect_tx(uint32_t bar, uint32_t bytes) {
    asm volatile("mbarrier.arrive.expect_tx.shared::cta.b64 _, [%0], %1;" ::"r"(bar), "r"(bytes) : "memory");
}
__device__ __forceinline__ void mbar_arrive(uint32_t bar) {
    asm volatile("mbarrier.arrive.shared::cta.b64 _, [%0];" ::"r"(bar) : "memory");
}
__device__ __forceinline__ void mbar_wait(uint32_t bar, uint32_t parity) {
    asm volatile(
        "{\n"
        ".reg .pred p;\n"
        ".reg .u32 n;\n"
        "mov.u32 n, 0;\n"
        "LAB_WAIT:\n"
        "mbarrier.try_wait.parity.shared::cta.b64 p, [%0], %1;\n"
        "@p bra LAB_DONE;\n"
        "add.u32 n, n, 1;\n"
        "setp.lt.u32 p, n, 0x400000;\n"
        "@p bra LAB_WAIT;\n"
        "trap;\n"
        "LAB_DONE:\n"
        "}\n" ::"r"(bar), "r"(parity) : "memory");
}
__device__ __forceinline__ void tma_load_2d(uint32_t dst, const CUtensorMap* map, uint32_t bar, int c0, int c1) {
    asm volatile(
        "cp.async.bulk.tensor.2d.shared::cluster.global.mbarrier::complete_tx::bytes [%0], [%1, {%3, %4}], [%2];"
        ::"r"(dst), "l"((uint64_t)map), "r"(bar), "r"(c0), "r"(c1) : "memory");
}
__device__ __forceinline__ void tma_load_4d(uint32_t dst, const CUtensorMap* map, uint32_t bar, int c0, int c1, int c2, int c3) {
    asm volatile(
        "cp.async.bulk.tensor.4d.shared::cluster.global.mbarrier::complete_tx::bytes [%0], [%1, {%3, %4, %5, %6}], [%2];"
        ::"r"(dst), "l"((uint64_t)map), "r"(bar), "r"(c0), "r"(c1), "r"(c2), "r"(c3) : "memory");
}
__device__ __forceinline__ void tma_load_5d(uint32_t dst, const CUtensorMap* map, uint32_t bar, int c0, int c1, int c2, int c3, int c4) {
    asm volatile(
        "cp.async.bulk.tensor.5d.shared::cluster.global.mbarrier::complete_tx::bytes [%0], [%1, {%3, %4, %5, %6, %7}], [%2];"
        ::"r"(dst), "l"((uint64_t)map), "r"(bar), "r"(c0), "r"(c1), "r"(c2), "r"(c3), "r"(c4) : "memory");
}
__device__ __forceinline__ void bulk_load(uint32_t dst, const void* src, uint32_t bytes, uint32_t bar) {
    asm volatile("cp.async.bulk.shared::cluster.global.mbarrier::complete_tx::bytes [%0], [%1], %2, [%3];"
                 ::"r"(dst), "l"(src), "r"(bytes), "r"(bar) : "memory");
}
__device__ __forceinline__ void tma_store_3d(const CUtensorMap* map, uint32_t src, int c0, int c1, int c2) {
    asm volatile("cp.async.bulk.tensor.3d.global.shared::cta.bulk_group [%0, {%2, %3, %4}], [%1];"
                 ::"l"((uint64_t)map), "r"(src), "r"(c0), "r"(c1), "r"(c2) : "memory");
}
__device__ __forceinline__ void bulk_commit() { asm volatile("cp.async.bulk.commit_group;" ::: "memory"); }
__device__ __forceinline__ void bulk_wait0() { asm volatile("cp.async.bulk.wait_group 0;" ::: "memory"); }
__device__ __forceinline__ void bulk_wait_read0() { asm volatile("cp.async.bulk.wait_group.read 0;" ::: "memory"); }
__device__ __forceinline__ void fence_async_smem() { asm volatile("fence.proxy.async.shared::cta;" ::: "memory"); }
__device__ __forceinline__ void named_bar(int id, int n) { asm volatile("bar.sync %0, %1;" ::"r"(id), "r"(n) : "memory"); }
__device__ __forceinline__ void sts128(uint32_t addr, uint32_t a, uint32_t b, uint32_t c, uint32_t d) {
    asm volatile("st.shared.v4.b32 [%0], {%1, %2, %3, %4};" ::"r"(addr), "r"(a), "r"(b), "r"(c), "r"(d) : "memory");
}
__device__ __forceinline__ void prefetch_map(const CUtensorMap* m) {
    asm volatile("prefetch.tensormap [%0];" ::"l"((uint64_t)m) : "memory");
}
__device__ __forceinline__ void wgmma_fence() { asm volatile("wgmma.fence.sync.aligned;" ::: "memory"); }
__device__ __forceinline__ void wgmma_commit() { asm volatile("wgmma.commit_group.sync.aligned;" ::: "memory"); }
template <int N>
__device__ __forceinline__ void wgmma_wait() { asm volatile("wgmma.wait_group.sync.aligned %0;" ::"n"(N) : "memory"); }
template <int N>
__device__ __forceinline__ void fence_regs(float (&a)[N]) {
#pragma unroll
    for (int i = 0; i < N; ++i) asm volatile("" : "+f"(a[i])::"memory");
}
template <int N>
__device__ __forceinline__ void fence_regs(uint32_t (&a)[N]) {
#pragma unroll
    for (int i = 0; i < N; ++i) asm volatile("" : "+r"(a[i])::"memory");
}
#define R8(a, i) "+f"(a[i + 0]), "+f"(a[i + 1]), "+f"(a[i + 2]), "+f"(a[i + 3]), "+f"(a[i + 4]), "+f"(a[i + 5]), "+f"(a[i + 6]), "+f"(a[i + 7])
#define REGS32 "{%0, %1, %2, %3, %4, %5, %6, %7, %8, %9, %10, %11, %12, %13, %14, %15, %16, %17, %18, %19, %20, %21, %22, %23, %24, %25, %26, %27, %28, %29, %30, %31}"
#define REGS16 "{%0, %1, %2, %3, %4, %5, %6, %7, %8, %9, %10, %11, %12, %13, %14, %15}"

__host__ __device__ constexpr uint32_t desc_hi(uint32_t sbo, uint32_t mode) { return (sbo >> 4) | (mode << 30); }
__device__ __forceinline__ uint32_t desc_lo(uint32_t saddr, uint32_t lbo) { return ((saddr & 0x3FFFF) >> 4) | ((lbo >> 4) << 16); }
constexpr uint32_t HI128 = desc_hi(1024, 1), HI64 = desc_hi(512, 2);
#define W8(a, i) "=f"(a[i + 0]), "=f"(a[i + 1]), "=f"(a[i + 2]), "=f"(a[i + 3]), "=f"(a[i + 4]), "=f"(a[i + 5]), "=f"(a[i + 6]), "=f"(a[i + 7])
template <int TA, int TB, int ACC, uint32_t AHI, uint32_t BHI>
__device__ __forceinline__ void wgmma_n64_ss(float (&d)[32], uint32_t alo, uint32_t blo) {
#define N64_TEXT "{\n.reg .pred p;\n.reg .b64 da, db;\nsetp.ne.b32 p, %36, 0;\nmov.b64 da, {%32, %37};\nmov.b64 db, {%33, %38};\n" \
        "wgmma.mma_async.sync.aligned.m64n64k16.f32.bf16.bf16 " REGS32 ", da, db, p, 1, 1, %34, %35;\n}\n"
    if (ACC) asm volatile(N64_TEXT : R8(d, 0), R8(d, 8), R8(d, 16), R8(d, 24) : "r"(alo), "r"(blo), "n"(TA), "n"(TB), "n"(ACC), "n"(AHI), "n"(BHI));
    else asm volatile(N64_TEXT : W8(d, 0), W8(d, 8), W8(d, 16), W8(d, 24) : "r"(alo), "r"(blo), "n"(TA), "n"(TB), "n"(ACC), "n"(AHI), "n"(BHI));
}
template <int ACC, int SA>
__device__ __forceinline__ void wgmma_n32_tt(float (&d)[16], uint32_t alo, uint32_t blo) {
#define N32T_TEXT "{\n.reg .pred p;\n.reg .b64 da, db;\nsetp.ne.b32 p, %18, 0;\nmov.b64 da, {%16, %19};\nmov.b64 db, {%17, %20};\n" \
        "wgmma.mma_async.sync.aligned.m64n32k16.f32.bf16.bf16 " REGS16 ", da, db, p, %21, 1, 1, 1;\n}\n"
    if (ACC) asm volatile(N32T_TEXT : R8(d, 0), R8(d, 8) : "r"(alo), "r"(blo), "n"(ACC), "n"(HI64), "n"(HI128), "n"(SA));
    else asm volatile(N32T_TEXT : W8(d, 0), W8(d, 8) : "r"(alo), "r"(blo), "n"(ACC), "n"(HI64), "n"(HI128), "n"(SA));
}
__device__ __forceinline__ void wgmma_n16_rs(float (&d)[8], const uint32_t (&a)[4], uint32_t blo) {
    asm volatile("{\n.reg .pred p;\n.reg .b64 db;\nsetp.ne.b32 p, 0, 0;\nmov.b64 db, {%12, %13};\n"
        "wgmma.mma_async.sync.aligned.m64n16k16.f32.bf16.bf16 {%0, %1, %2, %3, %4, %5, %6, %7}, {%8, %9, %10, %11}, db, p, 1, 1, 0;\n}\n"
        : W8(d, 0) : "r"(a[0]), "r"(a[1]), "r"(a[2]), "r"(a[3]), "r"(blo), "n"(HI128));
}

__device__ __forceinline__ float bf16r(float x) { return __bfloat162float(__float2bfloat16_rn(x)); }
__device__ __forceinline__ uint32_t pack_bf16(float lo, float hi) {
    __nv_bfloat162 v = __floats2bfloat162_rn(lo, hi);
    return *reinterpret_cast<uint32_t*>(&v);
}
__device__ __forceinline__ __nv_bfloat162 as_bf2(uint32_t w) { return *reinterpret_cast<__nv_bfloat162*>(&w); }
__device__ __forceinline__ uint32_t as_u32(__nv_bfloat162 v) { return *reinterpret_cast<uint32_t*>(&v); }
__device__ __forceinline__ float bf_lo(uint32_t w) { return __uint_as_float(w << 16); }
__device__ __forceinline__ float bf_hi(uint32_t w) { return __uint_as_float(w & 0xFFFF0000u); }
__device__ __forceinline__ void ldsm_x4_t(uint32_t& r0, uint32_t& r1, uint32_t& r2, uint32_t& r3, uint32_t addr) {
    asm volatile("ldmatrix.sync.aligned.m8n8.x4.trans.shared.b16 {%0,%1,%2,%3}, [%4];"
                 : "=r"(r0), "=r"(r1), "=r"(r2), "=r"(r3) : "r"(addr) : "memory");
}
__device__ __forceinline__ void stsm_x4(uint32_t addr, uint32_t r0, uint32_t r1, uint32_t r2, uint32_t r3) {
    asm volatile("stmatrix.sync.aligned.m8n8.x4.shared.b16 [%0], {%1,%2,%3,%4};"
                 ::"r"(addr), "r"(r0), "r"(r1), "r"(r2), "r"(r3) : "memory");
}
__device__ __forceinline__ void stsm_x4_t(uint32_t addr, uint32_t r0, uint32_t r1, uint32_t r2, uint32_t r3) {
    asm volatile("stmatrix.sync.aligned.m8n8.x4.trans.shared.b16 [%0], {%1,%2,%3,%4};"
                 ::"r"(addr), "r"(r0), "r"(r1), "r"(r2), "r"(r3) : "memory");
}
__device__ __forceinline__ uint32_t lds32(uint32_t addr) {
    uint32_t v;
    asm volatile("ld.shared.b32 %0, [%1];" : "=r"(v) : "r"(addr));
    return v;
}

typedef CUresult (*EncodeFn)(CUtensorMap*, CUtensorMapDataType, cuuint32_t, void*, const cuuint64_t*, const cuuint64_t*,
                             const cuuint32_t*, const cuuint32_t*, CUtensorMapInterleave, CUtensorMapSwizzle,
                             CUtensorMapL2promotion, CUtensorMapFloatOOBfill);
EncodeFn get_encode() {
    static EncodeFn fn = nullptr;
    if (!fn) {
        void* p = nullptr;
        cudaDriverEntryPointQueryResult qres;
        cudaGetDriverEntryPoint("cuTensorMapEncodeTiled", &p, cudaEnableDefault, &qres);
        fn = (EncodeFn)p;
    }
    return fn;
}
}
namespace {
constexpr double c_pi = 3.14159265358979323846;
constexpr double c_cos256(int i) {
    i &= 255;
    if (i > 128) i = 256 - i;
    double sgn = 1.0;
    if (i > 64) { i = 128 - i; sgn = -1.0; }
    if (i == 64) return 0.0;
    double x = 2.0 * c_pi * i / 256.0, x2 = x * x, term = 1.0, sum = 1.0;
    for (int k = 1; k < 20; ++k) { term *= -x2 / ((2 * k - 1) * (2 * k)); sum += term; }
    return sgn * sum;
}
constexpr uint32_t c_bf16(double v) {
    if (v == 0.0) return 0u;
    uint32_t s = v < 0 ? 0x8000u : 0u;
    double a = v < 0 ? -v : v;
    int e = 0;
    while (a >= 2.0) { a *= 0.5; ++e; }
    while (a < 1.0) { a *= 2.0; --e; }
    int r = (int)(a * 128.0 + 0.5);
    if (r == 256) { r = 128; ++e; }
    return s | (uint32_t)((e + 127) << 7) | (uint32_t)(r - 128);
}
__host__ __device__ constexpr int conv_k1(int r) { return (r & 8) ? 63 - (((r >> 4) << 3) | (r & 7)) : (((r >> 4) << 3) | (r & 7)); }
struct ConvTab { uint32_t w[96 * 32]; };
constexpr ConvTab make_conv_tab() {
    ConvTab t{};
    uint32_t cs[256] = {};
    for (int i = 0; i < 256; ++i) cs[i] = c_bf16(c_cos256(i));
    for (int n = 0; n < 96; ++n)
        for (int c = 0; c < 64; ++c) {
            int a = 0;
            if (n < 32) {
                const int ro = (n >> 3) & 1, ri = n & 7, co = (c >> 3) & 1, ci = c & 7;
                a = n < 16 ? 8 * ci * (4 * ri + (c >> 4)) : 8 * ri * (4 * ci + (c >> 4));
                a += (ro == co) ? 0 : (ro == 0) ? 192 : 64;
            } else {
                const int r = n - 32, n1 = 2 * (c & 31) + (c >> 5);
                a = n1 * (2 * (((r >> 4) << 3) | (r & 7)) + 1) + ((r & 8) ? 64 : 0);
            }
            const int off = n * 128 + (((c >> 3) ^ (n & 7)) << 4) + (c & 7) * 2;
            t.w[off >> 2] |= cs[a & 255] << ((off & 2) * 8);
        }
    return t;
}
__device__ __align__(128) constexpr ConvTab g_conv_tab = make_conv_tab();

struct Twiddle { uint32_t r[8], i[8], n[8]; };
constexpr double c_cospi(double x) {
    double sgn = 1.0;
    if (x > 0.5) { x = 1.0 - x; sgn = -1.0; }
    const double y = c_pi * x, y2 = y * y;
    double term = 1.0, sum = 1.0;
    for (int k = 1; k < 12; ++k) { term *= -y2 / ((2 * k - 1) * (2 * k)); sum += term; }
    return sgn * sum;
}
struct TwTab { uint32_t w[3072]; };
constexpr TwTab make_tw_tab() {
    TwTab t{};
    for (int th = 0; th < 128; ++th)
        for (int q = 0; q < 8; ++q)
            for (int e = 0; e < 2; ++e) {
                const int k1 = conv_k1(16 * (th >> 5) + 8 * (q & 1) + ((th & 31) >> 2)), n2 = 8 * (q >> 1) + 2 * (th & 3) + e;
                const double x = (double)(n2 * (2 * k1 + 1)) / 4096.0;
                const double cs = c_cospi(x), sn = n2 == 0 ? 0.0 : c_cospi(x > 0.5 ? x - 0.5 : 0.5 - x);
                t.w[((q >> 2) * 128 + th) * 4 + (q & 3)] |= c_bf16(cs * 0.0625) << (16 * e);
                t.w[((2 + (q >> 2)) * 128 + th) * 4 + (q & 3)] |= c_bf16(-sn * 0.0625) << (16 * e);
                t.w[((4 + (q >> 2)) * 128 + th) * 4 + (q & 3)] |= c_bf16(sn * 0.0625) << (16 * e);
            }
    return t;
}
__device__ __align__(128) constexpr TwTab g_tw_tab = make_tw_tab();
__device__ __forceinline__ void load_twiddle(Twiddle& tw, const uint4* p) {
#pragma unroll
    for (int q = 0; q < 2; ++q) {
        const uint4 a = __ldg(p + q * 128);
        const uint4 b = __ldg(p + (2 + q) * 128);
        tw.r[4 * q] = a.x; tw.r[4 * q + 1] = a.y; tw.r[4 * q + 2] = a.z; tw.r[4 * q + 3] = a.w;
        const uint4 n = __ldg(p + (4 + q) * 128);
        tw.n[4 * q] = n.x; tw.n[4 * q + 1] = n.y; tw.n[4 * q + 2] = n.z; tw.n[4 * q + 3] = n.w;
        tw.i[4 * q] = b.x; tw.i[4 * q + 1] = b.y; tw.i[4 * q + 2] = b.z; tw.i[4 * q + 3] = b.w;
    }
}

__device__ __forceinline__ int fresh_tid() { int v; asm volatile("mov.u32 %0, %tid.x;" : "=r"(v)); return v; }
__device__ __forceinline__ uint32_t hmul(uint32_t a, uint32_t b) { return as_u32(__hmul2_rn(as_bf2(a), as_bf2(b))); }
__device__ __forceinline__ uint32_t hadd(uint32_t a, uint32_t b) { return as_u32(__hadd2_rn(as_bf2(a), as_bf2(b))); }
__device__ __forceinline__ uint32_t hsub(uint32_t a, uint32_t b) { return as_u32(__hsub2_rn(as_bf2(a), as_bf2(b))); }
__device__ __forceinline__ uint32_t hfma(uint32_t a, uint32_t b, uint32_t c) { return as_u32(__hfma2(as_bf2(a), as_bf2(b), as_bf2(c))); }

__device__ __forceinline__ void conv_dft8(float (&x)[4][8], const uint32_t (&f)[4][4], uint32_t blo) {
#pragma unroll
    for (int r = 0; r < 4; ++r) wgmma_n16_rs(x[r], f[r], blo + 2 * r);
}
template <class T, int N>
__device__ __forceinline__ void fence_regs4(T (&a)[4][N]) { fence_regs(a[0]); fence_regs(a[1]); fence_regs(a[2]); fence_regs(a[3]); }
__device__ __forceinline__ void conv_s1(float (&dE)[32], float (&dO)[32], uint32_t tlo, uint32_t ulo) {
    wgmma_n64_ss<0, 1, 0, HI128, HI64>(dE, tlo + 256, ulo);
    wgmma_n64_ss<0, 1, 0, HI128, HI64>(dO, tlo + 256 + 4, ulo + 128);
    wgmma_n64_ss<0, 1, 1, HI128, HI64>(dE, tlo + 256 + 2, ulo + 64);
    wgmma_n64_ss<0, 1, 1, HI128, HI64>(dO, tlo + 256 + 6, ulo + 192);
}
template <int S>
__device__ __forceinline__ void conv_t1(const float (&dE)[32], const float (&dO)[32], const Twiddle& tw, float dsk, uint32_t (&f)[4][4]) {
    uint32_t ar[8], ai[8], fs[8], fd[8];
#pragma unroll
    for (int j = 0; j < 4; ++j) {
        const int i = 16 * S + 4 * j;
        const uint32_t e0 = pack_bf16(i == 16 ? dE[i] + dsk : dE[i], dE[i + 1]), e1 = pack_bf16(dE[i + 2], dE[i + 3]);
        const uint32_t o0 = pack_bf16(dO[i], dO[i + 1]), o1 = pack_bf16(dO[i + 2], dO[i + 3]);
        ar[2 * j] = hadd(e0, o0); ai[2 * j] = hadd(e1, o1);
        ar[2 * j + 1] = hsub(e0, o0); ai[2 * j + 1] = hsub(o1, e1);
    }
#pragma unroll
    for (int q = 0; q < 4; ++q) {
        const uint32_t pr = hfma(ar[q], tw.r[q], hmul(ai[q], tw.n[q])), pi = hfma(ar[q], tw.i[q], hmul(ai[q], tw.r[q]));
        fs[q] = hfma(ar[4 + q], tw.r[4 + q], hfma(ai[4 + q], tw.n[4 + q], pr));
        fs[4 + q] = hfma(ar[4 + q], tw.i[4 + q], hfma(ai[4 + q], tw.r[4 + q], pi));
        fd[q] = hfma(pr, 0xC000C000u, fs[q]);
        fd[4 + q] = hfma(pi, 0xC000C000u, fs[4 + q]);
    }
#pragma unroll
    for (int h = 0; h < 2; ++h) {
        f[0][h] = hadd(fs[h], fs[2 + h]); f[0][2 + h] = hadd(fs[4 + h], fs[6 + h]);
        f[2][h] = hsub(fs[h], fs[2 + h]); f[2][2 + h] = hsub(fs[4 + h], fs[6 + h]);
        f[1][h] = hadd(fd[h], fd[6 + h]); f[1][2 + h] = hsub(fd[4 + h], fd[2 + h]);
        f[3][h] = hsub(fd[h], fd[6 + h]); f[3][2 + h] = hadd(fd[4 + h], fd[2 + h]);
    }
}
__device__ __forceinline__ void conv_prod(const float (&xu)[8], const float (&xk)[8], uint32_t (&f)[4]) {
#pragma unroll
    for (int h = 0; h < 2; ++h) {
        float pr[2], pi[2];
#pragma unroll
        for (int e = 0; e < 2; ++e) {
            const float ur = xu[2 * h + e], ui = xu[4 + 2 * h + e], kr = xk[2 * h + e], ki = xk[4 + 2 * h + e];
            pr[e] = fmaf(ur, kr, -ui * ki);
            pi[e] = fmaf(-ur, ki, -ui * kr);
        }
        f[h] = pack_bf16(pr[0], pr[1]);
        f[2 + h] = pack_bf16(pi[0], pi[1]);
    }
}
template <bool SECOND, class G>
__device__ __forceinline__ void conv_channel(float (&dE)[32], float (&dO)[32], const Twiddle& tw, float dsk, uint32_t tlo, uint32_t nxt,
                                             uint32_t wre, uint32_t wim, int bar, G before_next) {
    float xu[4][8], xk[4][8];
    {
        uint32_t fu[4][4], fk[4][4];
        conv_t1<0>(dE, dO, tw, 0.f, fu);
        wgmma_fence();
        conv_dft8(xu, fu, tlo);
        wgmma_commit();
        conv_t1<1>(dE, dO, tw, dsk, fk);
        wgmma_fence();
        conv_dft8(xk, fk, tlo);
        wgmma_commit();
        before_next();
        wgmma_wait<0>();
        fence_regs4(xu); fence_regs4(xk);
        fence_regs4(fu); fence_regs4(fk);
    }
    uint32_t fp[4][4];
#pragma unroll
    for (int r = 0; r < 4; ++r) conv_prod(xu[r], xk[r], fp[r]);
    wgmma_fence();
    conv_dft8(xu, fp, tlo + 128);
    wgmma_commit();
    if (!SECOND || nxt) {
        if (SECOND) wgmma_fence();
        conv_s1(dE, dO, tlo, nxt);
        wgmma_commit();
        wgmma_wait<1>();
    } else {
        wgmma_wait<0>();
#pragma unroll
        for (int i = 0; i < 32; ++i) { dE[i] = 0.f; dO[i] = 0.f; }
        fence_regs(dE); fence_regs(dO);
    }
    fence_regs4(xu);
    fence_regs4(fp);
    uint32_t zr[8], zi[8], wr[8], wi[8];
#pragma unroll
    for (int h = 0; h < 2; ++h) {
        uint32_t yr[4], yi[4];
#pragma unroll
        for (int r = 0; r < 4; ++r) { yr[r] = pack_bf16(xu[r][2 * h], xu[r][2 * h + 1]); yi[r] = pack_bf16(xu[r][4 + 2 * h], xu[r][5 + 2 * h]); }
        const uint32_t u0r = hadd(yr[0], yr[2]), u0i = hadd(yi[0], yi[2]), u1r = hsub(yr[0], yr[2]), u1i = hsub(yi[0], yi[2]);
        const uint32_t v0r = hadd(yr[1], yr[3]), v0i = hadd(yi[1], yi[3]), v1r = hsub(yr[1], yr[3]), v1i = hsub(yi[1], yi[3]);
        zr[h] = hadd(u0r, v0r); zi[h] = hadd(u0i, v0i); zr[4 + h] = hsub(u0r, v0r); zi[4 + h] = hsub(u0i, v0i);
        zr[2 + h] = hadd(u1r, v1i); zi[2 + h] = hsub(u1i, v1r); zr[6 + h] = hsub(u1r, v1i); zi[6 + h] = hadd(u1i, v1r);
    }
#pragma unroll
    for (int q = 0; q < 8; ++q) {
        wr[q] = hfma(zr[q], tw.r[q], hmul(zi[q], tw.n[q]));
        wi[q] = hfma(zr[q], tw.i[q], hmul(zi[q], tw.r[q]));
    }
    if (SECOND) named_bar(bar, 128);
    stsm_x4(wre, hadd(wr[0], wr[1]), hadd(wr[2], wr[3]), hadd(wr[4], wr[5]), hadd(wr[6], wr[7]));
    stsm_x4(wre + 512, hsub(wi[1], wi[0]), hsub(wi[3], wi[2]), hsub(wi[5], wi[4]), hsub(wi[7], wi[6]));
    stsm_x4(wim, hsub(wr[1], wr[0]), hsub(wr[3], wr[2]), hsub(wr[5], wr[4]), hsub(wr[7], wr[6]));
    stsm_x4(wim + 512, hadd(wi[0], wi[1]), hadd(wi[2], wi[3]), hadd(wi[4], wi[5]), hadd(wi[6], wi[7]));
}
template <class G>
__device__ __forceinline__ void conv_pair(float (&dE)[32], float (&dO)[32], const Twiddle& tw, uint32_t dd, uint32_t tlo, uint32_t u0, uint32_t un,
                                          uint32_t lo, int BAR, G before_next) {
    conv_channel<false>(dE, dO, tw, bf_lo(dd), tlo, desc_lo(u0 + 4096, 8192), u0 + lo, u0 + 8192 + lo, BAR, []() {});
    wgmma_wait<0>();
    fence_regs(dE); fence_regs(dO);
    conv_channel<true>(dE, dO, tw, bf_hi(dd), tlo, un == u0 ? 0 : desc_lo(un, 8192), u0 + 4096 + lo, u0 + 12288 + lo, BAR, before_next);
    fence_async_smem();
    named_bar(BAR, 128);
    float ye[16], yo[16];
    wgmma_fence();
    const uint32_t wlo = desc_lo(u0, 4096);
    wgmma_n32_tt<0, 1>(ye, wlo, tlo + 256);
    wgmma_n32_tt<0, -1>(yo, wlo + 512, tlo + 256 + 4);
#pragma unroll
    for (int k = 1; k < 4; ++k) {
        wgmma_n32_tt<1, 1>(ye, wlo + 64 * k, tlo + 256 + 128 * k);
        wgmma_n32_tt<1, -1>(yo, wlo + 512 + 64 * k, tlo + 256 + 4 + 128 * k);
    }
    wgmma_commit();
    wgmma_wait<0>();
    fence_regs(ye); fence_regs(yo);
    fence_regs(dE); fence_regs(dO);
    named_bar(BAR, 128);
    const int t = fresh_tid();
    const uint32_t ya = u0 + (t & 64) * 64 + (t & 31) * 64 + (((((t >> 4) & 2) ^ (t >> 1)) & 3) << 4);
#pragma unroll
    for (int h = 0; h < 2; ++h) {
        stsm_x4_t(ya ^ (16 * h), pack_bf16(ye[2 * h], ye[2 * h + 1]), pack_bf16(ye[4 + 2 * h], ye[5 + 2 * h]),
                  pack_bf16(ye[8 + 2 * h], ye[9 + 2 * h]), pack_bf16(ye[12 + 2 * h], ye[13 + 2 * h]));
        stsm_x4_t((ya ^ (16 * h)) + 2048, pack_bf16(yo[2 * h], yo[2 * h + 1]), pack_bf16(yo[4 + 2 * h], yo[5 + 2 * h]),
                  pack_bf16(yo[8 + 2 * h], yo[9 + 2 * h]), pack_bf16(yo[12 + 2 * h], yo[13 + 2 * h]));
    }
    fence_async_smem();
    __syncwarp();
}
}

namespace {

constexpr int S_LEN = 2048;
constexpr int D_DIM = 1024;

#define REG_P 24
#define REG_AB 168
#define REG_C 152
#define SKEW1 4
#define SKEW2 4
#define QD 3
#define QKB 18
#define QD2 6
#define SLOT4 20
#define EPF 2
#define PFD 7
#define TK_PF0 0
#define TK_KV0 2
#define TK_KV1 4
#define TK_C 8
#define GAP_PF 300
#define GAP_KV 50
#define GAP_ST 50
#define GAP_CV 100
#define GAP_HB 100
#define GAP_Y 100
#define GAP_X 100
#define ALTMAP 0

__device__ __align__(1024) __nv_bfloat16 g_H[2 * D_DIM * S_LEN];
__device__ __align__(1024) __nv_bfloat16 g_y2[D_DIM * S_LEN];
__device__ __align__(1024) __nv_bfloat16 g_kvT[D_DIM * S_LEN];
__device__ __align__(128) float g_gate[S_LEN];
__device__ __align__(128) unsigned long long g_agg[8 * D_DIM];
__device__ __align__(128) unsigned int g_cnt[56 * 32];

#define STAMP(k, s) do { } while (0)
#define SAMPLE(i) do { } while (0)

__device__ __forceinline__ void tma_store_5d(const CUtensorMap* map, uint32_t src, int c0, int c1, int c2, int c3, int c4) {
    asm volatile("cp.async.bulk.tensor.5d.global.shared::cta.bulk_group [%0, {%2, %3, %4, %5, %6}], [%1];"
                 ::"l"((uint64_t)map), "r"(src), "r"(c0), "r"(c1), "r"(c2), "r"(c3), "r"(c4) : "memory");
}
#define ELECT "{\n.reg .pred p;\nelect.sync _|p, 0xffffffff;\n@p "
__device__ __forceinline__ void e_expect_tx(uint32_t bar, uint32_t bytes) {
    asm volatile(ELECT "mbarrier.arrive.expect_tx.shared::cta.b64 _, [%0], %1;\n}" ::"r"(bar), "r"(bytes) : "memory");
}
__device__ __forceinline__ void e_arrive(uint32_t bar) {
    asm volatile(ELECT "mbarrier.arrive.shared::cta.b64 _, [%0];\n}" ::"r"(bar) : "memory");
}
__device__ __forceinline__ void e_load_4d(uint32_t dst, const CUtensorMap* map, uint32_t bar, int c0, int c1, int c2, int c3) {
    asm volatile(ELECT "cp.async.bulk.tensor.4d.shared::cluster.global.mbarrier::complete_tx::bytes [%0], [%1, {%3, %4, %5, %6}], [%2];\n}"
        ::"r"(dst), "l"((uint64_t)map), "r"(bar), "r"(c0), "r"(c1), "r"(c2), "r"(c3) : "memory");
}
__device__ __forceinline__ void e_load_5d(uint32_t dst, const CUtensorMap* map, uint32_t bar, int c0, int c1, int c2, int c3, int c4) {
    asm volatile(ELECT "cp.async.bulk.tensor.5d.shared::cluster.global.mbarrier::complete_tx::bytes [%0], [%1, {%3, %4, %5, %6, %7}], [%2];\n}"
        ::"r"(dst), "l"((uint64_t)map), "r"(bar), "r"(c0), "r"(c1), "r"(c2), "r"(c3), "r"(c4) : "memory");
}
__device__ __forceinline__ void e_bulk_load(uint32_t dst, const void* src, uint32_t bytes, uint32_t bar) {
    asm volatile(ELECT "cp.async.bulk.shared::cluster.global.mbarrier::complete_tx::bytes [%0], [%1], %2, [%3];\n}"
                 ::"r"(dst), "l"(src), "r"(bytes), "r"(bar) : "memory");
}
__device__ __forceinline__ void l2_prefetch(const void* p, uint32_t bytes) {
    asm volatile("cp.async.bulk.prefetch.L2.global [%0], %1;" ::"l"(p), "r"(bytes) : "memory");
}
__device__ __forceinline__ void l2_prefetch_4d(const CUtensorMap* map, int c0, int c1, int c2, int c3) {
    asm volatile("cp.async.bulk.prefetch.tensor.4d.L2.global [%0, {%1, %2, %3, %4}];" ::"l"((uint64_t)map), "r"(c0), "r"(c1), "r"(c2), "r"(c3) : "memory");
}
__device__ __forceinline__ void l2_prefetch_5d(const CUtensorMap* map, int c0, int c1, int c2, int c3, int c4) {
    asm volatile("cp.async.bulk.prefetch.tensor.5d.L2.global [%0, {%1, %2, %3, %4, %5}];" ::"l"((uint64_t)map), "r"(c0), "r"(c1), "r"(c2), "r"(c3), "r"(c4) : "memory");
}
__device__ __forceinline__ unsigned int ld_relaxed(const unsigned int* p) {
    unsigned int v;
    asm volatile("ld.relaxed.gpu.global.u32 %0, [%1];" : "=r"(v) : "l"(p) : "memory");
    return v;
}
__device__ __forceinline__ void fence_async_global() { asm volatile("fence.proxy.async.global;" ::: "memory"); }
__device__ __forceinline__ void wait_counter(const unsigned int* p, unsigned int target) {
    unsigned int v;
    int it = 0;
    do { asm volatile("ld.acquire.gpu.global.u32 %0, [%1];" : "=r"(v) : "l"(p) : "memory"); } while (v != target && ++it < (1 << 22));
    fence_async_global();
}
__device__ __forceinline__ void red_release(unsigned int* p, unsigned int n) {
    asm volatile("red.release.gpu.global.add.u32 [%0], %1;" ::"l"(p), "r"(n) : "memory");
}
__device__ __forceinline__ uint4 ldg128(const void* p) {
    uint4 v;
    asm volatile("ld.global.nc.v4.u32 {%0,%1,%2,%3}, [%4];" : "=r"(v.x), "=r"(v.y), "=r"(v.z), "=r"(v.w) : "l"(p));
    return v;
}
__device__ __forceinline__ void stg128(void* p, uint32_t a, uint32_t b, uint32_t c, uint32_t d) {
    asm volatile("st.global.v4.b32 [%0], {%1, %2, %3, %4};" ::"l"(p), "r"(a), "r"(b), "r"(c), "r"(d) : "memory");
}

template <int TA>
__device__ __forceinline__ void wgmma_n128(float (&d)[64], uint32_t alo, uint32_t blo, int acc) {
    asm volatile(
        "{\n.reg .pred p;\n.reg .b64 da, db;\nsetp.ne.b32 p, %67, 0;\nmov.b64 da, {%64, %69};\nmov.b64 db, {%65, %66};\n"
        "wgmma.mma_async.sync.aligned.m64n128k16.f32.bf16.bf16 "
        "{%0, %1, %2, %3, %4, %5, %6, %7, %8, %9, %10, %11, %12, %13, %14, %15, "
        "%16, %17, %18, %19, %20, %21, %22, %23, %24, %25, %26, %27, %28, %29, %30, %31, "
        "%32, %33, %34, %35, %36, %37, %38, %39, %40, %41, %42, %43, %44, %45, %46, %47, "
        "%48, %49, %50, %51, %52, %53, %54, %55, %56, %57, %58, %59, %60, %61, %62, %63}, "
        "da, db, p, 1, 1, %68, 0;\n"
        "}\n"
        : R8(d, 0), R8(d, 8), R8(d, 16), R8(d, 24), R8(d, 32), R8(d, 40), R8(d, 48), R8(d, 56)
        : "r"(alo), "r"(blo), "n"(HI128), "r"(acc), "n"(TA), "n"(TA ? HI64 : HI128));
}

constexpr int NST = 5;
constexpr int XTRA = SKEW1 - 4;
static_assert(SKEW1 >= 4 && SKEW1 <= 12, "skew");
constexpr int OFF_BB = 4 * 32768;
constexpr int OFF_CT = 5 * 32768;
constexpr int OFF_CU = OFF_CT + 32768;
__host__ __device__ constexpr uint32_t conv_buf(int p) { return OFF_CT + 16384 + (p == 3 ? 0 : p) * 16384; }
constexpr int OFF_PAR = OFF_CU + 32768;
constexpr int OFF_BAR = OFF_PAR + 2048;
constexpr int SMEM_BYTES = OFF_BAR + 896;
static_assert(SMEM_BYTES <= 232448, "smem layout");

static_assert(SLOT4 % 4 == 0 && SLOT4 <= 24, "ring");
constexpr uint32_t PH4 = (SLOT4 / 4 - 1) & 1;
__host__ __device__ constexpr int ring_slot(int kb) { return (kb - SLOT4 + 4) % 5; }
__host__ __device__ constexpr uint32_t ring_par(int kb) { return ((SLOT4 / 4 - 1 + (kb - SLOT4 + 4) / 5) & 1) ^ (ring_slot(kb) == 4 ? PH4 : 0); }

struct Maps {
    CUtensorMap x5, b4, cre, cim, sk, yt, yt3, out, kvst, bre, bim;
};

__device__ __forceinline__ void cmul(float& r, float& i, float ar, float ai, float br, float bi) {
    const float a = ar * br - ai * bi, b = ar * bi + ai * br;
    r = a; i = b;
}
__device__ __forceinline__ void csqr(float& r, float& i) { const float a = r * r - i * i, b = 2.f * r * i; r = a; i = b; }
__device__ __forceinline__ float after(float v, float dep) { return __float_as_uint(dep) == 0x7fedcba9u ? dep : v; }

template <int BMODE>
__global__ void __launch_bounds__(512, 1)
fused_kernel(const __nv_bfloat16* __restrict__ x, const __nv_bfloat16* __restrict__ b_re, const __nv_bfloat16* __restrict__ b_im,
             const __nv_bfloat16* __restrict__ kin, const __nv_bfloat16* __restrict__ vin, const __nv_bfloat16* __restrict__ ssm_k,
             const __nv_bfloat16* __restrict__ shift_k, const __nv_bfloat16* __restrict__ ssm_D,
             const __nv_bfloat16* __restrict__ lam_re, const __nv_bfloat16* __restrict__ lam_im,
             const __nv_bfloat16* __restrict__ log_dt, const __nv_bfloat16* __restrict__ gate_w,
             const __nv_bfloat16* __restrict__ dskip,
             const __nv_bfloat16* __restrict__ c_re, const __nv_bfloat16* __restrict__ c_im,
             const __grid_constant__ Maps maps) {
    constexpr bool MERGED = BMODE != 0, SW = BMODE == 2;
    extern __shared__ __align__(1024) unsigned char smem_raw[];
    const uint32_t sbase = smem_u32(smem_raw);
    const uint32_t bar_full = sbase + OFF_BAR;
    const uint32_t bar_empty = bar_full + 32;
    const uint32_t bar_full2 = bar_empty + 32;
    const uint32_t bar_empty2 = bar_full2 + 40;
    const uint32_t bar_k = bar_empty2 + 40;
    const uint32_t bar_tab = bar_k + 32;
    const uint32_t bar_ab = bar_tab + 8;
    const uint32_t bar_adone = bar_ab + 8;
    const uint32_t bar_par = bar_adone + 8;
    const uint32_t bar_y = bar_par + 8;
    const uint32_t bar_rel = bar_y + 8;
    const uint32_t bar_kvrel = bar_rel + 8;
    const uint32_t bar_yrel = bar_kvrel + 8;
    const uint32_t bar_y1 = bar_yrel + 8;
    const uint32_t bar_fh = bar_y1 + 8;
    const uint32_t bar_tick = bar_fh + 24;
    const uint32_t bar_stg = bar_tick + 104;
    const uint32_t bar_bias = bar_stg + 112;
    const uint32_t bar_hw = bar_bias + 16;
    const uint32_t bar_gate = bar_hw + 32;
    const uint32_t bar_g2 = bar_hw;
    const uint32_t w_bid = bar_full + 600, w_dsk = bar_full + 608, w_ones = bar_full + 640;
    const int tid = threadIdx.x ^ (((threadIdx.x + 128) & 256) ? 0 : 384);
    if (tid == 384) { prefetch_map(&maps.x5); prefetch_map(&maps.b4); }
    if (EPF && (threadIdx.x >> 5) - 1u < EPF && blockIdx.x < 128) {
        const int ln = threadIdx.x & 31;
        const __nv_bfloat16* p = ln < 16 ? x + (size_t)(blockIdx.x * 16 + ln) * D_DIM : ((ln & 8) ? b_im : b_re) + (size_t)(blockIdx.x * 8 + (ln & 7)) * D_DIM;
        asm volatile("prefetch.global.L2 [%0];" ::"l"(p + ((threadIdx.x >> 5) - 1) * 64) : "memory");
    }
    int bid;
    {
        unsigned int sm, nsm;
        asm volatile("mov.u32 %0, %smid;" : "=r"(sm));
        asm volatile("mov.u32 %0, %nsmid;" : "=r"(nsm));
        const int tpc = sm >> 1, q7 = ((tpc - 32) * 37) >> 8;
        const int gp = tpc < 32 ? tpc & 7 : tpc < 60 ? tpc - 31 - 7 * q7 : 0;
        const int ix = tpc < 32 ? tpc >> 3 : tpc < 60 ? q7 + 4 : ALTMAP ? (tpc - 56) ^ 2 : tpc - 58;
        bid = (ALTMAP ? tpc >= 64 : (tpc | 1) == 61) ? 128 : (4 * (gp >> 1) + (ix >> 1)) * 8 + 4 * (gp & 1) + 2 * (ix & 1) + (sm & 1);
        if (gridDim.x != 132 || nsm != 132) bid = blockIdx.x;
    }
    const int tt = bid >> 3, dt = bid & 7;
    const int ti = tt >> 1;
    const int cg = (dt >> 2) * 8 + (tt & 1) * 4 + (dt & 3);
    if (MERGED && threadIdx.x == 0 && bid < 128) {
        mbar_init(bar_full, 1);
        asm volatile("fence.mbarrier_init.release.cluster;" ::: "memory");
        mbar_expect_tx(bar_full, 49152);
        tma_load_4d(sbase + OFF_CU, &maps.b4, bar_full, 0, 0, 0, cg * 4);
        tma_load_5d(sbase + ((0 - XTRA) & 3) * 32768, &maps.x5, bar_full, 0, 0, 0, 0, ti);
        tma_load_4d(sbase + OFF_BB, &maps.b4, bar_full, 0, 0, 0, 64 + cg * 4);
    }
    __syncwarp();
    const int warp = __shfl_sync(0xffffffffu, tid >> 5, 0), wg = warp >> 2, lane = tid & 31;
    if (warp == 12 && bid < 128) {
        if (lane == 0) {
#pragma unroll
            for (int s = MERGED; s < 4; ++s) mbar_init(bar_full + 8 * s, 1);
            asm volatile("fence.mbarrier_init.release.cluster;" ::: "memory");
        }
        __syncwarp();
        asm volatile("bar.arrive 4, 512;" ::: "memory");
        if (MERGED) {
#pragma unroll 1
            for (int it = 1; it < 4; ++it) {
                e_expect_tx(bar_full + 8 * it, 49152);
                e_load_4d(sbase + OFF_CU + it * 8192, &maps.b4, bar_full + 8 * it, it * 64, 0, 0, cg * 4);
                e_load_5d(sbase + ((it - XTRA) & 3) * 32768, &maps.x5, bar_full + 8 * it, it * 64, 0, 0, 0, ti);
                e_load_4d(sbase + OFF_BB + it * 8192, &maps.b4, bar_full + 8 * it, it * 64, 0, 0, 64 + cg * 4);
            }
        }
    }
    if (bid >= 128) {
        if (tid == 0) {
            __nanosleep(2000);
            const unsigned int target = (ld_relaxed(&g_cnt[32 * 32]) & ~63u) + 64u;
            for (int i = 0; i < 8; ++i)
                for (int it = 0; ld_relaxed(&g_cnt[(40 + i) * 32]) != target && it < (1 << 12); ++it) __nanosleep(500);
        }
        return;
    }
    if (wg == 0) {
        asm volatile("setmaxnreg.dec.sync.aligned.u32 %0;" ::"n"(REG_P));
        if (tid == 32) {
            if (sbase & 1023) __trap();
#pragma unroll
            for (int s = 0; s < 4; ++s) mbar_init(bar_empty + 8 * s, 2);
#pragma unroll
            for (int s = 0; s < NST; ++s) { mbar_init(bar_full2 + 8 * s, 1); mbar_init(bar_empty2 + 8 * s, 1); }
            mbar_init(bar_k, 1); mbar_init(bar_k + 8, 1); mbar_init(bar_k + 16, 1); mbar_init(bar_k + 24, 1);
            mbar_init(bar_tab, 1);
            mbar_init(bar_ab, 1);
            mbar_init(bar_adone, 4);
            mbar_init(bar_par, 2);
            asm volatile("fence.mbarrier_init.release.cluster;" ::: "memory");
        } else if (tid == 64) {
#pragma unroll
            for (int s = 0; s < 21; ++s) mbar_init(bar_y + 8 * s, 1);
        } else if (tid == 96) {
#pragma unroll
            for (int s = 0; s < 11; ++s) mbar_init(bar_stg + 8 * s, 4);
        } else if (tid == 0) {
#pragma unroll
            for (int s = 11; s < 21; ++s) mbar_init(bar_stg + 8 * s, 4);
            asm volatile("st.shared.b32 [%0], %1;" ::"r"(w_bid), "r"(bid) : "memory");
        }
        __syncwarp();
        asm volatile("bar.sync 4, 512;" ::: "memory");
        if (warp == 0) {
#pragma unroll 1
            for (int it = MERGED ? 4 : 0; it < 16 + XTRA; ++it) {
                const int st = it & 3, kb = it < 16 ? it : it - SKEW1;
                const bool fa = it < 16, fb = it < 16 - SKEW1 || it >= 12;
                const uint32_t bf = bar_full + 8 * st;
                mbar_wait(bar_empty + 8 * st, ((it >> 2) & 1) ^ 1);
                e_expect_tx(bf, fa && fb ? 49152 : 40960);
                e_load_5d(sbase + ((it - XTRA) & 3) * 32768, &maps.x5, bf, kb * 64, 0, 0, 0, ti);
                if (MERGED) {
                    if (fa) e_load_4d(sbase + OFF_CU + st * 8192, &maps.b4, bf, kb * 64, 0, 0, cg * 4);
                    if (fb) e_load_4d(sbase + OFF_BB + st * 8192, &maps.b4, bf, kb * 64, 0, 0, 64 + cg * 4);
                } else {
                    if (lane < 16 && ((lane & 8) ? fb : fa))
                        tma_load_2d(sbase + ((lane & 8) ? OFF_BB : OFF_CU) + st * 8192 + (lane & 7) * 1024, (lane & 1) ? &maps.bim : &maps.bre, bf,
                                    kb * 64, (lane >> 3) * 512 + cg * 32 + ((lane & 7) >> 1) * 8);
                    __syncwarp();
                }
                if (it >= 4 && it < 16) e_arrive(bar_tick + 8 * (it - 3));
                if (lane == 0) STAMP(1, 16 + it);
                if (lane == 0 && it < 16) SAMPLE(it - 3);
            }
            int st = 0;
            uint32_t ph = 0;
#pragma unroll 1
            for (int kb = 0; kb < 32; ++kb) {
                const uint32_t bf = bar_full2 + 8 * st;
                mbar_wait(bar_empty2 + 8 * st, st == 4 ? ph ^ PH4 : ph);
                e_expect_tx(bf, 32768);
                e_load_5d(sbase + st * 32768 + 16384, &maps.cre + ((kb >> 3) & 1), bf, ((kb >> 4) * 8 + (kb & 7)) * 64, 0, 0, 0, dt * 4);
                if (lane == 0) STAMP(2, 16 + kb);
                if (lane == 0 && (kb & 3) == 0) SAMPLE(13 + (kb >> 2));
                if (++st == (kb < SLOT4 - 1 ? 4 : 5)) { st = 0; ph ^= 1; }
            }
        } else if (warp == 1) {
            if (MERGED && PFD && lane == 0) {
#pragma unroll 1
                for (int n = 0; n + PFD < 16; ++n) {
                    mbar_wait(bar_tick + 8 * n, 0);
                    if (cg >= 4 && max(cg - PFD, 0) == n) l2_prefetch_5d(&maps.x5, cg * 64, 0, 0, 0, ti);
                    if (ti >= 2 && max(2 * ti - PFD, 0) == n) {
#pragma unroll 1
                        for (int i = 0; i < 4; ++i) l2_prefetch_4d(&maps.b4, (2 * ti + (i >> 1)) * 64, 0, 0, (i & 1) * 64 + cg * 4);
                    }
                }
            }
            __syncwarp();
            const char* hp = reinterpret_cast<const char*>(g_H) + (size_t)tt * 262144;
            mbar_wait(bar_adone, 0);
            e_expect_tx(bar_k + 8, 16384);
            e_expect_tx(bar_k + 16, 16384);
#pragma unroll 1
            for (int c = 2; c < 6; ++c) {
                e_load_4d(sbase + conv_buf(0) + (c >> 1) * 16384 + (c & 1) * 4096 + 8192, &maps.sk, bar_k + 8 * (c >> 1), 0, 0, 0, bid * 8 + c);
                if (GAP_CV) __nanosleep(GAP_CV);
            }
            mbar_wait(bar_kvrel, 0);
            const unsigned int target = lds32(w_bid + 4);
            mbar_wait(bar_rel, 0);
            int st = 0;
            uint32_t ph = 0;
#pragma unroll 1
            for (int q = 0; q < 4; ++q) {
                if (lane == 0) STAMP(0, 8 + 2 * q);
                if (q == 0) wait_counter(&g_cnt[(4 * ti) * 32], target);
                else { mbar_wait(bar_fh + 8 * q - 8, 0); fence_async_global(); }
                if (lane == 0) STAMP(0, 9 + 2 * q);
#pragma unroll 1
                for (int kb = 0; kb < 8; ++kb) {
                    mbar_wait(bar_empty2 + 8 * st, st == 4 ? ph ^ PH4 : ph);
                    e_bulk_load(sbase + st * 32768, hp + kb * 16384, 16384, bar_full2 + 8 * st);
                    if (++st == (8 * q + kb < SLOT4 - 1 ? 4 : 5)) { st = 0; ph ^= 1; }
                }
                hp += (q & 1) ? 4194304 - 131072 : 131072;
            }
        } else if (warp == 2) {
            if (lane == 0) {
                mbar_wait(bar_tick + 8, 0);
                const unsigned int target = (ld_relaxed(&g_cnt[(40 + dt) * 32]) & ~63u) + 64u;
                asm volatile("st.shared.b32 [%0], %1;" ::"r"(w_bid + 4), "r"(target) : "memory");
                prefetch_map(&maps.kvst); prefetch_map(&maps.sk);
#pragma unroll 1
                for (int bt = 0; bt < 2; ++bt) {
                    mbar_wait(bar_stg + 8 * bt, 0);
#pragma unroll 1
                    for (int i = 0; i < 4; ++i) {
                        if (i) __nanosleep(GAP_ST);
                        tma_store_3d(&maps.kvst, sbase + OFF_CT + bt * 16384 + i * 4096, (tt & 1) * 1024 + ti * 128 + 64 * bt, dt * 16, 2 * i);
                    }
                    bulk_commit();
                }
                bulk_wait0();
                fence_async_global();
                red_release(&g_cnt[(40 + dt) * 32], 4);
                mbar_arrive(bar_kvrel);
                STAMP(0, 23);
                mbar_expect_tx(bar_tab, 12288);
                bulk_load(sbase + OFF_CT, &g_conv_tab, 12288, bar_tab);
                mbar_expect_tx(bar_k, 16384);
                tma_load_4d(sbase + conv_buf(0) + 8192, &maps.sk, bar_k, 0, 0, 0, bid * 8);
                tma_load_4d(sbase + conv_buf(0) + 12288, &maps.sk, bar_k, 0, 0, 0, bid * 8 + 1);
                wait_counter(&g_cnt[(40 + (bid >> 4)) * 32], target);
                STAMP(0, 19);
#pragma unroll 1
                for (int p = 0; p < 3; ++p) {
                    if (p == 1) mbar_wait(bar_adone, 0);
                    bulk_load(sbase + conv_buf(p), g_kvT + (size_t)(bid * 8 + 2 * p) * 2048, 8192, bar_k + 8 * p);
                    if (GAP_CV) __nanosleep(GAP_CV);
                }
                prefetch_map(&maps.out); prefetch_map(&maps.yt); prefetch_map(&maps.yt3);
#pragma unroll 1
                for (int p = 0; p < 4; ++p) {
                    mbar_wait(bar_stg + 16 + 8 * p, 0);
                    if (p == 0) {
                        mbar_expect_tx(bar_k + 24, 16384);
                        tma_load_4d(sbase + conv_buf(3) + 8192, &maps.sk, bar_k + 24, 0, 0, 0, bid * 8 + 6);
                        mbar_wait(bar_g2, 0);
                        tma_load_4d(sbase + conv_buf(3) + 12288, &maps.sk, bar_k + 24, 0, 0, 0, bid * 8 + 7);
                    }
#pragma unroll 1
                    for (int i = 0; i < 2; ++i) {
                        if (i) __nanosleep(GAP_Y);
                        asm volatile("cp.async.bulk.global.shared::cta.bulk_group [%0], [%1], 4096;"
                                     ::"l"(g_y2 + (size_t)(bid * 8 + 2 * p + i) * 2048), "r"(sbase + conv_buf(p) + i * 4096) : "memory");
                    }
                    bulk_commit();
                    STAMP(0, 24 + p);
                    if (p == 0) {
                        bulk_wait_read0();
                        bulk_load(sbase + conv_buf(3), g_kvT + (size_t)(bid * 8 + 6) * 2048, 8192, bar_k + 24);
                    }
                    if (p == 2) {
                        bulk_wait0();
                        fence_async_global();
                        red_release(&g_cnt[(48 + (bid >> 4)) * 32], 4);
                        mbar_arrive(bar_yrel);
                        STAMP(0, 3);
                    }
                }
                bulk_wait0();
                fence_async_global();
                red_release(&g_cnt[(32 + (bid >> 4)) * 32], 4);
                STAMP(0, 2);
                wait_counter(&g_cnt[(32 + dt) * 32], target);
                STAMP(0, 5);
                mbar_expect_tx(bar_y, 8192);
#pragma unroll 1
                for (int i = 6; i < 8; ++i)
                    tma_load_5d(sbase + OFF_CU + i * 4096, &maps.yt, bar_y, (tt & 1) * 1024 + ti * 128 + (i & 1) * 64, 0, 0, i >> 1, dt * 4);
#pragma unroll 1
                for (int i = 0; i < 8; ++i) {
                    mbar_wait(bar_stg + 48 + 8 * i, 0);
                    tma_store_5d(&maps.out, sbase + ((i & 4) ? OFF_CT : OFF_CU) + (i & 3) * 8192, dt * 128 + (i & 3) * 32, 0, 0, (tt & 1) * 4 + ((i & 4) >> 1), ti);
                    bulk_commit();
                }
                bulk_wait_read0();
                STAMP(2, 3);
                SAMPLE(21);
            }
        } else if (lane == 0) {
            mbar_wait(bar_tick + 8 * TK_PF0, 0);
#pragma unroll 1
            for (int i = 0; i < 8; ++i) {
                l2_prefetch(((i & 1) ? vin : kin) + (size_t)(ti * 256 + 32 * (i & 4) + (bid & 15) * 8 + 2 * (i & 2)) * D_DIM, 8192);
                __nanosleep(GAP_PF);
            }
            if (bid < 3) l2_prefetch(reinterpret_cast<const char*>(&g_conv_tab) + bid * 4096, 4096);
            prefetch_map(&maps.cre); prefetch_map(&maps.cim);
            mbar_wait(bar_tick + 8 * TK_C, 0);
#pragma unroll 1
            for (int i = 0; i < 8; ++i) {
                l2_prefetch((i & 1) ? ((i & 4) ? c_im : c_re) + (size_t)bid * 8192 + (i & 2) * 2048 : ssm_k + (size_t)bid * 16384 + (i >> 1) * 4096, 8192);
                __nanosleep(GAP_PF);
            }
            const unsigned int target = (ld_relaxed(&g_cnt[(4 * ti + 1) * 32]) & ~63u) + 64u;
            mbar_wait(bar_gate, 0);
#pragma unroll 1
            for (int q = 1; q < 4; ++q) {
                if (q < 3) mbar_wait(bar_hw + 8 * q, 0);
                if (q > 1) {
                    mbar_wait(bar_g2, 0);
                    char* hp = reinterpret_cast<char*>(g_H) + (size_t)((16 + 2 * ti) * 16 + (q & 1) * 8 + (cg >> 1)) * 16384 + (cg & 1) * 2048;
#pragma unroll 1
                    for (int i = 0; i < 8; ++i) {
                        asm volatile("cp.async.bulk.global.shared::cta.bulk_group [%0], [%1], 2048;"
                                     ::"l"(hp + (i & 3) * 4096 + (i >> 2) * 262144), "r"(sbase + OFF_BB + (q & 1) * 16384 + i * 2048) : "memory");
                        __nanosleep(GAP_HB);
                    }
                    bulk_commit();
                    wait_counter(&g_cnt[(4 * ti + q - 1) * 32], target);
                    mbar_arrive(bar_fh + 8 * q - 16);
                    bulk_wait0();
                    if (q == 3) mbar_arrive(bar_empty2 + 32);
                    fence_async_global();
                }
                red_release(&g_cnt[(4 * ti + q) * 32], 4);
                STAMP(0, 36 + q);
                if (q == 3) {
                    wait_counter(&g_cnt[(4 * ti + q) * 32], target);
                    mbar_arrive(bar_fh + 8 * q - 8);
                }
            }
        }
    } else {
    if (wg == 3) {
        if (warp != 12) asm volatile("bar.sync 4, 512;" ::: "memory");
        named_bar(3, 128);
        asm volatile("setmaxnreg.inc.sync.aligned.u32 %0;" ::"n"(REG_C));
        const int t = tid & 127, w4 = t >> 5;
        if (t == 0) SAMPLE(0);
        mbar_wait(bar_tick, 0);
        if (t < 64) {
            const int ch = (t >> 5) * 512 + cg * 32 + (t & 31);
            unsigned long long oldagg;
            asm volatile("ld.relaxed.gpu.global.u64 %0, [%1];" : "=l"(oldagg) : "l"(&g_agg[ti * D_DIM + ch]) : "memory");
            const float Lr = __bfloat162float(lam_re[ch]), Li = __bfloat162float(lam_im[ch]);
            const float dtv = bf16r(expf(__bfloat162float(log_dt[ch])));
            const unsigned int tag = ((((unsigned int)oldagg & 1u) | ((unsigned int)(oldagg >> 31) & 2u)) + 1u) & 3u;
            const float er = expf(dtv * Lr);
            float s, c;
            sincospif(dtv * Li * 0.318309886183790672f, &s, &c);
            const float lr = er * c, li = er * s;
            const float nr = lr - 1.f, ni = li;
            const float den = Lr * Lr + Li * Li;
            const float cr = 2.f * (nr * Lr + ni * Li) / den, ci = 2.f * (ni * Lr - nr * Li) / den;
            float pr = lr, pi = -li;
#pragma unroll
            for (int i = 0; i < 5; ++i) csqr(pr, pi);
            sts128(sbase + OFF_PAR + t * 32, __float_as_uint(lr), __float_as_uint(-li), __float_as_uint(cr), __float_as_uint(ci));
            sts128(sbase + OFF_PAR + t * 32 + 16, __float_as_uint(pr), __float_as_uint(pi), tag, 0);
            __syncwarp();
            if (lane == 0) mbar_arrive(bar_par);
        }
        if (t >= 120) asm volatile("st.shared.b32 [%0], %1;" ::"r"(w_dsk - 480 + 4 * t),
                                   "r"(t < 124 ? __ldg(reinterpret_cast<const uint32_t*>(ssm_D + bid * 8) + (t & 3)) : 0u) : "memory");
        if (t < 64) asm volatile("st.shared.b32 [%0], %1;" ::"r"(w_ones + 4 * t), "r"(0x3F803F80u) : "memory");
        {
            const int cq = lane & 15, rg = (lane >> 4) + 2 * w4;
            uint32_t sk[4][4];
#pragma unroll
            for (int c = 0; c < 4; ++c) {
                const uint4 w = ldg128(shift_k + (size_t)(dt * 128 + 8 * cq + 2 * c) * 4);
                sk[0][c] = __byte_perm(w.x, w.z, 0x5410); sk[1][c] = __byte_perm(w.x, w.z, 0x7632);
                sk[2][c] = __byte_perm(w.y, w.w, 0x5410); sk[3][c] = __byte_perm(w.y, w.w, 0x7632);
            }
#pragma unroll 1
            for (int bt = 0; bt < 2; ++bt) {
                const int t0 = ti * 256 + 128 * bt + 16 * (rg & 4) + 32 * (tt & 1) + 8 * (rg & 3);
                mbar_wait(bar_tick + 8 * (bt ? TK_KV1 : TK_KV0), 0);
                if (t == 0) STAMP(0, 30 + 3 * bt);
                uint4 kk[11], vv[8];
                const __nv_bfloat16* kp = kin + (size_t)t0 * D_DIM + dt * 128 + 8 * cq;
                const __nv_bfloat16* vp = vin + (size_t)t0 * D_DIM + dt * 128 + 8 * cq;
#pragma unroll
                for (int i = 0; i < 11; ++i) {
                    if (i < 3 && t0 == 0) kk[i] = make_uint4(0, 0, 0, 0);
                    else kk[i] = ldg128(kp + (i - 3) * D_DIM);
                    if (i == 6 || i == 10) __nanosleep(GAP_KV);
                }
#pragma unroll
                for (int i = 0; i < 8; ++i) { vv[i] = ldg128(vp + i * D_DIM); if (i == 3) __nanosleep(GAP_KV); }
                const uint32_t ua = sbase + OFF_CT + bt * 16384 + cq * 128 + ((rg ^ ((2 * ti + bt) & 3) ^ (cq & 7)) << 4);
#pragma unroll
                for (int c = 0; c < 4; ++c) {
                    uint32_t res[8];
#pragma unroll
                    for (int i = 0; i < 8; ++i) {
                        uint32_t ks = hmul((&kk[i].x)[c], sk[3][c]);
                        ks = hadd(ks, hmul((&kk[i + 1].x)[c], sk[2][c]));
                        ks = hadd(ks, hmul((&kk[i + 2].x)[c], sk[1][c]));
                        ks = hadd(ks, hmul((&kk[i + 3].x)[c], sk[0][c]));
                        res[i] = hmul(ks, (&vv[i].x)[c]);
                    }
                    sts128(ua + (2 * c) * 2048, __byte_perm(res[0], res[1], 0x5410), __byte_perm(res[2], res[3], 0x5410),
                           __byte_perm(res[4], res[5], 0x5410), __byte_perm(res[6], res[7], 0x5410));
                    sts128(ua + (2 * c + 1) * 2048, __byte_perm(res[0], res[1], 0x7632), __byte_perm(res[2], res[3], 0x7632),
                           __byte_perm(res[4], res[5], 0x7632), __byte_perm(res[6], res[7], 0x7632));
                }
                fence_async_smem();
                __syncwarp();
                if (lane == 0) mbar_arrive(bar_stg + 8 * bt);
                if (t == 0) STAMP(0, 21 + bt);
            }
        }
        {
            const int row = bid * 16 + (t >> 3);
            uint4 xv[16];
#pragma unroll
            for (int n = 0; n < 16; ++n) {
                xv[n] = ldg128(x + (size_t)row * D_DIM + ((t & 7) + 8 * n) * 8);
                if ((n & 3) == 3) __nanosleep(GAP_KV);
            }
#pragma unroll
            for (int n8 = 0; n8 < 16; n8 += 8) {
                uint4 wv[8];
#pragma unroll
                for (int n = 0; n < 8; ++n) wv[n] = ldg128(gate_w + ((t & 7) + 8 * (n8 + n)) * 8);
#pragma unroll
                for (int n = 0; n < 8; ++n) {
                    uint4& p = xv[n8 + n];
                    p.x = hmul(p.x, wv[n].x); p.y = hmul(p.y, wv[n].y); p.z = hmul(p.z, wv[n].z); p.w = hmul(p.w, wv[n].w);
                }
            }
            float d[4] = {0.f, 0.f, 0.f, 0.f};
            fence_regs(d);
            named_bar(3, 128);
            wgmma_fence();
#pragma unroll
            for (int n = 0; n < 16; ++n)
                asm volatile("{\n.reg .b64 db;\nmov.b64 db, {%8, 8};\n"
                             "wgmma.mma_async.sync.aligned.m64n8k16.f32.bf16.bf16 {%0, %1, %2, %3}, {%4, %5, %6, %7}, db, 1, 1, 1, 0;\n}\n"
                             : "+f"(d[0]), "+f"(d[1]), "+f"(d[2]), "+f"(d[3]) : "r"(xv[n].x), "r"(xv[n].y), "r"(xv[n].z), "r"(xv[n].w), "r"(desc_lo(w_ones, 128)));
            wgmma_commit();
            wgmma_wait<0>();
            fence_regs(d);
#pragma unroll
            for (int n = 0; n < 16; ++n) asm volatile("" ::"r"(xv[n].x), "r"(xv[n].y), "r"(xv[n].z), "r"(xv[n].w) : "memory");
            float sum = d[0] + d[2];
            sum += __shfl_xor_sync(0xffffffffu, sum, 4);
            if ((t & 7) == 0) g_gate[row] = bf16r(1.f / (1.f + expf(-bf16r(sum))));
            if (t == 0) STAMP(0, 4);
            __syncwarp();
            if (lane == 0) mbar_arrive(bar_gate);
        }
    } else {
        asm volatile("setmaxnreg.inc.sync.aligned.u32 %0;" ::"n"(REG_AB));
        if (tid == 128) STAMP(1, 54);
        asm volatile("bar.sync 4, 512;" ::: "memory");
        if (tid == 128) STAMP(1, 55);
        const int cw = wg - 1;
        const int t = tid & 127, w4 = t >> 5, g = lane >> 2, t4 = lane & 3;
        {
            float a0[64], a1[64];
            auto release = [&](int it) {
                if (it < 12 + XTRA && t <= ((it >= 16 - SKEW1 && it < 12) || it >= 16)) mbar_arrive(bar_empty + 8 * (it & 3));
            };
#pragma unroll 1
            for (int kb = 0; kb < 16; ++kb) {
                const int it = cw == 1 && kb >= 16 - SKEW1 ? kb + XTRA : kb, st = it & 3;
                if (cw == 1 && kb == 16 - SKEW1) mbar_wait(bar_ab, 0);
                mbar_wait(bar_full + 8 * st, (it >> 2) & 1);
                if (kb == 0 && tid == 288) mbar_arrive(bar_tick);
                if (kb == 0 && t == 0) STAMP(1, 14 + cw);
                const uint32_t alo = desc_lo(sbase + (cw ? OFF_BB : OFF_CU) + st * 8192, 16), blo = desc_lo(sbase + ((it - XTRA) & 3) * 32768, 16);
                wgmma_fence();
#pragma unroll
                for (int k = 0; k < 4; ++k) {
                    wgmma_n128<0>(a0, alo + 2 * k, blo + 2 * k, k ? 1 : kb);
                    wgmma_n128<0>(a1, alo + 2 * k, blo + 1024 + 2 * k, k ? 1 : kb);
                }
                wgmma_commit();
                wgmma_wait<1>();
                if (kb > 0 && !(cw == 1 && kb == 16 - SKEW1)) release(it - 1);
                if (cw == 1 && kb == 15 - SKEW1) {
                    wgmma_wait<0>();
                    release(it);
                }
                if (cw == 1 && kb > 12) {
                    if (kb == 13) mbar_wait(bar_adone, 0);
                    if (t == 0) mbar_arrive(bar_empty2 + 8 * (kb - 13));
                }
            }
            if (tid == 192) mbar_arrive(bar_ab);
            float mr, mi, cr, ci, p32r, p32i;
            uint32_t tag;
            mbar_wait(bar_par, 0);
            {
                const uint32_t par = sbase + OFF_PAR + (cw * 32 + w4 * 8 + g) * 32;
                uint32_t dummy;
                asm volatile("ld.shared.v4.f32 {%0,%1,%2,%3}, [%4];" : "=f"(mr), "=f"(mi), "=f"(cr), "=f"(ci) : "r"(par));
                asm volatile("ld.shared.v4.b32 {%0,%1,%2,%3}, [%4];" : "=f"(p32r), "=f"(p32i), "=r"(tag), "=r"(dummy) : "r"(par + 16));
            }
            const float l1i = SW ? mi : -mi;
            auto map = [&](float p, float q, float& r, float& i) {
                if (SW) { r = fmaf(cr, q, -ci * p); i = fmaf(-cr, p, -ci * q); }
                else { r = fmaf(cr, p, -ci * q); i = fmaf(-cr, q, -ci * p); }
            };
            float p64r = p32r, p64i = p32i;
            csqr(p64r, p64i);
            float p128r = p64r, p128i = p64i;
            csqr(p128r, p128i);
            wgmma_wait<0>();
            fence_regs(a0); fence_regs(a1);
            if (cw == 0) { release(15); if (lane == 0) mbar_arrive(bar_adone); }
            else if (t == 0) mbar_arrive(bar_empty2 + 24);
            if (t == 0) STAMP(1, 2 + 6 * cw);
            float hr = 0.f, hi = 0.f, ar = 0.f, ai = 0.f;
#pragma unroll
            for (int j = 0; j < 16; ++j)
#pragma unroll
                for (int e = 0; e < 2; ++e) {
                    const float nr = fmaf(mr, ar, fmaf(-l1i, ai, a0[4 * j + e])), ni = fmaf(mr, ai, fmaf(l1i, ar, a0[4 * j + 2 + e]));
                    const float or_ = fmaf(mr, hr, fmaf(-l1i, hi, a1[4 * j + e])), oi = fmaf(mr, hi, fmaf(l1i, hr, a1[2 + 4 * j + e]));
                    ar = nr; ai = ni; hr = or_; hi = oi;
                }
            map(ar, ai, ar, ai);
            map(hr, hi, hr, hi);
            hr += p32r * ar - p32i * ai; hi += p32r * ai + p32i * ar;
            {
                float vr = __shfl_up_sync(0xffffffffu, hr, 1, 4), vi = __shfl_up_sync(0xffffffffu, hi, 1, 4);
                if (t4 >= 1) { hr += p64r * vr - p64i * vi; hi += p64r * vi + p64i * vr; }
                vr = __shfl_up_sync(0xffffffffu, hr, 2, 4); vi = __shfl_up_sync(0xffffffffu, hi, 2, 4);
                if (t4 >= 2) { hr += p128r * vr - p128i * vi; hi += p128r * vi + p128i * vr; }
            }
            unsigned long long* ap = &g_agg[ti * D_DIM + cw * 512 + cg * 32 + w4 * 8 + g];
            if (t4 == 3) asm volatile("{\n.reg .b64 a;\nmov.b64 a, {%1, %2};\nst.relaxed.gpu.global.u64 [%0], a;\n}\n" ::"l"(ap),
                                      "r"((__float_as_uint(hr) & ~1u) | (tag & 1u)), "r"((__float_as_uint(hi) & ~1u) | (tag >> 1)) : "memory");
            float exr = __shfl_up_sync(0xffffffffu, hr, 1, 4), exi = __shfl_up_sync(0xffffffffu, hi, 1, 4);
            if (t4 == 0) { exr = 0.f; exi = 0.f; }
            if (t == 0) STAMP(1, 3 + 6 * cw);
            ci = after(ci, exr);
#pragma unroll
            for (int j = 0; j < 16; ++j)
#pragma unroll
                for (int e = 0; e < 2; ++e) {
                    map(a0[4 * j + e], a0[4 * j + 2 + e], a0[4 * j + e], a0[4 * j + 2 + e]);
                    map(a1[4 * j + e], a1[4 * j + 2 + e], a1[4 * j + e], a1[4 * j + 2 + e]);
                }
            float qr = 1.f, qi = 0.f, ur = 1.f, ui = 0.f;
            if (t4 & 1) { qr = p64r; qi = p64i; }
            if (t4 & 2) cmul(qr, qi, qr, qi, p128r, p128i);
            csqr(p128r, p128i);
            if (t4 & 1) { ur = p128r; ui = p128i; }
            csqr(p128r, p128i);
            if (t4 & 2) cmul(ur, ui, ur, ui, p128r, p128i);
            csqr(p128r, p128i);
            fence_regs(a0); fence_regs(a1);
            if (t == 0) STAMP(1, 7 + 6 * cw);
            if (ti > 0) {
                const unsigned long long tmask = 0x0000000100000001ull, tval = ((unsigned long long)(tag >> 1) << 32) | (tag & 1u);
                unsigned long long u0 = tval, u1 = tval;
                ap -= D_DIM * (1 + t4);
                int it = 0;
                do {
                    asm volatile("{\n.reg .pred p, q;\nsetp.gt.s32 p, %3, 0;\nsetp.gt.s32 q, %3, 4;\n@p ld.relaxed.gpu.global.u64 %0, [%2];\n"
                                 "@q ld.relaxed.gpu.global.u64 %1, [%2+-32768];\n}\n" : "+l"(u0), "+l"(u1) : "l"(ap), "r"(ti - t4) : "memory");
                } while (__any_sync(0xffffffffu, (((u0 ^ tval) | (u1 ^ tval)) & tmask) != 0) && ++it < (1 << 22));
                float Pr = __uint_as_float((unsigned)u1 & ~1u), Pi = __uint_as_float((unsigned)(u1 >> 32) & ~1u);
                cmul(Pr, Pi, Pr, Pi, p128r, p128i);
                Pr += __uint_as_float((unsigned)u0 & ~1u); Pi += __uint_as_float((unsigned)(u0 >> 32) & ~1u);
                cmul(Pr, Pi, Pr, Pi, ur, ui);
                Pr += __shfl_xor_sync(0xffffffffu, Pr, 1); Pi += __shfl_xor_sync(0xffffffffu, Pi, 1);
                Pr += __shfl_xor_sync(0xffffffffu, Pr, 2); Pi += __shfl_xor_sync(0xffffffffu, Pi, 2);
                exr += qr * Pr - qi * Pi;
                exi += qr * Pi + qi * Pr;
            }
            if (t == 0) STAMP(1, 4 + 6 * cw);
            char* hp = reinterpret_cast<char*>(g_H) + (size_t)((2 * ti) * 16 + (cg >> 1)) * 16384 + ((cg & 1) * 32 + w4 * 8 + g) * 64 + ((t4 ^ (g >> 1)) << 4);
            float fxr = ar + p32r * exr - p32i * exi, fxi = ai + p32r * exi + p32i * exr;
            const uint32_t hs = sbase + OFF_BB + (w4 * 8 + g) * 64 + ((t4 ^ (g >> 1)) << 4);
            if (cw == 1) named_bar(2, 128);
            uint32_t im[32];
#pragma unroll
            for (int jj = 0; jj < 4; ++jj) {
                uint32_t pr[4], qq[4];
#pragma unroll
                for (int j4 = 0; j4 < 4; ++j4) {
                    const int j = jj * 4 + j4;
                    const float r0 = fmaf(mr, exr, fmaf(-mi, exi, a0[4 * j])), i0 = fmaf(mr, exi, fmaf(mi, exr, a0[4 * j + 2]));
                    const float r1 = fmaf(mr, fxr, fmaf(-mi, fxi, a1[4 * j])), i1 = fmaf(mr, fxi, fmaf(mi, fxr, a1[2 + 4 * j]));
                    exr = fmaf(mr, r0, fmaf(-mi, i0, a0[4 * j + 1]));
                    exi = fmaf(mr, i0, fmaf(mi, r0, a0[4 * j + 3]));
                    fxr = fmaf(mr, r1, fmaf(-mi, i1, a1[1 + 4 * j]));
                    fxi = fmaf(mr, i1, fmaf(mi, r1, a1[3 + 4 * j]));
                    pr[j4] = pack_bf16(r0, exr); im[j] = pack_bf16(i0, exi);
                    qq[j4] = pack_bf16(r1, fxr); im[16 + j] = pack_bf16(i1, fxi);
                }
                if (cw == 0) {
                    stg128(hp + jj * 4096, pr[0], pr[1], pr[2], pr[3]);
                    stg128(hp + jj * 4096 + 262144, qq[0], qq[1], qq[2], qq[3]);
                } else {
                    sts128(hs + jj * 2048, pr[0], pr[1], pr[2], pr[3]);
                    sts128(hs + jj * 2048 + 8192, qq[0], qq[1], qq[2], qq[3]);
                }
            }
            if (t == 0) STAMP(1, 5 + 6 * cw);
            if (cw == 0) {
                named_bar(1, 128);
                if (t == 0) { red_release(&g_cnt[(4 * ti) * 32], 4); mbar_arrive(bar_rel); }
                named_bar(1, 128);
                if (t == 0) STAMP(1, 6);
#pragma unroll
                for (int jj = 0; jj < 8; ++jj) stg128(hp + 131072 + (jj & 3) * 4096 + (jj >> 2) * 262144, im[4 * jj], im[4 * jj + 1], im[4 * jj + 2], im[4 * jj + 3]);
            } else {
#pragma unroll
                for (int jj = 0; jj < 8; ++jj) sts128(hs + 16384 + jj * 2048, im[4 * jj], im[4 * jj + 1], im[4 * jj + 2], im[4 * jj + 3]);
                fence_async_smem();
            }
            __syncwarp();
            if (lane == 0) mbar_arrive(bar_hw + 8 * cw + 8);
            if (t == 0) STAMP(1, 50 + cw);
        }
        if (cw == 0) {
            float c0[64], c1[64];
            int st = 0, pst = 0;
            uint32_t ph = 0;
            auto kblock = [&](int kb, auto shallow) {
                const int t = fresh_tid() & 127, lane = t & 31;
                mbar_wait(bar_full2 + 8 * st, st == 4 ? ph ^ PH4 : ph);
                if (kb == 0 && t == 0) STAMP(2, 6);
                if (kb == 0 && lane == 0) mbar_arrive(bar_g2);
                const uint32_t alo = desc_lo(sbase + st * 32768, 4096), blo = desc_lo(sbase + st * 32768 + 16384, 16);
                constexpr int Q = decltype(shallow)::value;
#pragma unroll
                for (int j = 0; j < 8; ++j) {
                    wgmma_fence();
                    if (j & 1) wgmma_n128<1>(c1, alo + 512 + 64 * (j >> 1), blo + 2 * (j >> 1), j >> 1 ? 1 : kb);
                    else wgmma_n128<1>(c0, alo + 64 * (j >> 1), blo + 2 * (j >> 1), j >> 1 ? 1 : kb);
                    wgmma_commit();
                    wgmma_wait<Q>();
                    if (j == Q - 1 && kb > 0 && t == 0) mbar_arrive(bar_empty2 + 8 * pst);
                }
                pst = st;
                if (++st == (kb < SLOT4 - 1 ? 4 : 5)) { st = 0; ph ^= 1; }
            };
#pragma unroll 1
            for (int kb = 0; kb < QKB; ++kb) kblock(kb, std::integral_constant<int, QD>());
#pragma unroll 1
            for (int kb = QKB; kb < 32 - SKEW2; ++kb) kblock(kb, std::integral_constant<int, QD2>());
            static_assert(SKEW2 <= 4, "slot release");
            const uint32_t alo = desc_lo(sbase, 4096), blo = desc_lo(sbase + 16384, 16);
#pragma unroll
            for (int kb = 32 - SKEW2; kb < 32; ++kb) {
                mbar_wait(bar_full2 + 8 * ring_slot(kb), ring_par(kb));
                wgmma_fence();
#pragma unroll
                for (int k = 0; k < 4; ++k) wgmma_n128<1>(c0, alo + ring_slot(kb) * 2048 + 64 * k, blo + ring_slot(kb) * 2048 + 2 * k, 1);
                wgmma_commit();
            }
            auto late = [&](int kb) {
                wgmma_fence();
#pragma unroll
                for (int k = 0; k < 4; ++k) wgmma_n128<1>(c1, alo + 512 + ring_slot(kb) * 2048 + 64 * k, blo + ring_slot(kb) * 2048 + 2 * k, 1);
                wgmma_commit();
            };
            late(32 - SKEW2);
            const int t = fresh_tid() & 127, lane = t & 31, w4 = t >> 5, g = lane >> 2, t4 = lane & 3;
            auto epilogue = [&](const float (&a)[64], int b) {
                const uint32_t ad0 = sbase + (b ? OFF_CT : OFF_CU) + (w4 * 16 + g) * 128 + (((2 * t4) ^ g) << 4);
                float gt[2];
                uint32_t bv[4][4];
#pragma unroll
                for (int h = 0; h < 2; ++h) gt[h] = __uint_as_float(lds32(sbase + OFF_PAR + (64 * b + 16 * w4 + 8 * h + g) * 4));
#pragma unroll
                for (int i = 0; i < 4; ++i)
                    asm volatile("ld.shared.v4.b32 {%0,%1,%2,%3}, [%4];" : "=r"(bv[i][0]), "=r"(bv[i][1]), "=r"(bv[i][2]), "=r"(bv[i][3])
                                 : "r"(ad0 + (i & 1) * 1024 + (i >> 1) * 8192) : "memory");
                if (b == 0) wgmma_wait<1>(); else wgmma_wait<0>();
                if (b == 0) fence_regs(c0); else fence_regs(c1);
                if (t == 0) STAMP(2, b ? 2 : 5);
#pragma unroll
                for (int jq = 0; jq < 4; ++jq) {
#pragma unroll
                    for (int h = 0; h < 2; ++h) {
                        const uint32_t ad = ad0 + h * 1024 + jq * 8192;
                        uint32_t (&w)[4] = bv[2 * (jq & 1) + h];
                        const int r = 16 * jq + 2 * h;
                        sts128(ad, __float_as_uint(fmaf(gt[h], a[r], bf_lo(w[0]))), __float_as_uint(fmaf(gt[h], a[r + 1], bf_hi(w[0]))),
                               __float_as_uint(fmaf(gt[h], a[r + 4], bf_lo(w[1]))), __float_as_uint(fmaf(gt[h], a[r + 5], bf_hi(w[1]))));
                        sts128(ad ^ 16, __float_as_uint(fmaf(gt[h], a[r + 8], bf_lo(w[2]))), __float_as_uint(fmaf(gt[h], a[r + 9], bf_hi(w[2]))),
                               __float_as_uint(fmaf(gt[h], a[r + 12], bf_lo(w[3]))), __float_as_uint(fmaf(gt[h], a[r + 13], bf_hi(w[3]))));
                        if (jq < 2) asm volatile("ld.shared.v4.b32 {%0,%1,%2,%3}, [%4];" : "=r"(w[0]), "=r"(w[1]), "=r"(w[2]), "=r"(w[3]) : "r"(ad + 16384) : "memory");
                    }
                    fence_async_smem();
                    __syncwarp();
                    if (lane == 0) mbar_arrive(bar_stg + 48 + 32 * b + 8 * jq);
                    if (b == 0 && jq < SKEW2 - 1) late(33 - SKEW2 + jq);
                }
            };
            mbar_wait(bar_bias, 0);
            if (t == 0) STAMP(2, 4);
            epilogue(c0, 0);
            mbar_wait(bar_bias + 8, 0);
            epilogue(c1, 1);
            if (t == 0) STAMP(2, 7);
            return;
        }
        asm volatile("setmaxnreg.dec.sync.aligned.u32 %0;" ::"n"(REG_C));
    }
    {
        {
            const int t = fresh_tid() & 127, lane = t & 31, w4 = t >> 5;
            Twiddle tw;
            load_twiddle(tw, reinterpret_cast<const uint4*>(g_tw_tab.w) + t);
            const uint32_t lo = (uint32_t)((16 * w4 + (lane & 7)) * 64 + (((lane >> 3) ^ ((lane >> 1) & 3)) << 4));
            const uint32_t tlo = desc_lo(sbase + OFF_CT, 16);
            float dE[32], dO[32];
            int p = wg == 2 ? 2 : 0;
            mbar_wait(bar_stg, 0);
            mbar_wait(bar_tab, 0);
            mbar_wait(bar_k + 8 * p, 0);
            if (t == 0) STAMP(0, wg == 2 ? 50 : 1);
            wgmma_fence();
            conv_s1(dE, dO, tlo, desc_lo(sbase + conv_buf(0) + p * 16384, 8192));
            wgmma_commit();
            wgmma_wait<0>();
            fence_regs(dE); fence_regs(dO);
            named_bar(wg, 128);
#pragma unroll 1
            for (; p < 4; p = 2 * p + 1) {
                const int pn = p < 2 ? 2 * p + 1 : p;
                if (t == 0) STAMP(0, 40 + 2 * p);
                conv_pair(dE, dO, tw, lds32(w_dsk + ((lane & 3) ? 16 : 4 * p)), tlo, sbase + conv_buf(p), sbase + conv_buf(pn), lo, wg,
                                [&]() { mbar_wait(bar_k + 8 * pn, 0); });
                if (lane == 0) mbar_arrive(bar_stg + 16 + 8 * p);
            }
            if (t == 0) STAMP(0, 57 + wg);
            __syncwarp();
        }
        if (wg == 2) {
            {
            const int t = fresh_tid() & 127, lane = t & 31, w4 = t >> 5, g = lane >> 2, t4 = lane & 3;
            const int bid = lds32(w_bid), dt = bid & 7;
            const int trow = (bid >> 4) * 256 + 4 * (bid & 8) + 128 * (w4 & 1) + 8 * (w4 >> 1) + g;
            uint4 xv[16], dk[4];
            const __nv_bfloat16* xp = x + (size_t)trow * D_DIM + dt * 128 + 8 * t4;
#pragma unroll
            for (int i = 0; i < 16; ++i) {
                xv[i] = ldg128(xp + (size_t)(16 * (i >> 3) + 64 * ((i >> 2) & 1)) * D_DIM + 32 * (i & 3));
                if (i & 1) __nanosleep(GAP_X);
            }
#pragma unroll
            for (int jq = 0; jq < 4; ++jq) dk[jq] = ldg128(dskip + dt * 128 + 32 * jq + 8 * t4);
            mbar_wait(bar_fh, 0);
            uint32_t omg[4], g2[4];
#pragma unroll
            for (int i = 0; i < 4; ++i) {
                const float gt = __ldcg(g_gate + trow + 16 * (i >> 1) + 64 * (i & 1));
                if (t4 == 0) asm volatile("st.shared.f32 [%0], %1;" ::"r"(sbase + OFF_PAR + (64 * (i >> 1) + 16 * w4 + 8 * (i & 1) + g) * 4), "f"(gt) : "memory");
                omg[i] = pack_bf16(2.f - 2.f * gt, 2.f - 2.f * gt); g2[i] = pack_bf16(gt, gt);
            }
            if (t == 0) {
                mbar_wait(bar_yrel, 0);
                wait_counter(&g_cnt[(48 + dt) * 32], lds32(w_bid + 4));
                STAMP(0, 16);
                mbar_expect_tx(bar_y1, 24576);
                tma_load_5d(sbase + OFF_CU, &maps.yt3, bar_y1, (bid & 8) * 128 + (bid >> 4) * 128, 0, 0, 0, dt * 4);
                tma_load_5d(sbase + OFF_CU + 12288, &maps.yt3, bar_y1, (bid & 8) * 128 + (bid >> 4) * 128 + 64, 0, 0, 0, dt * 4);
            }
            __syncwarp();
            uint32_t ya = sbase + OFF_CU + (w4 & 1) * 12288 + (lane >> 3) * 3072 + (lane & 7) * 128 + ((((w4 >> 1) ^ ((bid >> 3 & 2) + (w4 & 1))) ^ (lane & 7)) << 4);
#pragma unroll
            for (int p = 0; p < 4; ++p) {
                if (p == 0) { mbar_wait(bar_y1, 0); if (t == 0) STAMP(0, 18); }
                if (p == 3) {
                    if (t == 0) STAMP(0, 17);
                    ya += 21504 - (w4 & 1) * 8192 - (lane >> 3) * 2048;
                    mbar_wait(bar_y, 0);
                    if (t == 0) STAMP(0, 6);
                }
#pragma unroll
                for (int i = 0; i < 4; ++i) {
                    uint32_t yw[4];
                    ldsm_x4_t(yw[0], yw[1], yw[2], yw[3], (ya ^ ((i & 1) << 6) ^ ((i & 2) << 4)) + p * 1024);
#pragma unroll
                    for (int jq = 0; jq < 4; ++jq) {
                        uint32_t& w = (&xv[4 * i + jq].x)[p];
                        w = hfma(g2[i], hmul(w, (&dk[jq].x)[p]), hmul(omg[i], hmul(w, yw[jq])));
                    }
                }
            }
            named_bar(2, 128);
#pragma unroll
            for (int i = 0; i < 16; ++i) {
                sts128(sbase + (i & 8 ? OFF_CT : OFF_CU) + (i & 3) * 8192 + (w4 * 16 + g + (i & 4) * 2) * 128 + (((2 * t4) ^ g) << 4), xv[i].x, xv[i].y, xv[i].z, xv[i].w);
                if ((i & 7) == 7) {
                    __syncwarp();
                    if (lane == 0) mbar_arrive(bar_bias + (i & 8));
                }
            }
            if (t == 0) STAMP(0, 7);
            }
        }
    }
    }
}

void make_map(CUtensorMap* m, const void* ptr, int rank, const cuuint64_t* dims, const cuuint64_t* strides, const cuuint32_t* box,
              CUtensorMapSwizzle swz, bool f32 = false) {
    cuuint32_t es[5] = {1, 1, 1, 1, 1};
    get_encode()(m, f32 ? CU_TENSOR_MAP_DATA_TYPE_FLOAT32 : CU_TENSOR_MAP_DATA_TYPE_BFLOAT16, rank, const_cast<void*>(ptr), dims, strides, box, es,
                 CU_TENSOR_MAP_INTERLEAVE_NONE, swz, CU_TENSOR_MAP_L2_PROMOTION_L2_256B, CU_TENSOR_MAP_FLOAT_OOB_FILL_NONE);
}
void make_map_2d(CUtensorMap* m, const void* ptr, uint64_t inner, uint64_t outer, uint32_t box_in, uint32_t box_out) {
    cuuint64_t dims[2] = {inner, outer};
    cuuint64_t strides[1] = {inner * 2};
    cuuint32_t box[2] = {box_in, box_out};
    make_map(m, ptr, 2, dims, strides, box, CU_TENSOR_MAP_SWIZZLE_128B);
}
void make_map_conv(CUtensorMap* m, const void* p, uint32_t nch = 2) {
    cuuint64_t dims[4] = {32, 32, 2, 1024};
    cuuint64_t strides[3] = {128, 64, 4096};
    cuuint32_t box[4] = {32, 32, 2, nch};
    make_map(m, p, 4, dims, strides, box, CU_TENSOR_MAP_SWIZZLE_64B);
}

}

extern "C" void kernel_launch(void* const* d_in, const int* in_sizes, int n_in, void* d_out, int out_size) {
    const __nv_bfloat16* x = (const __nv_bfloat16*)d_in[0];
    const __nv_bfloat16* lam_re = (const __nv_bfloat16*)d_in[1];
    const __nv_bfloat16* lam_im = (const __nv_bfloat16*)d_in[2];
    const __nv_bfloat16* b_re = (const __nv_bfloat16*)d_in[3];
    const __nv_bfloat16* b_im = (const __nv_bfloat16*)d_in[4];
    const __nv_bfloat16* c_re = (const __nv_bfloat16*)d_in[5];
    const __nv_bfloat16* c_im = (const __nv_bfloat16*)d_in[6];
    const __nv_bfloat16* log_dt = (const __nv_bfloat16*)d_in[7];
    const __nv_bfloat16* dskip = (const __nv_bfloat16*)d_in[8];
    const __nv_bfloat16* kin = (const __nv_bfloat16*)d_in[10];
    const __nv_bfloat16* vin = (const __nv_bfloat16*)d_in[11];
    const __nv_bfloat16* shift_k = (const __nv_bfloat16*)d_in[12];
    const __nv_bfloat16* ssm_k = (const __nv_bfloat16*)d_in[13];
    const __nv_bfloat16* ssm_D = (const __nv_bfloat16*)d_in[14];
    const __nv_bfloat16* gate_w = (const __nv_bfloat16*)d_in[15];
    float* out = (float*)d_out;

    void *yptr = nullptr, *kvtptr = nullptr;
    cudaGetSymbolAddress(&yptr, g_y2);
    cudaGetSymbolAddress(&kvtptr, g_kvT);

    Maps maps;
    {
        cuuint64_t dims[5] = {1024, 2, 4, 32, 8};
        cuuint64_t strides[4] = {2048, 64 * 2048, 2 * 2048, 256 * 2048};
        cuuint32_t box[5] = {64, 2, 4, 32, 1};
        make_map(&maps.x5, x, 5, dims, strides, box, CU_TENSOR_MAP_SWIZZLE_128B);
    }
    int bmode = 0;
    {
        const uint64_t a = (uint64_t)b_re, b = (uint64_t)b_im;
        const uint64_t delta = a < b ? b - a : a - b;
        if (delta != 0 && (delta & 15) == 0 && delta < (1ull << 40)) bmode = a < b ? 1 : 2;
        cuuint64_t dims[4] = {1024, 8, 2, 128};
        cuuint64_t strides[3] = {2048, bmode ? delta : 16, 16384};
        cuuint32_t box[4] = {64, 8, 2, 4};
        make_map(&maps.b4, a < b ? b_re : b_im, 4, dims, strides, box, CU_TENSOR_MAP_SWIZZLE_128B);
    }
    make_map_2d(&maps.bre, b_re, 1024, 1024, 64, 8);
    make_map_2d(&maps.bim, b_im, 1024, 1024, 64, 8);
    {
        cuuint64_t dims[3] = {S_LEN, 128, 8};
        cuuint64_t strides[2] = {8 * 4096, 4096};
        cuuint32_t box[3] = {64, 16, 2};
        make_map(&maps.kvst, kvtptr, 3, dims, strides, box, CU_TENSOR_MAP_SWIZZLE_128B);
    }
    make_map_conv(&maps.sk, ssm_k, 1);
    for (int i = 0; i < 2; ++i) {
        cuuint64_t dims[5] = {1024, 2, 4, 4, 32};
        cuuint64_t strides[4] = {2048, 8 * 2048, 2 * 2048, 32 * 2048};
        cuuint32_t box[5] = {64, 2, 4, 4, 4};
        make_map(i ? &maps.cim : &maps.cre, i ? c_im : c_re, 5, dims, strides, box, CU_TENSOR_MAP_SWIZZLE_128B);
    }
    {
        cuuint64_t dims[5] = {S_LEN, 2, 4, 4, 32};
        cuuint64_t strides[4] = {4096, 8 * 4096, 2 * 4096, 32 * 4096};
        cuuint32_t box[5] = {64, 2, 4, 1, 4};
        make_map(&maps.yt, yptr, 5, dims, strides, box, CU_TENSOR_MAP_SWIZZLE_128B);
        box[3] = 3;
        make_map(&maps.yt3, yptr, 5, dims, strides, box, CU_TENSOR_MAP_SWIZZLE_128B);
    }
    {
        cuuint64_t dims[5] = {D_DIM, 8, 4, 8, 8};
        cuuint64_t strides[4] = {4096, 64 * 4096, 8 * 4096, 256 * 4096};
        cuuint32_t box[5] = {32, 8, 4, 2, 1};
        make_map(&maps.out, out, 5, dims, strides, box, CU_TENSOR_MAP_SWIZZLE_128B, true);
    }

    auto kern = bmode == 1 ? fused_kernel<1> : bmode == 2 ? fused_kernel<2> : fused_kernel<0>;
    cudaFuncSetAttribute(kern, cudaFuncAttributeMaxDynamicSharedMemorySize, SMEM_BYTES);
    static int grid = 0;
    if (!grid) {
        int dev = 0, sms = 0;
        cudaGetDevice(&dev);
        cudaDeviceGetAttribute(&sms, cudaDevAttrMultiProcessorCount, dev);
        grid = sms == 132 ? 132 : 128;
    }
    kern<<<grid, 512, SMEM_BYTES>>>(x, b_re, b_im, kin, vin, ssm_k, shift_k, ssm_D, lam_re, lam_im, log_dt, gate_w, dskip, c_re, c_im, maps);
}
```

```cpp
#include <cuda_runtime.h>
#include <cuda_bf16.h>
#include <cuda.h>
#include <stdint.h>
#include <type_traits>

namespace {
__device__ __forceinline__ uint32_t smem_u32(const void* p) { return (uint32_t)__cvta_generic_to_shared(p); }
__device__ __forceinline__ void mbar_init(uint32_t bar, uint32_t count) {
    asm volatile("mbarrier.init.shared::cta.b64 [%0], %1;" ::"r"(bar), "r"(count) : "memory");
}
__device__ __forceinline__ void mbar_expect_tx(uint32_t bar, uint32_t bytes) {
    asm volatile("mbarrier.arrive.expect_tx.shared::cta.b64 _, [%0], %1;" ::"r"(bar), "r"(bytes) : "memory");
}
__device__ __forceinline__ void mbar_arrive(uint32_t bar) {
    asm volatile("mbarrier.arrive.shared::cta.b64 _, [%0];" ::"r"(bar) : "memory");
}
__device__ __forceinline__ void mbar_wait(uint32_t bar, uint32_t parity) {
    asm volatile(
        "{\n"
        ".reg .pred p;\n"
        ".reg .u32 n;\n"
        "mov.u32 n, 0;\n"
        "LAB_WAIT:\n"
        "mbarrier.try_wait.parity.shared::cta.b64 p, [%0], %1;\n"
        "@p bra LAB_DONE;\n"
        "add.u32 n, n, 1;\n"
        "setp.lt.u32 p, n, 0x400000;\n"
        "@p bra LAB_WAIT;\n"
        "trap;\n"
        "LAB_DONE:\n"
        "}\n" ::"r"(bar), "r"(parity) : "memory");
}
__device__ __forceinline__ void tma_load_2d(uint32_t dst, const CUtensorMap* map, uint32_t bar, int c0, int c1) {
    asm volatile(
        "cp.async.bulk.tensor.2d.shared::cluster.global.mbarrier::complete_tx::bytes [%0], [%1, {%3, %4}], [%2];"
        ::"r"(dst), "l"((uint64_t)map), "r"(bar), "r"(c0), "r"(c1) : "memory");
}
__device__ __forceinline__ void tma_load_4d(uint32_t dst, const CUtensorMap* map, uint32_t bar, int c0, int c1, int c2, int c3) {
    asm volatile(
        "cp.async.bulk.tensor.4d.shared::cluster.global.mbarrier::complete_tx::bytes [%0], [%1, {%3, %4, %5, %6}], [%2];"
        ::"r"(dst), "l"((uint64_t)map), "r"(bar), "r"(c0), "r"(c1), "r"(c2), "r"(c3) : "memory");
}
__device__ __forceinline__ void tma_load_5d(uint32_t dst, const CUtensorMap* map, uint32_t bar, int c0, int c1, int c2, int c3, int c4) {
    asm volatile(
        "cp.async.bulk.tensor.5d.shared::cluster.global.mbarrier::complete_tx::bytes [%0], [%1, {%3, %4, %5, %6, %7}], [%2];"
        ::"r"(dst), "l"((uint64_t)map), "r"(bar), "r"(c0), "r"(c1), "r"(c2), "r"(c3), "r"(c4) : "memory");
}
__device__ __forceinline__ void bulk_load(uint32_t dst, const void* src, uint32_t bytes, uint32_t bar) {
    asm volatile("cp.async.bulk.shared::cluster.global.mbarrier::complete_tx::bytes [%0], [%1], %2, [%3];"
                 ::"r"(dst), "l"(src), "r"(bytes), "r"(bar) : "memory");
}
__device__ __forceinline__ void tma_store_3d(const CUtensorMap* map, uint32_t src, int c0, int c1, int c2) {
    asm volatile("cp.async.bulk.tensor.3d.global.shared::cta.bulk_group [%0, {%2, %3, %4}], [%1];"
                 ::"l"((uint64_t)map), "r"(src), "r"(c0), "r"(c1), "r"(c2) : "memory");
}
__device__ __forceinline__ void bulk_commit() { asm volatile("cp.async.bulk.commit_group;" ::: "memory"); }
__device__ __forceinline__ void bulk_wait0() { asm volatile("cp.async.bulk.wait_group 0;" ::: "memory"); }
__device__ __forceinline__ void bulk_wait_read0() { asm volatile("cp.async.bulk.wait_group.read 0;" ::: "memory"); }
__device__ __forceinline__ void fence_async_smem() { asm volatile("fence.proxy.async.shared::cta;" ::: "memory"); }
__device__ __forceinline__ void named_bar(int id, int n) { asm volatile("bar.sync %0, %1;" ::"r"(id), "r"(n) : "memory"); }
__device__ __forceinline__ void sts128(uint32_t addr, uint32_t a, uint32_t b, uint32_t c, uint32_t d) {
    asm volatile("st.shared.v4.b32 [%0], {%1, %2, %3, %4};" ::"r"(addr), "r"(a), "r"(b), "r"(c), "r"(d) : "memory");
}
__device__ __forceinline__ void prefetch_map(const CUtensorMap* m) {
    asm volatile("prefetch.tensormap [%0];" ::"l"((uint64_t)m) : "memory");
}
__device__ __forceinline__ void wgmma_fence() { asm volatile("wgmma.fence.sync.aligned;" ::: "memory"); }
__device__ __forceinline__ void wgmma_commit() { asm volatile("wgmma.commit_group.sync.aligned;" ::: "memory"); }
template <int N>
__device__ __forceinline__ void wgmma_wait() { asm volatile("wgmma.wait_group.sync.aligned %0;" ::"n"(N) : "memory"); }
template <int N>
__device__ __forceinline__ void fence_regs(float (&a)[N]) {
#pragma unroll
    for (int i = 0; i < N; ++i) asm volatile("" : "+f"(a[i])::"memory");
}
template <int N>
__device__ __forceinline__ void fence_regs(uint32_t (&a)[N]) {
#pragma unroll
    for (int i = 0; i < N; ++i) asm volatile("" : "+r"(a[i])::"memory");
}
#define R8(a, i) "+f"(a[i + 0]), "+f"(a[i + 1]), "+f"(a[i + 2]), "+f"(a[i + 3]), "+f"(a[i + 4]), "+f"(a[i + 5]), "+f"(a[i + 6]), "+f"(a[i + 7])
#define REGS32 "{%0, %1, %2, %3, %4, %5, %6, %7, %8, %9, %10, %11, %12, %13, %14, %15, %16, %17, %18, %19, %20, %21, %22, %23, %24, %25, %26, %27, %28, %29, %30, %31}"
#define REGS16 "{%0, %1, %2, %3, %4, %5, %6, %7, %8, %9, %10, %11, %12, %13, %14, %15}"

__host__ __device__ constexpr uint32_t desc_hi(uint32_t sbo, uint32_t mode) { return (sbo >> 4) | (mode << 30); }
__device__ __forceinline__ uint32_t desc_lo(uint32_t saddr, uint32_t lbo) { return ((saddr & 0x3FFFF) >> 4) | ((lbo >> 4) << 16); }
constexpr uint32_t HI128 = desc_hi(1024, 1), HI64 = desc_hi(512, 2);
#define W8(a, i) "=f"(a[i + 0]), "=f"(a[i + 1]), "=f"(a[i + 2]), "=f"(a[i + 3]), "=f"(a[i + 4]), "=f"(a[i + 5]), "=f"(a[i + 6]), "=f"(a[i + 7])
template <int TA, int TB, int ACC, uint32_t AHI, uint32_t BHI>
__device__ __forceinline__ void wgmma_n64_ss(float (&d)[32], uint32_t alo, uint32_t blo) {
#define N64_TEXT "{\n.reg .pred p;\n.reg .b64 da, db;\nsetp.ne.b32 p, %36, 0;\nmov.b64 da, {%32, %37};\nmov.b64 db, {%33, %38};\n" \
        "wgmma.mma_async.sync.aligned.m64n64k16.f32.bf16.bf16 " REGS32 ", da, db, p, 1, 1, %34, %35;\n}\n"
    if (ACC) asm volatile(N64_TEXT : R8(d, 0), R8(d, 8), R8(d, 16), R8(d, 24) : "r"(alo), "r"(blo), "n"(TA), "n"(TB), "n"(ACC), "n"(AHI), "n"(BHI));
    else asm volatile(N64_TEXT : W8(d, 0), W8(d, 8), W8(d, 16), W8(d, 24) : "r"(alo), "r"(blo), "n"(TA), "n"(TB), "n"(ACC), "n"(AHI), "n"(BHI));
}
template <int ACC, int SA>
__device__ __forceinline__ void wgmma_n32_tt(float (&d)[16], uint32_t alo, uint32_t blo) {
#define N32T_TEXT "{\n.reg .pred p;\n.reg .b64 da, db;\nsetp.ne.b32 p, %18, 0;\nmov.b64 da, {%16, %19};\nmov.b64 db, {%17, %20};\n" \
        "wgmma.mma_async.sync.aligned.m64n32k16.f32.bf16.bf16 " REGS16 ", da, db, p, %21, 1, 1, 1;\n}\n"
    if (ACC) asm volatile(N32T_TEXT : R8(d, 0), R8(d, 8) : "r"(alo), "r"(blo), "n"(ACC), "n"(HI64), "n"(HI128), "n"(SA));
    else asm volatile(N32T_TEXT : W8(d, 0), W8(d, 8) : "r"(alo), "r"(blo), "n"(ACC), "n"(HI64), "n"(HI128), "n"(SA));
}
__device__ __forceinline__ void wgmma_n16_rs(float (&d)[8], const uint32_t (&a)[4], uint32_t blo) {
    asm volatile("{\n.reg .pred p;\n.reg .b64 db;\nsetp.ne.b32 p, 0, 0;\nmov.b64 db, {%12, %13};\n"
        "wgmma.mma_async.sync.aligned.m64n16k16.f32.bf16.bf16 {%0, %1, %2, %3, %4, %5, %6, %7}, {%8, %9, %10, %11}, db, p, 1, 1, 0;\n}\n"
        : W8(d, 0) : "r"(a[0]), "r"(a[1]), "r"(a[2]), "r"(a[3]), "r"(blo), "n"(HI128));
}

__device__ __forceinline__ float bf16r(float x) { return __bfloat162float(__float2bfloat16_rn(x)); }
__device__ __forceinline__ uint32_t pack_bf16(float lo, float hi) {
    __nv_bfloat162 v = __floats2bfloat162_rn(lo, hi);
    return *reinterpret_cast<uint32_t*>(&v);
}
__device__ __forceinline__ __nv_bfloat162 as_bf2(uint32_t w) { return *reinterpret_cast<__nv_bfloat162*>(&w); }
__device__ __forceinline__ uint32_t as_u32(__nv_bfloat162 v) { return *reinterpret_cast<uint32_t*>(&v); }
__device__ __forceinline__ float bf_lo(uint32_t w) { return __uint_as_float(w << 16); }
__device__ __forceinline__ float bf_hi(uint32_t w) { return __uint_as_float(w & 0xFFFF0000u); }
__device__ __forceinline__ void ldsm_x4_t(uint32_t& r0, uint32_t& r1, uint32_t& r2, uint32_t& r3, uint32_t addr) {
    asm volatile("ldmatrix.sync.aligned.m8n8.x4.trans.shared.b16 {%0,%1,%2,%3}, [%4];"
                 : "=r"(r0), "=r"(r1), "=r"(r2), "=r"(r3) : "r"(addr) : "memory");
}
__device__ __forceinline__ void stsm_x4(uint32_t addr, uint32_t r0, uint32_t r1, uint32_t r2, uint32_t r3) {
    asm volatile("stmatrix.sync.aligned.m8n8.x4.shared.b16 [%0], {%1,%2,%3,%4};"
                 ::"r"(addr), "r"(r0), "r"(r1), "r"(r2), "r"(r3) : "memory");
}
__device__ __forceinline__ void stsm_x4_t(uint32_t addr, uint32_t r0, uint32_t r1, uint32_t r2, uint32_t r3) {
    asm volatile("stmatrix.sync.aligned.m8n8.x4.trans.shared.b16 [%0], {%1,%2,%3,%4};"
                 ::"r"(addr), "r"(r0), "r"(r1), "r"(r2), "r"(r3) : "memory");
}
__device__ __forceinline__ uint32_t lds32(uint32_t addr) {
    uint32_t v;
    asm volatile("ld.shared.b32 %0, [%1];" : "=r"(v) : "r"(addr));
    return v;
}

typedef CUresult (*EncodeFn)(CUtensorMap*, CUtensorMapDataType, cuuint32_t, void*, const cuuint64_t*, const cuuint64_t*,
                             const cuuint32_t*, const cuuint32_t*, CUtensorMapInterleave, CUtensorMapSwizzle,
                             CUtensorMapL2promotion, CUtensorMapFloatOOBfill);
EncodeFn get_encode() {
    static EncodeFn fn = nullptr;
    if (!fn) {
        void* p = nullptr;
        cudaDriverEntryPointQueryResult qres;
        cudaGetDriverEntryPoint("cuTensorMapEncodeTiled", &p, cudaEnableDefault, &qres);
        fn = (EncodeFn)p;
    }
    return fn;
}
}
namespace {
constexpr double c_pi = 3.14159265358979323846;
constexpr double c_cos256(int i) {
    i &= 255;
    if (i > 128) i = 256 - i;
    double sgn = 1.0;
    if (i > 64) { i = 128 - i; sgn = -1.0; }
    if (i == 64) return 0.0;
    double x = 2.0 * c_pi * i / 256.0, x2 = x * x, term = 1.0, sum = 1.0;
    for (int k = 1; k < 20; ++k) { term *= -x2 / ((2 * k - 1) * (2 * k)); sum += term; }
    return sgn * sum;
}
constexpr uint32_t c_bf16(double v) {
    if (v == 0.0) return 0u;
    uint32_t s = v < 0 ? 0x8000u : 0u;
    double a = v < 0 ? -v : v;
    int e = 0;
    while (a >= 2.0) { a *= 0.5; ++e; }
    while (a < 1.0) { a *= 2.0; --e; }
    int r = (int)(a * 128.0 + 0.5);
    if (r == 256) { r = 128; ++e; }
    return s | (uint32_t)((e + 127) << 7) | (uint32_t)(r - 128);
}
__host__ __device__ constexpr int conv_k1(int r) { return (r & 8) ? 63 - (((r >> 4) << 3) | (r & 7)) : (((r >> 4) << 3) | (r & 7)); }
struct ConvTab { uint32_t w[96 * 32]; };
constexpr ConvTab make_conv_tab() {
    ConvTab t{};
    uint32_t cs[256] = {};
    for (int i = 0; i < 256; ++i) cs[i] = c_bf16(c_cos256(i));
    for (int n = 0; n < 96; ++n)
        for (int c = 0; c < 64; ++c) {
            int a = 0;
            if (n < 32) {
                const int ro = (n >> 3) & 1, ri = n & 7, co = (c >> 3) & 1, ci = c & 7;
                a = n < 16 ? 8 * ci * (4 * ri + (c >> 4)) : 8 * ri * (4 * ci + (c >> 4));
                a += (ro == co) ? 0 : (ro == 0) ? 192 : 64;
            } else {
                const int r = n - 32, n1 = 2 * (c & 31) + (c >> 5);
                a = n1 * (2 * (((r >> 4) << 3) | (r & 7)) + 1) + ((r & 8) ? 64 : 0);
            }
            const int off = n * 128 + (((c >> 3) ^ (n & 7)) << 4) + (c & 7) * 2;
            t.w[off >> 2] |= cs[a & 255] << ((off & 2) * 8);
        }
    return t;
}
__device__ __align__(128) constexpr ConvTab g_conv_tab = make_conv_tab();

struct Twiddle { uint32_t r[8], i[8], n[8]; };
constexpr double c_cospi(double x) {
    double sgn = 1.0;
    if (x > 0.5) { x = 1.0 - x; sgn = -1.0; }
    const double y = c_pi * x, y2 = y * y;
    double term = 1.0, sum = 1.0;
    for (int k = 1; k < 12; ++k) { term *= -y2 / ((2 * k - 1) * (2 * k)); sum += term; }
    return sgn * sum;
}
struct TwTab { uint32_t w[3072]; };
constexpr TwTab make_tw_tab() {
    TwTab t{};
    for (int th = 0; th < 128; ++th)
        for (int q = 0; q < 8; ++q)
            for (int e = 0; e < 2; ++e) {
                const int k1 = conv_k1(16 * (th >> 5) + 8 * (q & 1) + ((th & 31) >> 2)), n2 = 8 * (q >> 1) + 2 * (th & 3) + e;
                const double x = (double)(n2 * (2 * k1 + 1)) / 4096.0;
                const double cs = c_cospi(x), sn = n2 == 0 ? 0.0 : c_cospi(x > 0.5 ? x - 0.5 : 0.5 - x);
                t.w[((q >> 2) * 128 + th) * 4 + (q & 3)] |= c_bf16(cs * 0.0625) << (16 * e);
                t.w[((2 + (q >> 2)) * 128 + th) * 4 + (q & 3)] |= c_bf16(-sn * 0.0625) << (16 * e);
                t.w[((4 + (q >> 2)) * 128 + th) * 4 + (q & 3)] |= c_bf16(sn * 0.0625) << (16 * e);
            }
    return t;
}
__device__ __align__(128) constexpr TwTab g_tw_tab = make_tw_tab();
__device__ __forceinline__ void load_twiddle(Twiddle& tw, const uint4* p) {
#pragma unroll
    for (int q = 0; q < 2; ++q) {
        const uint4 a = __ldg(p + q * 128);
        const uint4 b = __ldg(p + (2 + q) * 128);
        tw.r[4 * q] = a.x; tw.r[4 * q + 1] = a.y; tw.r[4 * q + 2] = a.z; tw.r[4 * q + 3] = a.w;
        const uint4 n = __ldg(p + (4 + q) * 128);
        tw.n[4 * q] = n.x; tw.n[4 * q + 1] = n.y; tw.n[4 * q + 2] = n.z; tw.n[4 * q + 3] = n.w;
        tw.i[4 * q] = b.x; tw.i[4 * q + 1] = b.y; tw.i[4 * q + 2] = b.z; tw.i[4 * q + 3] = b.w;
    }
}

__device__ __forceinline__ int fresh_tid() { int v; asm volatile("mov.u32 %0, %tid.x;" : "=r"(v)); return v; }
__device__ __forceinline__ uint32_t hmul(uint32_t a, uint32_t b) { return as_u32(__hmul2_rn(as_bf2(a), as_bf2(b))); }
__device__ __forceinline__ uint32_t hadd(uint32_t a, uint32_t b) { return as_u32(__hadd2_rn(as_bf2(a), as_bf2(b))); }
__device__ __forceinline__ uint32_t hsub(uint32_t a, uint32_t b) { return as_u32(__hsub2_rn(as_bf2(a), as_bf2(b))); }
__device__ __forceinline__ uint32_t hfma(uint32_t a, uint32_t b, uint32_t c) { return as_u32(__hfma2(as_bf2(a), as_bf2(b), as_bf2(c))); }

__device__ __forceinline__ void conv_dft8(float (&x)[4][8], const uint32_t (&f)[4][4], uint32_t blo) {
#pragma unroll
    for (int r = 0; r < 4; ++r) wgmma_n16_rs(x[r], f[r], blo + 2 * r);
}
template <class T, int N>
__device__ __forceinline__ void fence_regs4(T (&a)[4][N]) { fence_regs(a[0]); fence_regs(a[1]); fence_regs(a[2]); fence_regs(a[3]); }
__device__ __forceinline__ void conv_s1(float (&dE)[32], float (&dO)[32], uint32_t tlo, uint32_t ulo) {
    wgmma_n64_ss<0, 1, 0, HI128, HI64>(dE, tlo + 256, ulo);
    wgmma_n64_ss<0, 1, 0, HI128, HI64>(dO, tlo + 256 + 4, ulo + 128);
    wgmma_n64_ss<0, 1, 1, HI128, HI64>(dE, tlo + 256 + 2, ulo + 64);
    wgmma_n64_ss<0, 1, 1, HI128, HI64>(dO, tlo + 256 + 6, ulo + 192);
}
template <int S>
__device__ __forceinline__ void conv_t1(const float (&dE)[32], const float (&dO)[32], const Twiddle& tw, float dsk, uint32_t (&f)[4][4]) {
    uint32_t ar[8], ai[8], fs[8], fd[8];
#pragma unroll
    for (int j = 0; j < 4; ++j) {
        const int i = 16 * S + 4 * j;
        const uint32_t e0 = pack_bf16(i == 16 ? dE[i] + dsk : dE[i], dE[i + 1]), e1 = pack_bf16(dE[i + 2], dE[i + 3]);
        const uint32_t o0 = pack_bf16(dO[i], dO[i + 1]), o1 = pack_bf16(dO[i + 2], dO[i + 3]);
        ar[2 * j] = hadd(e0, o0); ai[2 * j] = hadd(e1, o1);
        ar[2 * j + 1] = hsub(e0, o0); ai[2 * j + 1] = hsub(o1, e1);
    }
#pragma unroll
    for (int q = 0; q < 4; ++q) {
        const uint32_t pr = hfma(ar[q], tw.r[q], hmul(ai[q], tw.n[q])), pi = hfma(ar[q], tw.i[q], hmul(ai[q], tw.r[q]));
        fs[q] = hfma(ar[4 + q], tw.r[4 + q], hfma(ai[4 + q], tw.n[4 + q], pr));
        fs[4 + q] = hfma(ar[4 + q], tw.i[4 + q], hfma(ai[4 + q], tw.r[4 + q], pi));
        fd[q] = hfma(pr, 0xC000C000u, fs[q]);
        fd[4 + q] = hfma(pi, 0xC000C000u, fs[4 + q]);
    }
#pragma unroll
    for (int h = 0; h < 2; ++h) {
        f[0][h] = hadd(fs[h], fs[2 + h]); f[0][2 + h] = hadd(fs[4 + h], fs[6 + h]);
        f[2][h] = hsub(fs[h], fs[2 + h]); f[2][2 + h] = hsub(fs[4 + h], fs[6 + h]);
        f[1][h] = hadd(fd[h], fd[6 + h]); f[1][2 + h] = hsub(fd[4 + h], fd[2 + h]);
        f[3][h] = hsub(fd[h], fd[6 + h]); f[3][2 + h] = hadd(fd[4 + h], fd[2 + h]);
    }
}
__device__ __forceinline__ void conv_prod(const float (&xu)[8], const float (&xk)[8], uint32_t (&f)[4]) {
#pragma unroll
    for (int h = 0; h < 2; ++h) {
        float pr[2], pi[2];
#pragma unroll
        for (int e = 0; e < 2; ++e) {
            const float ur = xu[2 * h + e], ui = xu[4 + 2 * h + e], kr = xk[2 * h + e], ki = xk[4 + 2 * h + e];
            pr[e] = fmaf(ur, kr, -ui * ki);
            pi[e] = fmaf(-ur, ki, -ui * kr);
        }
        f[h] = pack_bf16(pr[0], pr[1]);
        f[2 + h] = pack_bf16(pi[0], pi[1]);
    }
}
template <bool SECOND, class G>
__device__ __forceinline__ void conv_channel(float (&dE)[32], float (&dO)[32], const Twiddle& tw, float dsk, uint32_t tlo, uint32_t nxt,
                                             uint32_t wre, uint32_t wim, int bar, G before_next) {
    float xu[4][8], xk[4][8];
    {
        uint32_t fu[4][4], fk[4][4];
        conv_t1<0>(dE, dO, tw, 0.f, fu);
        wgmma_fence();
        conv_dft8(xu, fu, tlo);
        wgmma_commit();
        conv_t1<1>(dE, dO, tw, dsk, fk);
        wgmma_fence();
        conv_dft8(xk, fk, tlo);
        wgmma_commit();
        before_next();
        wgmma_wait<0>();
        fence_regs4(xu); fence_regs4(xk);
        fence_regs4(fu); fence_regs4(fk);
    }
    uint32_t fp[4][4];
#pragma unroll
    for (int r = 0; r < 4; ++r) conv_prod(xu[r], xk[r], fp[r]);
    wgmma_fence();
    conv_dft8(xu, fp, tlo + 128);
    wgmma_commit();
    if (!SECOND || nxt) {
        if (SECOND) wgmma_fence();
        conv_s1(dE, dO, tlo, nxt);
        wgmma_commit();
        wgmma_wait<1>();
    } else {
        wgmma_wait<0>();
#pragma unroll
        for (int i = 0; i < 32; ++i) { dE[i] = 0.f; dO[i] = 0.f; }
        fence_regs(dE); fence_regs(dO);
    }
    fence_regs4(xu);
    fence_regs4(fp);
    uint32_t zr[8], zi[8], wr[8], wi[8];
#pragma unroll
    for (int h = 0; h < 2; ++h) {
        uint32_t yr[4], yi[4];
#pragma unroll
        for (int r = 0; r < 4; ++r) { yr[r] = pack_bf16(xu[r][2 * h], xu[r][2 * h + 1]); yi[r] = pack_bf16(xu[r][4 + 2 * h], xu[r][5 + 2 * h]); }
        const uint32_t u0r = hadd(yr[0], yr[2]), u0i = hadd(yi[0], yi[2]), u1r = hsub(yr[0], yr[2]), u1i = hsub(yi[0], yi[2]);
        const uint32_t v0r = hadd(yr[1], yr[3]), v0i = hadd(yi[1], yi[3]), v1r = hsub(yr[1], yr[3]), v1i = hsub(yi[1], yi[3]);
        zr[h] = hadd(u0r, v0r); zi[h] = hadd(u0i, v0i); zr[4 + h] = hsub(u0r, v0r); zi[4 + h] = hsub(u0i, v0i);
        zr[2 + h] = hadd(u1r, v1i); zi[2 + h] = hsub(u1i, v1r); zr[6 + h] = hsub(u1r, v1i); zi[6 + h] = hadd(u1i, v1r);
    }
#pragma unroll
    for (int q = 0; q < 8; ++q) {
        wr[q] = hfma(zr[q], tw.r[q], hmul(zi[q], tw.n[q]));
        wi[q] = hfma(zr[q], tw.i[q], hmul(zi[q], tw.r[q]));
    }
    if (SECOND) named_bar(bar, 128);
    stsm_x4(wre, hadd(wr[0], wr[1]), hadd(wr[2], wr[3]), hadd(wr[4], wr[5]), hadd(wr[6], wr[7]));
    stsm_x4(wre + 512, hsub(wi[1], wi[0]), hsub(wi[3], wi[2]), hsub(wi[5], wi[4]), hsub(wi[7], wi[6]));
    stsm_x4(wim, hsub(wr[1], wr[0]), hsub(wr[3], wr[2]), hsub(wr[5], wr[4]), hsub(wr[7], wr[6]));
    stsm_x4(wim + 512, hadd(wi[0], wi[1]), hadd(wi[2], wi[3]), hadd(wi[4], wi[5]), hadd(wi[6], wi[7]));
}
template <class G>
__device__ __forceinline__ void conv_pair(float (&dE)[32], float (&dO)[32], const Twiddle& tw, uint32_t dd, uint32_t tlo, uint32_t u0, uint32_t un,
                                          uint32_t lo, int BAR, G before_next) {
    conv_channel<false>(dE, dO, tw, bf_lo(dd), tlo, desc_lo(u0 + 4096, 8192), u0 + lo, u0 + 8192 + lo, BAR, []() {});
    wgmma_wait<0>();
    fence_regs(dE); fence_regs(dO);
    conv_channel<true>(dE, dO, tw, bf_hi(dd), tlo, un == u0 ? 0 : desc_lo(un, 8192), u0 + 4096 + lo, u0 + 12288 + lo, BAR, before_next);
    fence_async_smem();
    named_bar(BAR, 128);
    float ye[16], yo[16];
    wgmma_fence();
    const uint32_t wlo = desc_lo(u0, 4096);
    wgmma_n32_tt<0, 1>(ye, wlo, tlo + 256);
    wgmma_n32_tt<0, -1>(yo, wlo + 512, tlo + 256 + 4);
#pragma unroll
    for (int k = 1; k < 4; ++k) {
        wgmma_n32_tt<1, 1>(ye, wlo + 64 * k, tlo + 256 + 128 * k);
        wgmma_n32_tt<1, -1>(yo, wlo + 512 + 64 * k, tlo + 256 + 4 + 128 * k);
    }
    wgmma_commit();
    wgmma_wait<0>();
    fence_regs(ye); fence_regs(yo);
    fence_regs(dE); fence_regs(dO);
    named_bar(BAR, 128);
    const int t = fresh_tid();
    const uint32_t ya = u0 + (t & 64) * 64 + (t & 31) * 64 + (((((t >> 4) & 2) ^ (t >> 1)) & 3) << 4);
#pragma unroll
    for (int h = 0; h < 2; ++h) {
        stsm_x4_t(ya ^ (16 * h), pack_bf16(ye[2 * h], ye[2 * h + 1]), pack_bf16(ye[4 + 2 * h], ye[5 + 2 * h]),
                  pack_bf16(ye[8 + 2 * h], ye[9 + 2 * h]), pack_bf16(ye[12 + 2 * h], ye[13 + 2 * h]));
        stsm_x4_t((ya ^ (16 * h)) + 2048, pack_bf16(yo[2 * h], yo[2 * h + 1]), pack_bf16(yo[4 + 2 * h], yo[5 + 2 * h]),
                  pack_bf16(yo[8 + 2 * h], yo[9 + 2 * h]), pack_bf16(yo[12 + 2 * h], yo[13 + 2 * h]));
    }
    fence_async_smem();
    __syncwarp();
}
}

namespace {

constexpr int S_LEN = 2048;
constexpr int D_DIM = 1024;

#define REG_P 24
#define REG_AB 168
#define REG_C 152
#define BWAIT 0
#define SKEW1 4
#define SKEW2 4
#define QD 4
#define QKB 18
#define QD2 6
#define SLOT4 16
#define EPF 2
#define PFD 7
#define TK_PF0 0
#define TK_KV0 2
#define TK_KV1 4
#define TK_C 8
#define GAP_PF 300
#define GAP_KV 50
#define GAP_ST 50
#define GAP_CV 100
#define GAP_HB 100
#define GAP_Y 100
#define GAP_X 150
#define ALTMAP 0

__device__ __align__(1024) __nv_bfloat16 g_H[2 * D_DIM * S_LEN];
__device__ __align__(1024) __nv_bfloat16 g_y2[D_DIM * S_LEN];
__device__ __align__(1024) __nv_bfloat16 g_kvT[D_DIM * S_LEN];
__device__ __align__(128) float g_gate[S_LEN];
__device__ __align__(128) unsigned long long g_agg[8 * D_DIM];
__device__ __align__(128) unsigned int g_cnt[56 * 32];

#define STAMP(k, s) do { } while (0)
#define SAMPLE(i) do { } while (0)

__device__ __forceinline__ void tma_store_5d(const CUtensorMap* map, uint32_t src, int c0, int c1, int c2, int c3, int c4) {
    asm volatile("cp.async.bulk.tensor.5d.global.shared::cta.bulk_group [%0, {%2, %3, %4, %5, %6}], [%1];"
                 ::"l"((uint64_t)map), "r"(src), "r"(c0), "r"(c1), "r"(c2), "r"(c3), "r"(c4) : "memory");
}
#define ELECT "{\n.reg .pred p;\nelect.sync _|p, 0xffffffff;\n@p "
__device__ __forceinline__ void e_expect_tx(uint32_t bar, uint32_t bytes) {
    asm volatile(ELECT "mbarrier.arrive.expect_tx.shared::cta.b64 _, [%0], %1;\n}" ::"r"(bar), "r"(bytes) : "memory");
}
__device__ __forceinline__ void e_arrive(uint32_t bar) {
    asm volatile(ELECT "mbarrier.arrive.shared::cta.b64 _, [%0];\n}" ::"r"(bar) : "memory");
}
__device__ __forceinline__ void e_load_4d(uint32_t dst, const CUtensorMap* map, uint32_t bar, int c0, int c1, int c2, int c3) {
    asm volatile(ELECT "cp.async.bulk.tensor.4d.shared::cluster.global.mbarrier::complete_tx::bytes [%0], [%1, {%3, %4, %5, %6}], [%2];\n}"
        ::"r"(dst), "l"((uint64_t)map), "r"(bar), "r"(c0), "r"(c1), "r"(c2), "r"(c3) : "memory");
}
__device__ __forceinline__ void e_load_5d(uint32_t dst, const CUtensorMap* map, uint32_t bar, int c0, int c1, int c2, int c3, int c4) {
    asm volatile(ELECT "cp.async.bulk.tensor.5d.shared::cluster.global.mbarrier::complete_tx::bytes [%0], [%1, {%3, %4, %5, %6, %7}], [%2];\n}"
        ::"r"(dst), "l"((uint64_t)map), "r"(bar), "r"(c0), "r"(c1), "r"(c2), "r"(c3), "r"(c4) : "memory");
}
__device__ __forceinline__ void e_bulk_load(uint32_t dst, const void* src, uint32_t bytes, uint32_t bar) {
    asm volatile(ELECT "cp.async.bulk.shared::cluster.global.mbarrier::complete_tx::bytes [%0], [%1], %2, [%3];\n}"
                 ::"r"(dst), "l"(src), "r"(bytes), "r"(bar) : "memory");
}
__device__ __forceinline__ void l2_prefetch(const void* p, uint32_t bytes) {
    asm volatile("cp.async.bulk.prefetch.L2.global [%0], %1;" ::"l"(p), "r"(bytes) : "memory");
}
__device__ __forceinline__ void l2_prefetch_4d(const CUtensorMap* map, int c0, int c1, int c2, int c3) {
    asm volatile("cp.async.bulk.prefetch.tensor.4d.L2.global [%0, {%1, %2, %3, %4}];" ::"l"((uint64_t)map), "r"(c0), "r"(c1), "r"(c2), "r"(c3) : "memory");
}
__device__ __forceinline__ void l2_prefetch_5d(const CUtensorMap* map, int c0, int c1, int c2, int c3, int c4) {
    asm volatile("cp.async.bulk.prefetch.tensor.5d.L2.global [%0, {%1, %2, %3, %4, %5}];" ::"l"((uint64_t)map), "r"(c0), "r"(c1), "r"(c2), "r"(c3), "r"(c4) : "memory");
}
__device__ __forceinline__ unsigned int ld_relaxed(const unsigned int* p) {
    unsigned int v;
    asm volatile("ld.relaxed.gpu.global.u32 %0, [%1];" : "=r"(v) : "l"(p) : "memory");
    return v;
}
__device__ __forceinline__ void fence_async_global() { asm volatile("fence.proxy.async.global;" ::: "memory"); }
__device__ __forceinline__ void wait_counter(const unsigned int* p, unsigned int target) {
    unsigned int v;
    int it = 0;
    do { asm volatile("ld.acquire.gpu.global.u32 %0, [%1];" : "=r"(v) : "l"(p) : "memory"); } while (v != target && ++it < (1 << 22));
    fence_async_global();
}
__device__ __forceinline__ void red_release(unsigned int* p, unsigned int n) {
    asm volatile("red.release.gpu.global.add.u32 [%0], %1;" ::"l"(p), "r"(n) : "memory");
}
__device__ __forceinline__ uint4 ldg128(const void* p) {
    uint4 v;
    asm volatile("ld.global.nc.v4.u32 {%0,%1,%2,%3}, [%4];" : "=r"(v.x), "=r"(v.y), "=r"(v.z), "=r"(v.w) : "l"(p));
    return v;
}
__device__ __forceinline__ void stg128(void* p, uint32_t a, uint32_t b, uint32_t c, uint32_t d) {
    asm volatile("st.global.v4.b32 [%0], {%1, %2, %3, %4};" ::"l"(p), "r"(a), "r"(b), "r"(c), "r"(d) : "memory");
}

template <int TA>
__device__ __forceinline__ void wgmma_n128(float (&d)[64], uint32_t alo, uint32_t blo, int acc) {
    asm volatile(
        "{\n.reg .pred p;\n.reg .b64 da, db;\nsetp.ne.b32 p, %67, 0;\nmov.b64 da, {%64, %69};\nmov.b64 db, {%65, %66};\n"
        "wgmma.mma_async.sync.aligned.m64n128k16.f32.bf16.bf16 "
        "{%0, %1, %2, %3, %4, %5, %6, %7, %8, %9, %10, %11, %12, %13, %14, %15, "
        "%16, %17, %18, %19, %20, %21, %22, %23, %24, %25, %26, %27, %28, %29, %30, %31, "
        "%32, %33, %34, %35, %36, %37, %38, %39, %40, %41, %42, %43, %44, %45, %46, %47, "
        "%48, %49, %50, %51, %52, %53, %54, %55, %56, %57, %58, %59, %60, %61, %62, %63}, "
        "da, db, p, 1, 1, %68, 0;\n"
        "}\n"
        : R8(d, 0), R8(d, 8), R8(d, 16), R8(d, 24), R8(d, 32), R8(d, 40), R8(d, 48), R8(d, 56)
        : "r"(alo), "r"(blo), "n"(HI128), "r"(acc), "n"(TA), "n"(TA ? HI64 : HI128));
}

constexpr int NST = 5;
constexpr int XTRA = SKEW1 - 4;
static_assert(SKEW1 >= 4 && SKEW1 <= 12, "skew");
constexpr int OFF_BB = 4 * 32768;
constexpr int OFF_CT = 5 * 32768;
constexpr int OFF_CU = OFF_CT + 32768;
__host__ __device__ constexpr uint32_t conv_buf(int p) { return OFF_CT + 16384 + (p == 3 ? 0 : p) * 16384; }
constexpr int OFF_PAR = OFF_CU + 32768;
constexpr int OFF_BAR = OFF_PAR + 2048;
constexpr int SMEM_BYTES = OFF_BAR + 896;
static_assert(SMEM_BYTES <= 232448, "smem layout");

static_assert(SLOT4 % 4 == 0 && SLOT4 <= 24, "ring");
constexpr uint32_t PH4 = (SLOT4 / 4 - 1) & 1;
__host__ __device__ constexpr int ring_slot(int kb) { return (kb - SLOT4 + 4) % 5; }
__host__ __device__ constexpr uint32_t ring_par(int kb) { return ((SLOT4 / 4 - 1 + (kb - SLOT4 + 4) / 5) & 1) ^ (ring_slot(kb) == 4 ? PH4 : 0); }

struct Maps {
    CUtensorMap x5, b4, cre, cim, sk, yt, yt3, out, kvst, bre, bim;
};

__device__ __forceinline__ void cmul(float& r, float& i, float ar, float ai, float br, float bi) {
    const float a = ar * br - ai * bi, b = ar * bi + ai * br;
    r = a; i = b;
}
__device__ __forceinline__ void csqr(float& r, float& i) { const float a = r * r - i * i, b = 2.f * r * i; r = a; i = b; }
__device__ __forceinline__ float after(float v, float dep) { return __float_as_uint(dep) == 0x7fedcba9u ? dep : v; }

template <int BMODE>
__global__ void __launch_bounds__(512, 1)
fused_kernel(const __nv_bfloat16* __restrict__ x, const __nv_bfloat16* __restrict__ b_re, const __nv_bfloat16* __restrict__ b_im,
             const __nv_bfloat16* __restrict__ kin, const __nv_bfloat16* __restrict__ vin, const __nv_bfloat16* __restrict__ ssm_k,
             const __nv_bfloat16* __restrict__ shift_k, const __nv_bfloat16* __restrict__ ssm_D,
             const __nv_bfloat16* __restrict__ lam_re, const __nv_bfloat16* __restrict__ lam_im,
             const __nv_bfloat16* __restrict__ log_dt, const __nv_bfloat16* __restrict__ gate_w,
             const __nv_bfloat16* __restrict__ dskip,
             const __nv_bfloat16* __restrict__ c_re, const __nv_bfloat16* __restrict__ c_im,
             const __grid_constant__ Maps maps) {
    constexpr bool MERGED = BMODE != 0, SW = BMODE == 2;
    extern __shared__ __align__(1024) unsigned char smem_raw[];
    const uint32_t sbase = smem_u32(smem_raw);
    const uint32_t bar_full = sbase + OFF_BAR;
    const uint32_t bar_empty = bar_full + 32;
    const uint32_t bar_full2 = bar_empty + 32;
    const uint32_t bar_empty2 = bar_full2 + 40;
    const uint32_t bar_k = bar_empty2 + 40;
    const uint32_t bar_tab = bar_k + 32;
    const uint32_t bar_ab = bar_tab + 8;
    const uint32_t bar_adone = bar_ab + 8;
    const uint32_t bar_par = bar_adone + 8;
    const uint32_t bar_y = bar_par + 8;
    const uint32_t bar_rel = bar_y + 8;
    const uint32_t bar_kvrel = bar_rel + 8;
    const uint32_t bar_yrel = bar_kvrel + 8;
    const uint32_t bar_y1 = bar_yrel + 8;
    const uint32_t bar_fh = bar_y1 + 8;
    const uint32_t bar_tick = bar_fh + 8;
    const uint32_t bar_stg = bar_tick + 104;
    const uint32_t bar_bias = bar_stg + 112;
    const uint32_t bar_hw = bar_bias + 16;
    const uint32_t bar_gate = bar_hw + 8;
    const uint32_t bar_g2 = bar_gate + 8;
    const uint32_t bar_ascan = bar_g2 + 8;
    const uint32_t w_bid = bar_full + 600, w_dsk = bar_full + 608, w_ones = bar_full + 640;
    const int tid = threadIdx.x ^ (((threadIdx.x + 128) & 256) ? 0 : 384);
    if (tid == 384) { prefetch_map(&maps.x5); prefetch_map(&maps.b4); }
    if (EPF && (threadIdx.x >> 5) - 1u < EPF && blockIdx.x < 128) {
        const int ln = threadIdx.x & 31;
        const __nv_bfloat16* p = ln < 16 ? x + (size_t)(blockIdx.x * 16 + ln) * D_DIM : ((ln & 8) ? b_im : b_re) + (size_t)(blockIdx.x * 8 + (ln & 7)) * D_DIM;
        asm volatile("prefetch.global.L2 [%0];" ::"l"(p + ((threadIdx.x >> 5) - 1) * 64) : "memory");
    }
    int bid;
    {
        unsigned int sm, nsm;
        asm volatile("mov.u32 %0, %smid;" : "=r"(sm));
        asm volatile("mov.u32 %0, %nsmid;" : "=r"(nsm));
        const int tpc = sm >> 1, q7 = ((tpc - 32) * 37) >> 8;
        const int gp = tpc < 32 ? tpc & 7 : tpc < 60 ? tpc - 31 - 7 * q7 : 0;
        const int ix = tpc < 32 ? tpc >> 3 : tpc < 60 ? q7 + 4 : ALTMAP ? (tpc - 56) ^ 2 : tpc - 58;
        bid = (ALTMAP ? tpc >= 64 : (tpc | 1) == 61) ? 128 : (4 * (gp >> 1) + (ix >> 1)) * 8 + 4 * (gp & 1) + 2 * (ix & 1) + (sm & 1);
        if (gridDim.x != 132 || nsm != 132) bid = blockIdx.x;
    }
    const int tt = bid >> 3, dt = bid & 7;
    const int ti = tt >> 1;
    const int cg = (dt >> 2) * 8 + (tt & 1) * 4 + (dt & 3);
    if (MERGED && threadIdx.x == 0 && bid < 128) {
        mbar_init(bar_full, 1);
        asm volatile("fence.mbarrier_init.release.cluster;" ::: "memory");
        mbar_expect_tx(bar_full, 49152);
        tma_load_4d(sbase + OFF_CU, &maps.b4, bar_full, 0, 0, 0, cg * 4);
        tma_load_5d(sbase + ((0 - XTRA) & 3) * 32768, &maps.x5, bar_full, 0, 0, 0, 0, ti);
        tma_load_4d(sbase + OFF_BB, &maps.b4, bar_full, 0, 0, 0, 64 + cg * 4);
    }
    __syncwarp();
    const int warp = __shfl_sync(0xffffffffu, tid >> 5, 0), wg = warp >> 2, lane = tid & 31;
    if (warp == 12 && bid < 128) {
        if (lane == 0) {
#pragma unroll
            for (int s = MERGED; s < 4; ++s) mbar_init(bar_full + 8 * s, 1);
            asm volatile("fence.mbarrier_init.release.cluster;" ::: "memory");
        }
        __syncwarp();
        asm volatile("bar.arrive 4, 512;" ::: "memory");
        if (MERGED) {
#pragma unroll 1
            for (int it = 1; it < 4; ++it) {
                e_expect_tx(bar_full + 8 * it, 49152);
                e_load_4d(sbase + OFF_CU + it * 8192, &maps.b4, bar_full + 8 * it, it * 64, 0, 0, cg * 4);
                e_load_5d(sbase + ((it - XTRA) & 3) * 32768, &maps.x5, bar_full + 8 * it, it * 64, 0, 0, 0, ti);
                e_load_4d(sbase + OFF_BB + it * 8192, &maps.b4, bar_full + 8 * it, it * 64, 0, 0, 64 + cg * 4);
            }
        }
    }
    if (bid >= 128) {
        if (tid == 0) {
            __nanosleep(2000);
            const unsigned int target = (ld_relaxed(&g_cnt[32 * 32]) & ~63u) + 64u;
            for (int i = 0; i < 8; ++i)
                for (int it = 0; ld_relaxed(&g_cnt[(40 + i) * 32]) != target && it < (1 << 12); ++it) __nanosleep(500);
        }
        return;
    }
    if (wg == 0) {
        asm volatile("setmaxnreg.dec.sync.aligned.u32 %0;" ::"n"(REG_P));
        if (tid == 32) {
            if (sbase & 1023) __trap();
#pragma unroll
            for (int s = 0; s < 4; ++s) mbar_init(bar_empty + 8 * s, 2);
#pragma unroll
            for (int s = 0; s < NST; ++s) { mbar_init(bar_full2 + 8 * s, 1); mbar_init(bar_empty2 + 8 * s, 1); }
            mbar_init(bar_k, 1); mbar_init(bar_k + 8, 1); mbar_init(bar_k + 16, 1); mbar_init(bar_k + 24, 1);
            mbar_init(bar_tab, 1);
            mbar_init(bar_ab, 1);
            mbar_init(bar_adone, 4);
            mbar_init(bar_par, 2);
            asm volatile("fence.mbarrier_init.release.cluster;" ::: "memory");
        } else if (tid == 64) {
#pragma unroll
            for (int s = 0; s < 19; ++s) mbar_init(bar_y + 8 * s, 1);
        } else if (tid == 96) {
#pragma unroll
            for (int s = 0; s < 11; ++s) mbar_init(bar_stg + 8 * s, 4);
        } else if (tid == 0) {
#pragma unroll
            for (int s = 11; s < 20; ++s) mbar_init(bar_stg + 8 * s, 4);
            asm volatile("st.shared.b32 [%0], %1;" ::"r"(w_bid), "r"(bid) : "memory");
        }
        __syncwarp();
        asm volatile("bar.sync 4, 512;" ::: "memory");
        if (warp == 0) {
#pragma unroll 1
            for (int it = MERGED ? 4 : 0; it < 16 + XTRA; ++it) {
                const int st = it & 3, kb = it < 16 ? it : it - SKEW1;
                const bool fa = it < 16, fb = it < 16 - SKEW1 || it >= 12;
                const uint32_t bf = bar_full + 8 * st;
                mbar_wait(bar_empty + 8 * st, ((it >> 2) & 1) ^ 1);
                e_expect_tx(bf, fa && fb ? 49152 : 40960);
                e_load_5d(sbase + ((it - XTRA) & 3) * 32768, &maps.x5, bf, kb * 64, 0, 0, 0, ti);
                if (MERGED) {
                    if (fa) e_load_4d(sbase + OFF_CU + st * 8192, &maps.b4, bf, kb * 64, 0, 0, cg * 4);
                    if (fb) e_load_4d(sbase + OFF_BB + st * 8192, &maps.b4, bf, kb * 64, 0, 0, 64 + cg * 4);
                } else {
                    if (lane < 16 && ((lane & 8) ? fb : fa))
                        tma_load_2d(sbase + ((lane & 8) ? OFF_BB : OFF_CU) + st * 8192 + (lane & 7) * 1024, (lane & 1) ? &maps.bim : &maps.bre, bf,
                                    kb * 64, (lane >> 3) * 512 + cg * 32 + ((lane & 7) >> 1) * 8);
                    __syncwarp();
                }
                if (it >= 4 && it < 16) e_arrive(bar_tick + 8 * (it - 3));
                if (lane == 0) STAMP(1, 16 + it);
                if (lane == 0 && it < 16) SAMPLE(it - 3);
            }
            int st = 0;
            uint32_t ph = 0;
#pragma unroll 1
            for (int kb = 0; kb < 32; ++kb) {
                const uint32_t bf = bar_full2 + 8 * st;
                mbar_wait(bar_empty2 + 8 * st, st == 4 ? ph ^ PH4 : ph);
                e_expect_tx(bf, 32768);
                e_load_5d(sbase + st * 32768 + 16384, &maps.cre + ((kb >> 3) & 1), bf, ((kb >> 4) * 8 + (kb & 7)) * 64, 0, 0, 0, dt * 4);
                if (lane == 0) STAMP(2, 16 + kb);
                if (lane == 0 && (kb & 3) == 0) SAMPLE(13 + (kb >> 2));
                if (++st == (kb < SLOT4 - 1 ? 4 : 5)) { st = 0; ph ^= 1; }
            }
        } else if (warp == 1) {
            if (MERGED && PFD && lane == 0) {
#pragma unroll 1
                for (int n = 0; n + PFD < 16; ++n) {
                    mbar_wait(bar_tick + 8 * n, 0);
                    if (cg >= 4 && max(cg - PFD, 0) == n) l2_prefetch_5d(&maps.x5, cg * 64, 0, 0, 0, ti);
                    if (ti >= 2 && max(2 * ti - PFD, 0) == n) {
#pragma unroll 1
                        for (int i = 0; i < 4; ++i) l2_prefetch_4d(&maps.b4, (2 * ti + (i >> 1)) * 64, 0, 0, (i & 1) * 64 + cg * 4);
                    }
                }
            }
            __syncwarp();
            const char* hp = reinterpret_cast<const char*>(g_H) + (size_t)tt * 262144;
            mbar_wait(bar_adone, 0);
            e_expect_tx(bar_k + 8, 16384);
            e_expect_tx(bar_k + 16, 16384);
#pragma unroll 1
            for (int c = 2; c < 6; ++c) {
                e_load_4d(sbase + conv_buf(0) + (c >> 1) * 16384 + (c & 1) * 4096 + 8192, &maps.sk, bar_k + 8 * (c >> 1), 0, 0, 0, bid * 8 + c);
                if (GAP_CV) __nanosleep(GAP_CV);
            }
            mbar_wait(bar_kvrel, 0);
            const unsigned int target = lds32(w_bid + 4);
            mbar_wait(bar_rel, 0);
            int st = 0;
            uint32_t ph = 0;
#pragma unroll 1
            for (int q = 0; q < 2; ++q) {
                if (lane == 0) STAMP(0, 8 + 4 * q);
                if (q == 0) wait_counter(&g_cnt[(2 * ti) * 32], target);
                else { mbar_wait(bar_fh, 0); fence_async_global(); }
                if (lane == 0) STAMP(0, 9 + 4 * q);
#pragma unroll 1
                for (int kb = 0; kb < 16; ++kb) {
                    mbar_wait(bar_empty2 + 8 * st, st == 4 ? ph ^ PH4 : ph);
                    e_bulk_load(sbase + st * 32768, hp + kb * 16384, 16384, bar_full2 + 8 * st);
                    if (++st == (16 * q + kb < SLOT4 - 1 ? 4 : 5)) { st = 0; ph ^= 1; }
                }
                hp += 4194304;
            }
        } else if (warp == 2) {
            if (lane == 0) {
                mbar_wait(bar_tick + 8, 0);
                const unsigned int target = (ld_relaxed(&g_cnt[(40 + dt) * 32]) & ~63u) + 64u;
                asm volatile("st.shared.b32 [%0], %1;" ::"r"(w_bid + 4), "r"(target) : "memory");
                prefetch_map(&maps.kvst); prefetch_map(&maps.sk);
#pragma unroll 1
                for (int bt = 0; bt < 2; ++bt) {
                    mbar_wait(bar_stg + 8 * bt, 0);
#pragma unroll 1
                    for (int i = 0; i < 4; ++i) {
                        if (i) __nanosleep(GAP_ST);
                        tma_store_3d(&maps.kvst, sbase + OFF_CT + bt * 16384 + i * 4096, (tt & 1) * 1024 + ti * 128 + 64 * bt, dt * 16, 2 * i);
                    }
                    bulk_commit();
                }
                bulk_wait0();
                fence_async_global();
                red_release(&g_cnt[(40 + dt) * 32], 4);
                mbar_arrive(bar_kvrel);
                STAMP(0, 23);
                mbar_expect_tx(bar_tab, 12288);
                bulk_load(sbase + OFF_CT, &g_conv_tab, 12288, bar_tab);
                mbar_expect_tx(bar_k, 16384);
                tma_load_4d(sbase + conv_buf(0) + 8192, &maps.sk, bar_k, 0, 0, 0, bid * 8);
                tma_load_4d(sbase + conv_buf(0) + 12288, &maps.sk, bar_k, 0, 0, 0, bid * 8 + 1);
                wait_counter(&g_cnt[(40 + (bid >> 4)) * 32], target);
                STAMP(0, 19);
#pragma unroll 1
                for (int p = 0; p < 3; ++p) {
                    if (p == 1) mbar_wait(bar_adone, 0);
                    bulk_load(sbase + conv_buf(p), g_kvT + (size_t)(bid * 8 + 2 * p) * 2048, 8192, bar_k + 8 * p);
                    if (GAP_CV) __nanosleep(GAP_CV);
                }
                prefetch_map(&maps.out); prefetch_map(&maps.yt); prefetch_map(&maps.yt3);
#pragma unroll 1
                for (int p = 0; p < 4; ++p) {
                    mbar_wait(bar_stg + 16 + 8 * p, 0);
                    if (p == 0) {
                        mbar_expect_tx(bar_k + 24, 16384);
                        tma_load_4d(sbase + conv_buf(3) + 8192, &maps.sk, bar_k + 24, 0, 0, 0, bid * 8 + 6);
                        mbar_wait(bar_g2, 0);
                        tma_load_4d(sbase + conv_buf(3) + 12288, &maps.sk, bar_k + 24, 0, 0, 0, bid * 8 + 7);
                    }
#pragma unroll 1
                    for (int i = 0; i < 2; ++i) {
                        if (i) __nanosleep(GAP_Y);
                        asm volatile("cp.async.bulk.global.shared::cta.bulk_group [%0], [%1], 4096;"
                                     ::"l"(g_y2 + (size_t)(bid * 8 + 2 * p + i) * 2048), "r"(sbase + conv_buf(p) + i * 4096) : "memory");
                    }
                    bulk_commit();
                    STAMP(0, 24 + p);
                    if (p == 0) {
                        bulk_wait_read0();
                        bulk_load(sbase + conv_buf(3), g_kvT + (size_t)(bid * 8 + 6) * 2048, 8192, bar_k + 24);
                    }
                    if (p == 2) {
                        bulk_wait0();
                        fence_async_global();
                        red_release(&g_cnt[(48 + (bid >> 4)) * 32], 4);
                        mbar_arrive(bar_yrel);
                        STAMP(0, 3);
                    }
                }
                bulk_wait0();
                fence_async_global();
                red_release(&g_cnt[(32 + (bid >> 4)) * 32], 4);
                STAMP(0, 2);
                wait_counter(&g_cnt[(32 + dt) * 32], target);
                STAMP(0, 5);
                mbar_expect_tx(bar_y, 8192);
#pragma unroll 1
                for (int i = 6; i < 8; ++i)
                    tma_load_5d(sbase + OFF_CU + i * 4096, &maps.yt, bar_y, (tt & 1) * 1024 + ti * 128 + (i & 1) * 64, 0, 0, i >> 1, dt * 4);
#pragma unroll 1
                for (int i = 0; i < 8; ++i) {
                    mbar_wait(bar_stg + 48 + 8 * i, 0);
                    tma_store_5d(&maps.out, sbase + ((i & 4) ? OFF_CT : OFF_CU) + (i & 3) * 8192, dt * 128 + (i & 3) * 32, 0, 0, (tt & 1) * 4 + ((i & 4) >> 1), ti);
                    bulk_commit();
                }
                bulk_wait_read0();
                STAMP(2, 3);
                SAMPLE(21);
            }
        } else if (lane == 0) {
            mbar_wait(bar_tick + 8 * TK_PF0, 0);
#pragma unroll 1
            for (int i = 0; i < 8; ++i) {
                l2_prefetch(((i & 1) ? vin : kin) + (size_t)(ti * 256 + 32 * (i & 4) + (bid & 15) * 8 + 2 * (i & 2)) * D_DIM, 8192);
                __nanosleep(GAP_PF);
            }
            if (bid < 3) l2_prefetch(reinterpret_cast<const char*>(&g_conv_tab) + bid * 4096, 4096);
            prefetch_map(&maps.cre); prefetch_map(&maps.cim);
            mbar_wait(bar_tick + 8 * TK_C, 0);
#pragma unroll 1
            for (int i = 0; i < 8; ++i) {
                l2_prefetch((i & 1) ? ((i & 4) ? c_im : c_re) + (size_t)bid * 8192 + (i & 2) * 2048 : ssm_k + (size_t)bid * 16384 + (i >> 1) * 4096, 8192);
                __nanosleep(GAP_PF);
            }
            const unsigned int target = (ld_relaxed(&g_cnt[(2 * ti + 1) * 32]) & ~63u) + 64u;
            mbar_wait(bar_gate, 0);
            mbar_wait(bar_hw, 0);
            mbar_wait(bar_g2, 0);
            char* hp = reinterpret_cast<char*>(g_H) + (size_t)((16 + 2 * ti) * 16 + (cg >> 1)) * 16384 + (cg & 1) * 2048;
#pragma unroll 1
            for (int i = 0; i < 16; ++i) {
                asm volatile("cp.async.bulk.global.shared::cta.bulk_group [%0], [%1], 2048;"
                             ::"l"(hp + (i & 3) * 4096 + ((i >> 2) & 1) * 262144 + (i >> 3) * 131072), "r"(sbase + OFF_BB + i * 2048) : "memory");
                __nanosleep(GAP_HB);
            }
            bulk_commit();
            bulk_wait0();
            mbar_arrive(bar_empty2 + 32);
            fence_async_global();
            red_release(&g_cnt[(2 * ti + 1) * 32], 4);
            STAMP(0, 38);
            wait_counter(&g_cnt[(2 * ti + 1) * 32], target);
            mbar_arrive(bar_fh);
        }
    } else {
    if (wg == 3) {
        if (warp != 12) asm volatile("bar.sync 4, 512;" ::: "memory");
        named_bar(3, 128);
        asm volatile("setmaxnreg.inc.sync.aligned.u32 %0;" ::"n"(REG_C));
        const int t = tid & 127, w4 = t >> 5;
        if (t == 0) SAMPLE(0);
        mbar_wait(bar_tick, 0);
        if (t < 64) {
            const int ch = (t >> 5) * 512 + cg * 32 + (t & 31);
            unsigned long long oldagg;
            asm volatile("ld.relaxed.gpu.global.u64 %0, [%1];" : "=l"(oldagg) : "l"(&g_agg[ti * D_DIM + ch]) : "memory");
            const float Lr = __bfloat162float(lam_re[ch]), Li = __bfloat162float(lam_im[ch]);
            const float dtv = bf16r(expf(__bfloat162float(log_dt[ch])));
            const unsigned int tag = ((((unsigned int)oldagg & 1u) | ((unsigned int)(oldagg >> 31) & 2u)) + 1u) & 3u;
            const float er = expf(dtv * Lr);
            float s, c;
            sincospif(dtv * Li * 0.318309886183790672f, &s, &c);
            const float lr = er * c, li = er * s;
            const float nr = lr - 1.f, ni = li;
            const float den = Lr * Lr + Li * Li;
            const float cr = 2.f * (nr * Lr + ni * Li) / den, ci = 2.f * (ni * Lr - nr * Li) / den;
            float pr = lr, pi = -li;
#pragma unroll
            for (int i = 0; i < 5; ++i) csqr(pr, pi);
            sts128(sbase + OFF_PAR + t * 32, __float_as_uint(lr), __float_as_uint(-li), __float_as_uint(cr), __float_as_uint(ci));
            sts128(sbase + OFF_PAR + t * 32 + 16, __float_as_uint(pr), __float_as_uint(pi), tag, 0);
            __syncwarp();
            if (lane == 0) mbar_arrive(bar_par);
        }
        if (t >= 120) asm volatile("st.shared.b32 [%0], %1;" ::"r"(w_dsk - 480 + 4 * t),
                                   "r"(t < 124 ? __ldg(reinterpret_cast<const uint32_t*>(ssm_D + bid * 8) + (t & 3)) : 0u) : "memory");
        if (t < 64) asm volatile("st.shared.b32 [%0], %1;" ::"r"(w_ones + 4 * t), "r"(0x3F803F80u) : "memory");
        {
            const int cq = lane & 15, rg = (lane >> 4) + 2 * w4;
            uint32_t sk[4][4];
#pragma unroll
            for (int c = 0; c < 4; ++c) {
                const uint4 w = ldg128(shift_k + (size_t)(dt * 128 + 8 * cq + 2 * c) * 4);
                sk[0][c] = __byte_perm(w.x, w.z, 0x5410); sk[1][c] = __byte_perm(w.x, w.z, 0x7632);
                sk[2][c] = __byte_perm(w.y, w.w, 0x5410); sk[3][c] = __byte_perm(w.y, w.w, 0x7632);
            }
#pragma unroll 1
            for (int bt = 0; bt < 2; ++bt) {
                const int t0 = ti * 256 + 128 * bt + 16 * (rg & 4) + 32 * (tt & 1) + 8 * (rg & 3);
                mbar_wait(bar_tick + 8 * (bt ? TK_KV1 : TK_KV0), 0);
                if (t == 0) STAMP(0, 30 + 3 * bt);
                uint4 kk[11], vv[8];
                const __nv_bfloat16* kp = kin + (size_t)t0 * D_DIM + dt * 128 + 8 * cq;
                const __nv_bfloat16* vp = vin + (size_t)t0 * D_DIM + dt * 128 + 8 * cq;
#pragma unroll
                for (int i = 0; i < 11; ++i) {
                    if (i < 3 && t0 == 0) kk[i] = make_uint4(0, 0, 0, 0);
                    else kk[i] = ldg128(kp + (i - 3) * D_DIM);
                    if (i == 6 || i == 10) __nanosleep(GAP_KV);
                }
#pragma unroll
                for (int i = 0; i < 8; ++i) { vv[i] = ldg128(vp + i * D_DIM); if (i == 3) __nanosleep(GAP_KV); }
                const uint32_t ua = sbase + OFF_CT + bt * 16384 + cq * 128 + ((rg ^ ((2 * ti + bt) & 3) ^ (cq & 7)) << 4);
#pragma unroll
                for (int c = 0; c < 4; ++c) {
                    uint32_t res[8];
#pragma unroll
                    for (int i = 0; i < 8; ++i) {
                        uint32_t ks = hmul((&kk[i].x)[c], sk[3][c]);
                        ks = hadd(ks, hmul((&kk[i + 1].x)[c], sk[2][c]));
                        ks = hadd(ks, hmul((&kk[i + 2].x)[c], sk[1][c]));
                        ks = hadd(ks, hmul((&kk[i + 3].x)[c], sk[0][c]));
                        res[i] = hmul(ks, (&vv[i].x)[c]);
                    }
                    sts128(ua + (2 * c) * 2048, __byte_perm(res[0], res[1], 0x5410), __byte_perm(res[2], res[3], 0x5410),
                           __byte_perm(res[4], res[5], 0x5410), __byte_perm(res[6], res[7], 0x5410));
                    sts128(ua + (2 * c + 1) * 2048, __byte_perm(res[0], res[1], 0x7632), __byte_perm(res[2], res[3], 0x7632),
                           __byte_perm(res[4], res[5], 0x7632), __byte_perm(res[6], res[7], 0x7632));
                }
                fence_async_smem();
                __syncwarp();
                if (lane == 0) mbar_arrive(bar_stg + 8 * bt);
                if (t == 0) STAMP(0, 21 + bt);
            }
        }
        {
            const int row = bid * 16 + (t >> 3);
            uint4 xv[16];
#pragma unroll
            for (int n = 0; n < 16; ++n) {
                xv[n] = ldg128(x + (size_t)row * D_DIM + ((t & 7) + 8 * n) * 8);
                if ((n & 3) == 3) __nanosleep(GAP_KV);
            }
#pragma unroll
            for (int n8 = 0; n8 < 16; n8 += 8) {
                uint4 wv[8];
#pragma unroll
                for (int n = 0; n < 8; ++n) wv[n] = ldg128(gate_w + ((t & 7) + 8 * (n8 + n)) * 8);
#pragma unroll
                for (int n = 0; n < 8; ++n) {
                    uint4& p = xv[n8 + n];
                    p.x = hmul(p.x, wv[n].x); p.y = hmul(p.y, wv[n].y); p.z = hmul(p.z, wv[n].z); p.w = hmul(p.w, wv[n].w);
                }
            }
            float d[4] = {0.f, 0.f, 0.f, 0.f};
            fence_regs(d);
            named_bar(3, 128);
            wgmma_fence();
#pragma unroll
            for (int n = 0; n < 16; ++n)
                asm volatile("{\n.reg .b64 db;\nmov.b64 db, {%8, 8};\n"
                             "wgmma.mma_async.sync.aligned.m64n8k16.f32.bf16.bf16 {%0, %1, %2, %3}, {%4, %5, %6, %7}, db, 1, 1, 1, 0;\n}\n"
                             : "+f"(d[0]), "+f"(d[1]), "+f"(d[2]), "+f"(d[3]) : "r"(xv[n].x), "r"(xv[n].y), "r"(xv[n].z), "r"(xv[n].w), "r"(desc_lo(w_ones, 128)));
            wgmma_commit();
            wgmma_wait<0>();
            fence_regs(d);
#pragma unroll
            for (int n = 0; n < 16; ++n) asm volatile("" ::"r"(xv[n].x), "r"(xv[n].y), "r"(xv[n].z), "r"(xv[n].w) : "memory");
            float sum = d[0] + d[2];
            sum += __shfl_xor_sync(0xffffffffu, sum, 4);
            if ((t & 7) == 0) g_gate[row] = bf16r(1.f / (1.f + expf(-bf16r(sum))));
            if (t == 0) STAMP(0, 4);
            __syncwarp();
            if (lane == 0) mbar_arrive(bar_gate);
        }
    } else {
        asm volatile("setmaxnreg.inc.sync.aligned.u32 %0;" ::"n"(REG_AB));
        if (tid == 128) STAMP(1, 54);
        asm volatile("bar.sync 4, 512;" ::: "memory");
        if (tid == 128) STAMP(1, 55);
        const int cw = wg - 1;
        const int t = tid & 127, w4 = t >> 5, g = lane >> 2, t4 = lane & 3;
        {
            float a0[64], a1[64];
            auto release = [&](int it) {
                if (it < 12 + XTRA && t <= ((it >= 16 - SKEW1 && it < 12) || it >= 16)) mbar_arrive(bar_empty + 8 * (it & 3));
            };
#pragma unroll 1
            for (int kb = 0; kb < 16; ++kb) {
                const int it = cw == 1 && kb >= 16 - SKEW1 ? kb + XTRA : kb, st = it & 3;
                if (cw == 1 && kb == 16 - SKEW1) mbar_wait(bar_ab, 0);
                mbar_wait(bar_full + 8 * st, (it >> 2) & 1);
                if (kb == 0 && tid == 288) mbar_arrive(bar_tick);
                if (kb == 0 && t == 0) STAMP(1, 14 + cw);
                const uint32_t alo = desc_lo(sbase + (cw ? OFF_BB : OFF_CU) + st * 8192, 16), blo = desc_lo(sbase + ((it - XTRA) & 3) * 32768, 16);
                wgmma_fence();
#pragma unroll
                for (int k = 0; k < 4; ++k) {
                    wgmma_n128<0>(a0, alo + 2 * k, blo + 2 * k, k ? 1 : kb);
                    wgmma_n128<0>(a1, alo + 2 * k, blo + 1024 + 2 * k, k ? 1 : kb);
                }
                wgmma_commit();
                wgmma_wait<1>();
                if (kb > 0 && !(cw == 1 && kb == 16 - SKEW1)) release(it - 1);
                if (cw == 1 && kb == 15 - SKEW1) {
                    wgmma_wait<0>();
                    release(it);
                }
                if (cw == 1 && kb > 12) {
                    if (kb == 13) mbar_wait(bar_adone, 0);
                    if (t == 0) mbar_arrive(bar_empty2 + 8 * (kb - 13));
                }
            }
            if (tid == 192) mbar_arrive(bar_ab);
            float mr, mi, cr, ci, p32r, p32i;
            uint32_t tag;
            mbar_wait(bar_par, 0);
            {
                const uint32_t par = sbase + OFF_PAR + (cw * 32 + w4 * 8 + g) * 32;
                uint32_t dummy;
                asm volatile("ld.shared.v4.f32 {%0,%1,%2,%3}, [%4];" : "=f"(mr), "=f"(mi), "=f"(cr), "=f"(ci) : "r"(par));
                asm volatile("ld.shared.v4.b32 {%0,%1,%2,%3}, [%4];" : "=f"(p32r), "=f"(p32i), "=r"(tag), "=r"(dummy) : "r"(par + 16));
            }
            const float l1i = SW ? mi : -mi;
            auto map = [&](float p, float q, float& r, float& i) {
                if (SW) { r = fmaf(cr, q, -ci * p); i = fmaf(-cr, p, -ci * q); }
                else { r = fmaf(cr, p, -ci * q); i = fmaf(-cr, q, -ci * p); }
            };
            float p64r = p32r, p64i = p32i;
            csqr(p64r, p64i);
            float p128r = p64r, p128i = p64i;
            csqr(p128r, p128i);
            wgmma_wait<0>();
            fence_regs(a0); fence_regs(a1);
            if (cw == 0) { release(15); if (lane == 0) mbar_arrive(bar_adone); }
            else if (t == 0) mbar_arrive(bar_empty2 + 24);
            if (t == 0) STAMP(1, 2 + 6 * cw);
            if (BWAIT == 1 && cw == 1) mbar_wait(bar_ascan, 0);
            float hr = 0.f, hi = 0.f, ar = 0.f, ai = 0.f;
#pragma unroll
            for (int j = 0; j < 16; ++j)
#pragma unroll
                for (int e = 0; e < 2; ++e) {
                    const float nr = fmaf(mr, ar, fmaf(-l1i, ai, a0[4 * j + e])), ni = fmaf(mr, ai, fmaf(l1i, ar, a0[4 * j + 2 + e]));
                    const float or_ = fmaf(mr, hr, fmaf(-l1i, hi, a1[4 * j + e])), oi = fmaf(mr, hi, fmaf(l1i, hr, a1[2 + 4 * j + e]));
                    ar = nr; ai = ni; hr = or_; hi = oi;
                }
            map(ar, ai, ar, ai);
            map(hr, hi, hr, hi);
            hr += p32r * ar - p32i * ai; hi += p32r * ai + p32i * ar;
            {
                float vr = __shfl_up_sync(0xffffffffu, hr, 1, 4), vi = __shfl_up_sync(0xffffffffu, hi, 1, 4);
                if (t4 >= 1) { hr += p64r * vr - p64i * vi; hi += p64r * vi + p64i * vr; }
                vr = __shfl_up_sync(0xffffffffu, hr, 2, 4); vi = __shfl_up_sync(0xffffffffu, hi, 2, 4);
                if (t4 >= 2) { hr += p128r * vr - p128i * vi; hi += p128r * vi + p128i * vr; }
            }
            unsigned long long* ap = &g_agg[ti * D_DIM + cw * 512 + cg * 32 + w4 * 8 + g];
            if (t4 == 3) asm volatile("{\n.reg .b64 a;\nmov.b64 a, {%1, %2};\nst.relaxed.gpu.global.u64 [%0], a;\n}\n" ::"l"(ap),
                                      "r"((__float_as_uint(hr) & ~1u) | (tag & 1u)), "r"((__float_as_uint(hi) & ~1u) | (tag >> 1)) : "memory");
            float exr = __shfl_up_sync(0xffffffffu, hr, 1, 4), exi = __shfl_up_sync(0xffffffffu, hi, 1, 4);
            if (t4 == 0) { exr = 0.f; exi = 0.f; }
            if (t == 0) STAMP(1, 3 + 6 * cw);
            if (BWAIT == 2 && cw == 1) mbar_wait(bar_ascan, 0);
            ci = after(ci, exr);
#pragma unroll
            for (int j = 0; j < 16; ++j)
#pragma unroll
                for (int e = 0; e < 2; ++e) {
                    map(a0[4 * j + e], a0[4 * j + 2 + e], a0[4 * j + e], a0[4 * j + 2 + e]);
                    map(a1[4 * j + e], a1[4 * j + 2 + e], a1[4 * j + e], a1[4 * j + 2 + e]);
                }
            float qr = 1.f, qi = 0.f, ur = 1.f, ui = 0.f;
            if (t4 & 1) { qr = p64r; qi = p64i; }
            if (t4 & 2) cmul(qr, qi, qr, qi, p128r, p128i);
            csqr(p128r, p128i);
            if (t4 & 1) { ur = p128r; ui = p128i; }
            csqr(p128r, p128i);
            if (t4 & 2) cmul(ur, ui, ur, ui, p128r, p128i);
            csqr(p128r, p128i);
            fence_regs(a0); fence_regs(a1);
            if (t == 0) STAMP(1, 7 + 6 * cw);
            if (ti > 0) {
                const unsigned long long tmask = 0x0000000100000001ull, tval = ((unsigned long long)(tag >> 1) << 32) | (tag & 1u);
                unsigned long long u0 = tval, u1 = tval;
                ap -= D_DIM * (1 + t4);
                int it = 0;
                do {
                    asm volatile("{\n.reg .pred p, q;\nsetp.gt.s32 p, %3, 0;\nsetp.gt.s32 q, %3, 4;\n@p ld.relaxed.gpu.global.u64 %0, [%2];\n"
                                 "@q ld.relaxed.gpu.global.u64 %1, [%2+-32768];\n}\n" : "+l"(u0), "+l"(u1) : "l"(ap), "r"(ti - t4) : "memory");
                } while (__any_sync(0xffffffffu, (((u0 ^ tval) | (u1 ^ tval)) & tmask) != 0) && ++it < (1 << 22));
                float Pr = __uint_as_float((unsigned)u1 & ~1u), Pi = __uint_as_float((unsigned)(u1 >> 32) & ~1u);
                cmul(Pr, Pi, Pr, Pi, p128r, p128i);
                Pr += __uint_as_float((unsigned)u0 & ~1u); Pi += __uint_as_float((unsigned)(u0 >> 32) & ~1u);
                cmul(Pr, Pi, Pr, Pi, ur, ui);
                Pr += __shfl_xor_sync(0xffffffffu, Pr, 1); Pi += __shfl_xor_sync(0xffffffffu, Pi, 1);
                Pr += __shfl_xor_sync(0xffffffffu, Pr, 2); Pi += __shfl_xor_sync(0xffffffffu, Pi, 2);
                exr += qr * Pr - qi * Pi;
                exi += qr * Pi + qi * Pr;
            }
            if (t == 0) STAMP(1, 4 + 6 * cw);
            char* hp = reinterpret_cast<char*>(g_H) + (size_t)((2 * ti) * 16 + (cg >> 1)) * 16384 + ((cg & 1) * 32 + w4 * 8 + g) * 64 + ((t4 ^ (g >> 1)) << 4);
            float fxr = ar + p32r * exr - p32i * exi, fxi = ai + p32r * exi + p32i * exr;
            const uint32_t hs = sbase + OFF_BB + (w4 * 8 + g) * 64 + ((t4 ^ (g >> 1)) << 4);
            if (cw == 1) named_bar(2, 128);
#pragma unroll
            for (int jj = 0; jj < 4; ++jj) {
                uint32_t pr[4], qq[4], pi[4], qi[4];
#pragma unroll
                for (int j4 = 0; j4 < 4; ++j4) {
                    const int j = jj * 4 + j4;
                    const float r0 = fmaf(mr, exr, fmaf(-mi, exi, a0[4 * j])), i0 = fmaf(mr, exi, fmaf(mi, exr, a0[4 * j + 2]));
                    const float r1 = fmaf(mr, fxr, fmaf(-mi, fxi, a1[4 * j])), i1 = fmaf(mr, fxi, fmaf(mi, fxr, a1[2 + 4 * j]));
                    exr = fmaf(mr, r0, fmaf(-mi, i0, a0[4 * j + 1]));
                    exi = fmaf(mr, i0, fmaf(mi, r0, a0[4 * j + 3]));
                    fxr = fmaf(mr, r1, fmaf(-mi, i1, a1[1 + 4 * j]));
                    fxi = fmaf(mr, i1, fmaf(mi, r1, a1[3 + 4 * j]));
                    pr[j4] = pack_bf16(r0, exr); pi[j4] = pack_bf16(i0, exi);
                    qq[j4] = pack_bf16(r1, fxr); qi[j4] = pack_bf16(i1, fxi);
                }
                if (cw == 0) {
                    stg128(hp + jj * 4096, pr[0], pr[1], pr[2], pr[3]);
                    stg128(hp + jj * 4096 + 262144, qq[0], qq[1], qq[2], qq[3]);
                    stg128(hp + jj * 4096 + 131072, pi[0], pi[1], pi[2], pi[3]);
                    stg128(hp + jj * 4096 + 393216, qi[0], qi[1], qi[2], qi[3]);
                } else {
                    sts128(hs + jj * 2048, pr[0], pr[1], pr[2], pr[3]);
                    sts128(hs + jj * 2048 + 8192, qq[0], qq[1], qq[2], qq[3]);
                    sts128(hs + jj * 2048 + 16384, pi[0], pi[1], pi[2], pi[3]);
                    sts128(hs + jj * 2048 + 24576, qi[0], qi[1], qi[2], qi[3]);
                }
            }
            if (t == 0) STAMP(1, 5 + 6 * cw);
            if (cw == 0) {
                if (BWAIT && lane == 0) mbar_arrive(bar_ascan);
                named_bar(1, 128);
                if (t == 0) { red_release(&g_cnt[(2 * ti) * 32], 4); mbar_arrive(bar_rel); }
                if (t == 0) STAMP(1, 6);
                __syncwarp();
            } else {
                fence_async_smem();
                __syncwarp();
                if (lane == 0) mbar_arrive(bar_hw);
            }
            if (t == 0) STAMP(1, 50 + cw);
        }
        if (cw == 0) {
            float c0[64], c1[64];
            int st = 0, pst = 0;
            uint32_t ph = 0;
            auto kblock = [&](int kb, auto shallow) {
                const int t = fresh_tid() & 127, lane = t & 31;
                mbar_wait(bar_full2 + 8 * st, st == 4 ? ph ^ PH4 : ph);
                if (kb == 0 && t == 0) STAMP(2, 6);
                if (kb == 0 && lane == 0) mbar_arrive(bar_g2);
                const uint32_t alo = desc_lo(sbase + st * 32768, 4096), blo = desc_lo(sbase + st * 32768 + 16384, 16);
                constexpr int Q = decltype(shallow)::value;
#pragma unroll
                for (int j = 0; j < 8; ++j) {
                    wgmma_fence();
                    if (j & 1) wgmma_n128<1>(c1, alo + 512 + 64 * (j >> 1), blo + 2 * (j >> 1), j >> 1 ? 1 : kb);
                    else wgmma_n128<1>(c0, alo + 64 * (j >> 1), blo + 2 * (j >> 1), j >> 1 ? 1 : kb);
                    wgmma_commit();
                    wgmma_wait<Q>();
                    if (j == Q - 1 && kb > 0 && t == 0) mbar_arrive(bar_empty2 + 8 * pst);
                }
                pst = st;
                if (++st == (kb < SLOT4 - 1 ? 4 : 5)) { st = 0; ph ^= 1; }
            };
#pragma unroll 1
            for (int kb = 0; kb < QKB; ++kb) kblock(kb, std::integral_constant<int, QD>());
#pragma unroll 1
            for (int kb = QKB; kb < 32 - SKEW2; ++kb) kblock(kb, std::integral_constant<int, QD2>());
            static_assert(SKEW2 <= 4, "slot release");
            const uint32_t alo = desc_lo(sbase, 4096), blo = desc_lo(sbase + 16384, 16);
#pragma unroll
            for (int kb = 32 - SKEW2; kb < 32; ++kb) {
                mbar_wait(bar_full2 + 8 * ring_slot(kb), ring_par(kb));
                wgmma_fence();
#pragma unroll
                for (int k = 0; k < 4; ++k) wgmma_n128<1>(c0, alo + ring_slot(kb) * 2048 + 64 * k, blo + ring_slot(kb) * 2048 + 2 * k, 1);
                wgmma_commit();
            }
            auto late = [&](int kb) {
                wgmma_fence();
#pragma unroll
                for (int k = 0; k < 4; ++k) wgmma_n128<1>(c1, alo + 512 + ring_slot(kb) * 2048 + 64 * k, blo + ring_slot(kb) * 2048 + 2 * k, 1);
                wgmma_commit();
            };
            late(32 - SKEW2);
            const int t = fresh_tid() & 127, lane = t & 31, w4 = t >> 5, g = lane >> 2, t4 = lane & 3;
            auto epilogue = [&](const float (&a)[64], int b) {
                const uint32_t ad0 = sbase + (b ? OFF_CT : OFF_CU) + (w4 * 16 + g) * 128 + (((2 * t4) ^ g) << 4);
                float gt[2];
                uint32_t bv[4][4];
#pragma unroll
                for (int h = 0; h < 2; ++h) gt[h] = __uint_as_float(lds32(sbase + OFF_PAR + (64 * b + 16 * w4 + 8 * h + g) * 4));
#pragma unroll
                for (int i = 0; i < 4; ++i)
                    asm volatile("ld.shared.v4.b32 {%0,%1,%2,%3}, [%4];" : "=r"(bv[i][0]), "=r"(bv[i][1]), "=r"(bv[i][2]), "=r"(bv[i][3])
                                 : "r"(ad0 + (i & 1) * 1024 + (i >> 1) * 8192) : "memory");
                if (b == 0) wgmma_wait<1>(); else wgmma_wait<0>();
                if (b == 0) fence_regs(c0); else fence_regs(c1);
                if (t == 0) STAMP(2, b ? 2 : 5);
#pragma unroll
                for (int jq = 0; jq < 4; ++jq) {
#pragma unroll
                    for (int h = 0; h < 2; ++h) {
                        const uint32_t ad = ad0 + h * 1024 + jq * 8192;
                        uint32_t (&w)[4] = bv[2 * (jq & 1) + h];
                        const int r = 16 * jq + 2 * h;
                        sts128(ad, __float_as_uint(fmaf(gt[h], a[r], bf_lo(w[0]))), __float_as_uint(fmaf(gt[h], a[r + 1], bf_hi(w[0]))),
                               __float_as_uint(fmaf(gt[h], a[r + 4], bf_lo(w[1]))), __float_as_uint(fmaf(gt[h], a[r + 5], bf_hi(w[1]))));
                        sts128(ad ^ 16, __float_as_uint(fmaf(gt[h], a[r + 8], bf_lo(w[2]))), __float_as_uint(fmaf(gt[h], a[r + 9], bf_hi(w[2]))),
                               __float_as_uint(fmaf(gt[h], a[r + 12], bf_lo(w[3]))), __float_as_uint(fmaf(gt[h], a[r + 13], bf_hi(w[3]))));
                        if (jq < 2) asm volatile("ld.shared.v4.b32 {%0,%1,%2,%3}, [%4];" : "=r"(w[0]), "=r"(w[1]), "=r"(w[2]), "=r"(w[3]) : "r"(ad + 16384) : "memory");
                    }
                    fence_async_smem();
                    __syncwarp();
                    if (lane == 0) mbar_arrive(bar_stg + 48 + 32 * b + 8 * jq);
                    if (b == 0 && jq < SKEW2 - 1) late(33 - SKEW2 + jq);
                }
            };
            mbar_wait(bar_bias, 0);
            if (t == 0) STAMP(2, 4);
            epilogue(c0, 0);
            mbar_wait(bar_bias + 8, 0);
            epilogue(c1, 1);
            if (t == 0) STAMP(2, 7);
            return;
        }
        asm volatile("setmaxnreg.dec.sync.aligned.u32 %0;" ::"n"(REG_C));
    }
    {
        {
            const int t = fresh_tid() & 127, lane = t & 31, w4 = t >> 5;
            Twiddle tw;
            load_twiddle(tw, reinterpret_cast<const uint4*>(g_tw_tab.w) + t);
            const uint32_t lo = (uint32_t)((16 * w4 + (lane & 7)) * 64 + (((lane >> 3) ^ ((lane >> 1) & 3)) << 4));
            const uint32_t tlo = desc_lo(sbase + OFF_CT, 16);
            float dE[32], dO[32];
            int p = wg == 2 ? 2 : 0;
            mbar_wait(bar_stg, 0);
            mbar_wait(bar_tab, 0);
            mbar_wait(bar_k + 8 * p, 0);
            if (BWAIT == 3) mbar_wait(bar_ascan, 0);
            if (t == 0) STAMP(0, wg == 2 ? 50 : 1);
            wgmma_fence();
            conv_s1(dE, dO, tlo, desc_lo(sbase + conv_buf(0) + p * 16384, 8192));
            wgmma_commit();
            wgmma_wait<0>();
            fence_regs(dE); fence_regs(dO);
            named_bar(wg, 128);
#pragma unroll 1
            for (; p < 4; p = 2 * p + 1) {
                const int pn = p < 2 ? 2 * p + 1 : p;
                if (t == 0) STAMP(0, 40 + 2 * p);
                conv_pair(dE, dO, tw, lds32(w_dsk + ((lane & 3) ? 16 : 4 * p)), tlo, sbase + conv_buf(p), sbase + conv_buf(pn), lo, wg,
                                [&]() { mbar_wait(bar_k + 8 * pn, 0); });
                if (lane == 0) mbar_arrive(bar_stg + 16 + 8 * p);
            }
            if (t == 0) STAMP(0, 57 + wg);
            __syncwarp();
        }
        if (wg == 2) {
            {
            const int t = fresh_tid() & 127, lane = t & 31, w4 = t >> 5, g = lane >> 2, t4 = lane & 3;
            const int bid = lds32(w_bid), dt = bid & 7;
            const int trow = (bid >> 4) * 256 + 4 * (bid & 8) + 128 * (w4 & 1) + 8 * (w4 >> 1) + g;
            uint4 xv[16], dk[4];
            const __nv_bfloat16* xp = x + (size_t)trow * D_DIM + dt * 128 + 8 * t4;
#pragma unroll
            for (int i = 0; i < 16; ++i) {
                xv[i] = ldg128(xp + (size_t)(16 * (i >> 3) + 64 * ((i >> 2) & 1)) * D_DIM + 32 * (i & 3));
                if (i & 1) __nanosleep(GAP_X);
            }
#pragma unroll
            for (int jq = 0; jq < 4; ++jq) dk[jq] = ldg128(dskip + dt * 128 + 32 * jq + 8 * t4);
            mbar_wait(bar_fh, 0);
            uint32_t omg[4], g2[4];
#pragma unroll
            for (int i = 0; i < 4; ++i) {
                const float gt = __ldcg(g_gate + trow + 16 * (i >> 1) + 64 * (i & 1));
                if (t4 == 0) asm volatile("st.shared.f32 [%0], %1;" ::"r"(sbase + OFF_PAR + (64 * (i >> 1) + 16 * w4 + 8 * (i & 1) + g) * 4), "f"(gt) : "memory");
                omg[i] = pack_bf16(2.f - 2.f * gt, 2.f - 2.f * gt); g2[i] = pack_bf16(gt, gt);
            }
            if (t == 0) {
                mbar_wait(bar_yrel, 0);
                wait_counter(&g_cnt[(48 + dt) * 32], lds32(w_bid + 4));
                STAMP(0, 16);
                mbar_expect_tx(bar_y1, 24576);
                tma_load_5d(sbase + OFF_CU, &maps.yt3, bar_y1, (bid & 8) * 128 + (bid >> 4) * 128, 0, 0, 0, dt * 4);
                tma_load_5d(sbase + OFF_CU + 12288, &maps.yt3, bar_y1, (bid & 8) * 128 + (bid >> 4) * 128 + 64, 0, 0, 0, dt * 4);
            }
            __syncwarp();
            uint32_t ya = sbase + OFF_CU + (w4 & 1) * 12288 + (lane >> 3) * 3072 + (lane & 7) * 128 + ((((w4 >> 1) ^ ((bid >> 3 & 2) + (w4 & 1))) ^ (lane & 7)) << 4);
#pragma unroll
            for (int p = 0; p < 4; ++p) {
                if (p == 0) { mbar_wait(bar_y1, 0); if (t == 0) STAMP(0, 18); }
                if (p == 3) {
                    if (t == 0) STAMP(0, 17);
                    ya += 21504 - (w4 & 1) * 8192 - (lane >> 3) * 2048;
                    mbar_wait(bar_y, 0);
                    if (t == 0) STAMP(0, 6);
                }
#pragma unroll
                for (int i = 0; i < 4; ++i) {
                    uint32_t yw[4];
                    ldsm_x4_t(yw[0], yw[1], yw[2], yw[3], (ya ^ ((i & 1) << 6) ^ ((i & 2) << 4)) + p * 1024);
#pragma unroll
                    for (int jq = 0; jq < 4; ++jq) {
                        uint32_t& w = (&xv[4 * i + jq].x)[p];
                        w = hfma(g2[i], hmul(w, (&dk[jq].x)[p]), hmul(omg[i], hmul(w, yw[jq])));
                    }
                }
            }
            named_bar(2, 128);
#pragma unroll
            for (int i = 0; i < 16; ++i) {
                sts128(sbase + (i & 8 ? OFF_CT : OFF_CU) + (i & 3) * 8192 + (w4 * 16 + g + (i & 4) * 2) * 128 + (((2 * t4) ^ g) << 4), xv[i].x, xv[i].y, xv[i].z, xv[i].w);
                if ((i & 7) == 7) {
                    __syncwarp();
                    if (lane == 0) mbar_arrive(bar_bias + (i & 8));
                }
            }
            if (t == 0) STAMP(0, 7);
            }
        }
    }
    }
}

void make_map(CUtensorMap* m, const void* ptr, int rank, const cuuint64_t* dims, const cuuint64_t* strides, const cuuint32_t* box,
              CUtensorMapSwizzle swz, bool f32 = false) {
    cuuint32_t es[5] = {1, 1, 1, 1, 1};
    get_encode()(m, f32 ? CU_TENSOR_MAP_DATA_TYPE_FLOAT32 : CU_TENSOR_MAP_DATA_TYPE_BFLOAT16, rank, const_cast<void*>(ptr), dims, strides, box, es,
                 CU_TENSOR_MAP_INTERLEAVE_NONE, swz, CU_TENSOR_MAP_L2_PROMOTION_L2_256B, CU_TENSOR_MAP_FLOAT_OOB_FILL_NONE);
}
void make_map_2d(CUtensorMap* m, const void* ptr, uint64_t inner, uint64_t outer, uint32_t box_in, uint32_t box_out) {
    cuuint64_t dims[2] = {inner, outer};
    cuuint64_t strides[1] = {inner * 2};
    cuuint32_t box[2] = {box_in, box_out};
    make_map(m, ptr, 2, dims, strides, box, CU_TENSOR_MAP_SWIZZLE_128B);
}
void make_map_conv(CUtensorMap* m, const void* p, uint32_t nch = 2) {
    cuuint64_t dims[4] = {32, 32, 2, 1024};
    cuuint64_t strides[3] = {128, 64, 4096};
    cuuint32_t box[4] = {32, 32, 2, nch};
    make_map(m, p, 4, dims, strides, box, CU_TENSOR_MAP_SWIZZLE_64B);
}

}

extern "C" void kernel_launch(void* const* d_in, const int* in_sizes, int n_in, void* d_out, int out_size) {
    const __nv_bfloat16* x = (const __nv_bfloat16*)d_in[0];
    const __nv_bfloat16* lam_re = (const __nv_bfloat16*)d_in[1];
    const __nv_bfloat16* lam_im = (const __nv_bfloat16*)d_in[2];
    const __nv_bfloat16* b_re = (const __nv_bfloat16*)d_in[3];
    const __nv_bfloat16* b_im = (const __nv_bfloat16*)d_in[4];
    const __nv_bfloat16* c_re = (const __nv_bfloat16*)d_in[5];
    const __nv_bfloat16* c_im = (const __nv_bfloat16*)d_in[6];
    const __nv_bfloat16* log_dt = (const __nv_bfloat16*)d_in[7];
    const __nv_bfloat16* dskip = (const __nv_bfloat16*)d_in[8];
    const __nv_bfloat16* kin = (const __nv_bfloat16*)d_in[10];
    const __nv_bfloat16* vin = (const __nv_bfloat16*)d_in[11];
    const __nv_bfloat16* shift_k = (const __nv_bfloat16*)d_in[12];
    const __nv_bfloat16* ssm_k = (const __nv_bfloat16*)d_in[13];
    const __nv_bfloat16* ssm_D = (const __nv_bfloat16*)d_in[14];
    const __nv_bfloat16* gate_w = (const __nv_bfloat16*)d_in[15];
    float* out = (float*)d_out;

    void *yptr = nullptr, *kvtptr = nullptr;
    cudaGetSymbolAddress(&yptr, g_y2);
    cudaGetSymbolAddress(&kvtptr, g_kvT);

    Maps maps;
    {
        cuuint64_t dims[5] = {1024, 2, 4, 32, 8};
        cuuint64_t strides[4] = {2048, 64 * 2048, 2 * 2048, 256 * 2048};
        cuuint32_t box[5] = {64, 2, 4, 32, 1};
        make_map(&maps.x5, x, 5, dims, strides, box, CU_TENSOR_MAP_SWIZZLE_128B);
    }
    int bmode = 0;
    {
        const uint64_t a = (uint64_t)b_re, b = (uint64_t)b_im;
        const uint64_t delta = a < b ? b - a : a - b;
        if (delta != 0 && (delta & 15) == 0 && delta < (1ull << 40)) bmode = a < b ? 1 : 2;
        cuuint64_t dims[4] = {1024, 8, 2, 128};
        cuuint64_t strides[3] = {2048, bmode ? delta : 16, 16384};
        cuuint32_t box[4] = {64, 8, 2, 4};
        make_map(&maps.b4, a < b ? b_re : b_im, 4, dims, strides, box, CU_TENSOR_MAP_SWIZZLE_128B);
    }
    make_map_2d(&maps.bre, b_re, 1024, 1024, 64, 8);
    make_map_2d(&maps.bim, b_im, 1024, 1024, 64, 8);
    {
        cuuint64_t dims[3] = {S_LEN, 128, 8};
        cuuint64_t strides[2] = {8 * 4096, 4096};
        cuuint32_t box[3] = {64, 16, 2};
        make_map(&maps.kvst, kvtptr, 3, dims, strides, box, CU_TENSOR_MAP_SWIZZLE_128B);
    }
    make_map_conv(&maps.sk, ssm_k, 1);
    for (int i = 0; i < 2; ++i) {
        cuuint64_t dims[5] = {1024, 2, 4, 4, 32};
        cuuint64_t strides[4] = {2048, 8 * 2048, 2 * 2048, 32 * 2048};
        cuuint32_t box[5] = {64, 2, 4, 4, 4};
        make_map(i ? &maps.cim : &maps.cre, i ? c_im : c_re, 5, dims, strides, box, CU_TENSOR_MAP_SWIZZLE_128B);
    }
    {
        cuuint64_t dims[5] = {S_LEN, 2, 4, 4, 32};
        cuuint64_t strides[4] = {4096, 8 * 4096, 2 * 4096, 32 * 4096};
        cuuint32_t box[5] = {64, 2, 4, 1, 4};
        make_map(&maps.yt, yptr, 5, dims, strides, box, CU_TENSOR_MAP_SWIZZLE_128B);
        box[3] = 3;
        make_map(&maps.yt3, yptr, 5, dims, strides, box, CU_TENSOR_MAP_SWIZZLE_128B);
    }
    {
        cuuint64_t dims[5] = {D_DIM, 8, 4, 8, 8};
        cuuint64_t strides[4] = {4096, 64 * 4096, 8 * 4096, 256 * 4096};
        cuuint32_t box[5] = {32, 8, 4, 2, 1};
        make_map(&maps.out, out, 5, dims, strides, box, CU_TENSOR_MAP_SWIZZLE_128B, true);
    }

    auto kern = bmode == 1 ? fused_kernel<1> : bmode == 2 ? fused_kernel<2> : fused_kernel<0>;
    cudaFuncSetAttribute(kern, cudaFuncAttributeMaxDynamicSharedMemorySize, SMEM_BYTES);
    static int grid = 0;
    if (!grid) {
        int dev = 0, sms = 0;
        cudaGetDevice(&dev);
        cudaDeviceGetAttribute(&sms, cudaDevAttrMultiProcessorCount, dev);
        grid = sms == 132 ? 132 : 128;
    }
    kern<<<grid, 512, SMEM_BYTES>>>(x, b_re, b_im, kin, vin, ssm_k, shift_k, ssm_D, lam_re, lam_im, log_dt, gate_w, dskip, c_re, c_im, maps);
}
```

```cpp
#include <cuda_runtime.h>
#include <cuda_bf16.h>
#include <cuda.h>
#include <stdint.h>
#include <type_traits>

namespace {
__device__ __forceinline__ uint32_t smem_u32(const void* p) { return (uint32_t)__cvta_generic_to_shared(p); }
__device__ __forceinline__ void mbar_init(uint32_t bar, uint32_t count) {
    asm volatile("mbarrier.init.shared::cta.b64 [%0], %1;" ::"r"(bar), "r"(count) : "memory");
}
__device__ __forceinline__ void mbar_expect_tx(uint32_t bar, uint32_t bytes) {
    asm volatile("mbarrier.arrive.expect_tx.shared::cta.b64 _, [%0], %1;" ::"r"(bar), "r"(bytes) : "memory");
}
__device__ __forceinline__ void mbar_arrive(uint32_t bar) {
    asm volatile("mbarrier.arrive.shared::cta.b64 _, [%0];" ::"r"(bar) : "memory");
}
__device__ __forceinline__ void mbar_wait(uint32_t bar, uint32_t parity) {
    asm volatile(
        "{\n"
        ".reg .pred p;\n"
        ".reg .u32 n;\n"
        "mov.u32 n, 0;\n"
        "LAB_WAIT:\n"
        "mbarrier.try_wait.parity.shared::cta.b64 p, [%0], %1;\n"
        "@p bra LAB_DONE;\n"
        "add.u32 n, n, 1;\n"
        "setp.lt.u32 p, n, 0x400000;\n"
        "@p bra LAB_WAIT;\n"
        "trap;\n"
        "LAB_DONE:\n"
        "}\n" ::"r"(bar), "r"(parity) : "memory");
}
__device__ __forceinline__ void tma_load_2d(uint32_t dst, const CUtensorMap* map, uint32_t bar, int c0, int c1) {
    asm volatile(
        "cp.async.bulk.tensor.2d.shared::cluster.global.mbarrier::complete_tx::bytes [%0], [%1, {%3, %4}], [%2];"
        ::"r"(dst), "l"((uint64_t)map), "r"(bar), "r"(c0), "r"(c1) : "memory");
}
__device__ __forceinline__ void tma_load_4d(uint32_t dst, const CUtensorMap* map, uint32_t bar, int c0, int c1, int c2, int c3) {
    asm volatile(
        "cp.async.bulk.tensor.4d.shared::cluster.global.mbarrier::complete_tx::bytes [%0], [%1, {%3, %4, %5, %6}], [%2];"
        ::"r"(dst), "l"((uint64_t)map), "r"(bar), "r"(c0), "r"(c1), "r"(c2), "r"(c3) : "memory");
}
__device__ __forceinline__ void tma_load_5d(uint32_t dst, const CUtensorMap* map, uint32_t bar, int c0, int c1, int c2, int c3, int c4) {
    asm volatile(
        "cp.async.bulk.tensor.5d.shared::cluster.global.mbarrier::complete_tx::bytes [%0], [%1, {%3, %4, %5, %6, %7}], [%2];"
        ::"r"(dst), "l"((uint64_t)map), "r"(bar), "r"(c0), "r"(c1), "r"(c2), "r"(c3), "r"(c4) : "memory");
}
__device__ __forceinline__ void bulk_load(uint32_t dst, const void* src, uint32_t bytes, uint32_t bar) {
    asm volatile("cp.async.bulk.shared::cluster.global.mbarrier::complete_tx::bytes [%0], [%1], %2, [%3];"
                 ::"r"(dst), "l"(src), "r"(bytes), "r"(bar) : "memory");
}
__device__ __forceinline__ void tma_store_3d(const CUtensorMap* map, uint32_t src, int c0, int c1, int c2) {
    asm volatile("cp.async.bulk.tensor.3d.global.shared::cta.bulk_group [%0, {%2, %3, %4}], [%1];"
                 ::"l"((uint64_t)map), "r"(src), "r"(c0), "r"(c1), "r"(c2) : "memory");
}
__device__ __forceinline__ void bulk_commit() { asm volatile("cp.async.bulk.commit_group;" ::: "memory"); }
__device__ __forceinline__ void bulk_wait0() { asm volatile("cp.async.bulk.wait_group 0;" ::: "memory"); }
__device__ __forceinline__ void bulk_wait_read0() { asm volatile("cp.async.bulk.wait_group.read 0;" ::: "memory"); }
__device__ __forceinline__ void fence_async_smem() { asm volatile("fence.proxy.async.shared::cta;" ::: "memory"); }
__device__ __forceinline__ void named_bar(int id, int n) { asm volatile("bar.sync %0, %1;" ::"r"(id), "r"(n) : "memory"); }
__device__ __forceinline__ void sts128(uint32_t addr, uint32_t a, uint32_t b, uint32_t c, uint32_t d) {
    asm volatile("st.shared.v4.b32 [%0], {%1, %2, %3, %4};" ::"r"(addr), "r"(a), "r"(b), "r"(c), "r"(d) : "memory");
}
__device__ __forceinline__ void prefetch_map(const CUtensorMap* m) {
    asm volatile("prefetch.tensormap [%0];" ::"l"((uint64_t)m) : "memory");
}
__device__ __forceinline__ void wgmma_fence() { asm volatile("wgmma.fence.sync.aligned;" ::: "memory"); }
__device__ __forceinline__ void wgmma_commit() { asm volatile("wgmma.commit_group.sync.aligned;" ::: "memory"); }
template <int N>
__device__ __forceinline__ void wgmma_wait() { asm volatile("wgmma.wait_group.sync.aligned %0;" ::"n"(N) : "memory"); }
template <int N>
__device__ __forceinline__ void fence_regs(float (&a)[N]) {
#pragma unroll
    for (int i = 0; i < N; ++i) asm volatile("" : "+f"(a[i])::"memory");
}
template <int N>
__device__ __forceinline__ void fence_regs(uint32_t (&a)[N]) {
#pragma unroll
    for (int i = 0; i < N; ++i) asm volatile("" : "+r"(a[i])::"memory");
}
#define R8(a, i) "+f"(a[i + 0]), "+f"(a[i + 1]), "+f"(a[i + 2]), "+f"(a[i + 3]), "+f"(a[i + 4]), "+f"(a[i + 5]), "+f"(a[i + 6]), "+f"(a[i + 7])
#define REGS32 "{%0, %1, %2, %3, %4, %5, %6, %7, %8, %9, %10, %11, %12, %13, %14, %15, %16, %17, %18, %19, %20, %21, %22, %23, %24, %25, %26, %27, %28, %29, %30, %31}"
#define REGS16 "{%0, %1, %2, %3, %4, %5, %6, %7, %8, %9, %10, %11, %12, %13, %14, %15}"

__host__ __device__ constexpr uint32_t desc_hi(uint32_t sbo, uint32_t mode) { return (sbo >> 4) | (mode << 30); }
__device__ __forceinline__ uint32_t desc_lo(uint32_t saddr, uint32_t lbo) { return ((saddr & 0x3FFFF) >> 4) | ((lbo >> 4) << 16); }
constexpr uint32_t HI128 = desc_hi(1024, 1), HI64 = desc_hi(512, 2);
#define W8(a, i) "=f"(a[i + 0]), "=f"(a[i + 1]), "=f"(a[i + 2]), "=f"(a[i + 3]), "=f"(a[i + 4]), "=f"(a[i + 5]), "=f"(a[i + 6]), "=f"(a[i + 7])
template <int TA, int TB, int ACC, uint32_t AHI, uint32_t BHI>
__device__ __forceinline__ void wgmma_n64_ss(float (&d)[32], uint32_t alo, uint32_t blo) {
#define N64_TEXT "{\n.reg .pred p;\n.reg .b64 da, db;\nsetp.ne.b32 p, %36, 0;\nmov.b64 da, {%32, %37};\nmov.b64 db, {%33, %38};\n" \
        "wgmma.mma_async.sync.aligned.m64n64k16.f32.bf16.bf16 " REGS32 ", da, db, p, 1, 1, %34, %35;\n}\n"
    if (ACC) asm volatile(N64_TEXT : R8(d, 0), R8(d, 8), R8(d, 16), R8(d, 24) : "r"(alo), "r"(blo), "n"(TA), "n"(TB), "n"(ACC), "n"(AHI), "n"(BHI));
    else asm volatile(N64_TEXT : W8(d, 0), W8(d, 8), W8(d, 16), W8(d, 24) : "r"(alo), "r"(blo), "n"(TA), "n"(TB), "n"(ACC), "n"(AHI), "n"(BHI));
}
template <int ACC, int SA>
__device__ __forceinline__ void wgmma_n32_tt(float (&d)[16], uint32_t alo, uint32_t blo) {
#define N32T_TEXT "{\n.reg .pred p;\n.reg .b64 da, db;\nsetp.ne.b32 p, %18, 0;\nmov.b64 da, {%16, %19};\nmov.b64 db, {%17, %20};\n" \
        "wgmma.mma_async.sync.aligned.m64n32k16.f32.bf16.bf16 " REGS16 ", da, db, p, %21, 1, 1, 1;\n}\n"
    if (ACC) asm volatile(N32T_TEXT : R8(d, 0), R8(d, 8) : "r"(alo), "r"(blo), "n"(ACC), "n"(HI64), "n"(HI128), "n"(SA));
    else asm volatile(N32T_TEXT : W8(d, 0), W8(d, 8) : "r"(alo), "r"(blo), "n"(ACC), "n"(HI64), "n"(HI128), "n"(SA));
}
__device__ __forceinline__ void wgmma_n16_rs(float (&d)[8], const uint32_t (&a)[4], uint32_t blo) {
    asm volatile("{\n.reg .pred p;\n.reg .b64 db;\nsetp.ne.b32 p, 0, 0;\nmov.b64 db, {%12, %13};\n"
        "wgmma.mma_async.sync.aligned.m64n16k16.f32.bf16.bf16 {%0, %1, %2, %3, %4, %5, %6, %7}, {%8, %9, %10, %11}, db, p, 1, 1, 0;\n}\n"
        : W8(d, 0) : "r"(a[0]), "r"(a[1]), "r"(a[2]), "r"(a[3]), "r"(blo), "n"(HI128));
}

__device__ __forceinline__ float bf16r(float x) { return __bfloat162float(__float2bfloat16_rn(x)); }
__device__ __forceinline__ uint32_t pack_bf16(float lo, float hi) {
    __nv_bfloat162 v = __floats2bfloat162_rn(lo, hi);
    return *reinterpret_cast<uint32_t*>(&v);
}
__device__ __forceinline__ __nv_bfloat162 as_bf2(uint32_t w) { return *reinterpret_cast<__nv_bfloat162*>(&w); }
__device__ __forceinline__ uint32_t as_u32(__nv_bfloat162 v) { return *reinterpret_cast<uint32_t*>(&v); }
__device__ __forceinline__ float bf_lo(uint32_t w) { return __uint_as_float(w << 16); }
__device__ __forceinline__ float bf_hi(uint32_t w) { return __uint_as_float(w & 0xFFFF0000u); }
__device__ __forceinline__ void ldsm_x4_t(uint32_t& r0, uint32_t& r1, uint32_t& r2, uint32_t& r3, uint32_t addr) {
    asm volatile("ldmatrix.sync.aligned.m8n8.x4.trans.shared.b16 {%0,%1,%2,%3}, [%4];"
                 : "=r"(r0), "=r"(r1), "=r"(r2), "=r"(r3) : "r"(addr) : "memory");
}
__device__ __forceinline__ void stsm_x4(uint32_t addr, uint32_t r0, uint32_t r1, uint32_t r2, uint32_t r3) {
    asm volatile("stmatrix.sync.aligned.m8n8.x4.shared.b16 [%0], {%1,%2,%3,%4};"
                 ::"r"(addr), "r"(r0), "r"(r1), "r"(r2), "r"(r3) : "memory");
}
__device__ __forceinline__ void stsm_x4_t(uint32_t addr, uint32_t r0, uint32_t r1, uint32_t r2, uint32_t r3) {
    asm volatile("stmatrix.sync.aligned.m8n8.x4.trans.shared.b16 [%0], {%1,%2,%3,%4};"
                 ::"r"(addr), "r"(r0), "r"(r1), "r"(r2), "r"(r3) : "memory");
}
__device__ __forceinline__ uint32_t lds32(uint32_t addr) {
    uint32_t v;
    asm volatile("ld.shared.b32 %0, [%1];" : "=r"(v) : "r"(addr));
    return v;
}

typedef CUresult (*EncodeFn)(CUtensorMap*, CUtensorMapDataType, cuuint32_t, void*, const cuuint64_t*, const cuuint64_t*,
                             const cuuint32_t*, const cuuint32_t*, CUtensorMapInterleave, CUtensorMapSwizzle,
                             CUtensorMapL2promotion, CUtensorMapFloatOOBfill);
EncodeFn get_encode() {
    static EncodeFn fn = nullptr;
    if (!fn) {
        void* p = nullptr;
        cudaDriverEntryPointQueryResult qres;
        cudaGetDriverEntryPoint("cuTensorMapEncodeTiled", &p, cudaEnableDefault, &qres);
        fn = (EncodeFn)p;
    }
    return fn;
}
}
namespace {
constexpr double c_pi = 3.14159265358979323846;
constexpr double c_cos256(int i) {
    i &= 255;
    if (i > 128) i = 256 - i;
    double sgn = 1.0;
    if (i > 64) { i = 128 - i; sgn = -1.0; }
    if (i == 64) return 0.0;
    double x = 2.0 * c_pi * i / 256.0, x2 = x * x, term = 1.0, sum = 1.0;
    for (int k = 1; k < 20; ++k) { term *= -x2 / ((2 * k - 1) * (2 * k)); sum += term; }
    return sgn * sum;
}
constexpr uint32_t c_bf16(double v) {
    if (v == 0.0) return 0u;
    uint32_t s = v < 0 ? 0x8000u : 0u;
    double a = v < 0 ? -v : v;
    int e = 0;
    while (a >= 2.0) { a *= 0.5; ++e; }
    while (a < 1.0) { a *= 2.0; --e; }
    int r = (int)(a * 128.0 + 0.5);
    if (r == 256) { r = 128; ++e; }
    return s | (uint32_t)((e + 127) << 7) | (uint32_t)(r - 128);
}
__host__ __device__ constexpr int conv_k1(int r) { return (r & 8) ? 63 - (((r >> 4) << 3) | (r & 7)) : (((r >> 4) << 3) | (r & 7)); }
struct ConvTab { uint32_t w[96 * 32]; };
constexpr ConvTab make_conv_tab() {
    ConvTab t{};
    uint32_t cs[256] = {};
    for (int i = 0; i < 256; ++i) cs[i] = c_bf16(c_cos256(i));
    for (int n = 0; n < 96; ++n)
        for (int c = 0; c < 64; ++c) {
            int a = 0;
            if (n < 32) {
                const int ro = (n >> 3) & 1, ri = n & 7, co = (c >> 3) & 1, ci = c & 7;
                a = n < 16 ? 8 * ci * (4 * ri + (c >> 4)) : 8 * ri * (4 * ci + (c >> 4));
                a += (ro == co) ? 0 : (ro == 0) ? 192 : 64;
            } else {
                const int r = n - 32, n1 = 2 * (c & 31) + (c >> 5);
                a = n1 * (2 * (((r >> 4) << 3) | (r & 7)) + 1) + ((r & 8) ? 64 : 0);
            }
            const int off = n * 128 + (((c >> 3) ^ (n & 7)) << 4) + (c & 7) * 2;
            t.w[off >> 2] |= cs[a & 255] << ((off & 2) * 8);
        }
    return t;
}
__device__ __align__(128) constexpr ConvTab g_conv_tab = make_conv_tab();

struct Twiddle { uint32_t r[8], i[8], n[8]; };
constexpr double c_cospi(double x) {
    double sgn = 1.0;
    if (x > 0.5) { x = 1.0 - x; sgn = -1.0; }
    const double y = c_pi * x, y2 = y * y;
    double term = 1.0, sum = 1.0;
    for (int k = 1; k < 12; ++k) { term *= -y2 / ((2 * k - 1) * (2 * k)); sum += term; }
    return sgn * sum;
}
struct TwTab { uint32_t w[3072]; };
constexpr TwTab make_tw_tab() {
    TwTab t{};
    for (int th = 0; th < 128; ++th)
        for (int q = 0; q < 8; ++q)
            for (int e = 0; e < 2; ++e) {
                const int k1 = conv_k1(16 * (th >> 5) + 8 * (q & 1) + ((th & 31) >> 2)), n2 = 8 * (q >> 1) + 2 * (th & 3) + e;
                const double x = (double)(n2 * (2 * k1 + 1)) / 4096.0;
                const double cs = c_cospi(x), sn = n2 == 0 ? 0.0 : c_cospi(x > 0.5 ? x - 0.5 : 0.5 - x);
                t.w[((q >> 2) * 128 + th) * 4 + (q & 3)] |= c_bf16(cs * 0.0625) << (16 * e);
                t.w[((2 + (q >> 2)) * 128 + th) * 4 + (q & 3)] |= c_bf16(-sn * 0.0625) << (16 * e);
                t.w[((4 + (q >> 2)) * 128 + th) * 4 + (q & 3)] |= c_bf16(sn * 0.0625) << (16 * e);
            }
    return t;
}
__device__ __align__(128) constexpr TwTab g_tw_tab = make_tw_tab();
__device__ __forceinline__ void load_twiddle(Twiddle& tw, const uint4* p) {
#pragma unroll
    for (int q = 0; q < 2; ++q) {
        const uint4 a = __ldg(p + q * 128);
        const uint4 b = __ldg(p + (2 + q) * 128);
        tw.r[4 * q] = a.x; tw.r[4 * q + 1] = a.y; tw.r[4 * q + 2] = a.z; tw.r[4 * q + 3] = a.w;
        const uint4 n = __ldg(p + (4 + q) * 128);
        tw.n[4 * q] = n.x; tw.n[4 * q + 1] = n.y; tw.n[4 * q + 2] = n.z; tw.n[4 * q + 3] = n.w;
        tw.i[4 * q] = b.x; tw.i[4 * q + 1] = b.y; tw.i[4 * q + 2] = b.z; tw.i[4 * q + 3] = b.w;
    }
}

__device__ __forceinline__ int fresh_tid() { int v; asm volatile("mov.u32 %0, %tid.x;" : "=r"(v)); return v; }
__device__ __forceinline__ uint32_t hmul(uint32_t a, uint32_t b) { return as_u32(__hmul2_rn(as_bf2(a), as_bf2(b))); }
__device__ __forceinline__ uint32_t hadd(uint32_t a, uint32_t b) { return as_u32(__hadd2_rn(as_bf2(a), as_bf2(b))); }
__device__ __forceinline__ uint32_t hsub(uint32_t a, uint32_t b) { return as_u32(__hsub2_rn(as_bf2(a), as_bf2(b))); }
__device__ __forceinline__ uint32_t hfma(uint32_t a, uint32_t b, uint32_t c) { return as_u32(__hfma2(as_bf2(a), as_bf2(b), as_bf2(c))); }

__device__ __forceinline__ void conv_dft8(float (&x)[4][8], const uint32_t (&f)[4][4], uint32_t blo) {
#pragma unroll
    for (int r = 0; r < 4; ++r) wgmma_n16_rs(x[r], f[r], blo + 2 * r);
}
template <class T, int N>
__device__ __forceinline__ void fence_regs4(T (&a)[4][N]) { fence_regs(a[0]); fence_regs(a[1]); fence_regs(a[2]); fence_regs(a[3]); }
__device__ __forceinline__ void conv_s1(float (&dE)[32], float (&dO)[32], uint32_t tlo, uint32_t ulo) {
    wgmma_n64_ss<0, 1, 0, HI128, HI64>(dE, tlo + 256, ulo);
    wgmma_n64_ss<0, 1, 0, HI128, HI64>(dO, tlo + 256 + 4, ulo + 128);
    wgmma_n64_ss<0, 1, 1, HI128, HI64>(dE, tlo + 256 + 2, ulo + 64);
    wgmma_n64_ss<0, 1, 1, HI128, HI64>(dO, tlo + 256 + 6, ulo + 192);
}
template <int S>
__device__ __forceinline__ void conv_t1(const float (&dE)[32], const float (&dO)[32], const Twiddle& tw, float dsk, uint32_t (&f)[4][4]) {
    uint32_t ar[8], ai[8], fs[8], fd[8];
#pragma unroll
    for (int j = 0; j < 4; ++j) {
        const int i = 16 * S + 4 * j;
        const uint32_t e0 = pack_bf16(i == 16 ? dE[i] + dsk : dE[i], dE[i + 1]), e1 = pack_bf16(dE[i + 2], dE[i + 3]);
        const uint32_t o0 = pack_bf16(dO[i], dO[i + 1]), o1 = pack_bf16(dO[i + 2], dO[i + 3]);
        ar[2 * j] = hadd(e0, o0); ai[2 * j] = hadd(e1, o1);
        ar[2 * j + 1] = hsub(e0, o0); ai[2 * j + 1] = hsub(o1, e1);
    }
#pragma unroll
    for (int q = 0; q < 4; ++q) {
        const uint32_t pr = hfma(ar[q], tw.r[q], hmul(ai[q], tw.n[q])), pi = hfma(ar[q], tw.i[q], hmul(ai[q], tw.r[q]));
        fs[q] = hfma(ar[4 + q], tw.r[4 + q], hfma(ai[4 + q], tw.n[4 + q], pr));
        fs[4 + q] = hfma(ar[4 + q], tw.i[4 + q], hfma(ai[4 + q], tw.r[4 + q], pi));
        fd[q] = hfma(pr, 0xC000C000u, fs[q]);
        fd[4 + q] = hfma(pi, 0xC000C000u, fs[4 + q]);
    }
#pragma unroll
    for (int h = 0; h < 2; ++h) {
        f[0][h] = hadd(fs[h], fs[2 + h]); f[0][2 + h] = hadd(fs[4 + h], fs[6 + h]);
        f[2][h] = hsub(fs[h], fs[2 + h]); f[2][2 + h] = hsub(fs[4 + h], fs[6 + h]);
        f[1][h] = hadd(fd[h], fd[6 + h]); f[1][2 + h] = hsub(fd[4 + h], fd[2 + h]);
        f[3][h] = hsub(fd[h], fd[6 + h]); f[3][2 + h] = hadd(fd[4 + h], fd[2 + h]);
    }
}
__device__ __forceinline__ void conv_prod(const float (&xu)[8], const float (&xk)[8], uint32_t (&f)[4]) {
#pragma unroll
    for (int h = 0; h < 2; ++h) {
        float pr[2], pi[2];
#pragma unroll
        for (int e = 0; e < 2; ++e) {
            const float ur = xu[2 * h + e], ui = xu[4 + 2 * h + e], kr = xk[2 * h + e], ki = xk[4 + 2 * h + e];
            pr[e] = fmaf(ur, kr, -ui * ki);
            pi[e] = fmaf(-ur, ki, -ui * kr);
        }
        f[h] = pack_bf16(pr[0], pr[1]);
        f[2 + h] = pack_bf16(pi[0], pi[1]);
    }
}
template <bool SECOND, class G>
__device__ __forceinline__ void conv_channel(float (&dE)[32], float (&dO)[32], const Twiddle& tw, float dsk, uint32_t tlo, uint32_t nxt,
                                             uint32_t wre, uint32_t wim, int bar, G before_next) {
    float xu[4][8], xk[4][8];
    {
        uint32_t fu[4][4], fk[4][4];
        conv_t1<0>(dE, dO, tw, 0.f, fu);
        wgmma_fence();
        conv_dft8(xu, fu, tlo);
        wgmma_commit();
        conv_t1<1>(dE, dO, tw, dsk, fk);
        wgmma_fence();
        conv_dft8(xk, fk, tlo);
        wgmma_commit();
        before_next();
        wgmma_wait<0>();
        fence_regs4(xu); fence_regs4(xk);
        fence_regs4(fu); fence_regs4(fk);
    }
    uint32_t fp[4][4];
#pragma unroll
    for (int r = 0; r < 4; ++r) conv_prod(xu[r], xk[r], fp[r]);
    wgmma_fence();
    conv_dft8(xu, fp, tlo + 128);
    wgmma_commit();
    if (!SECOND || nxt) {
        if (SECOND) wgmma_fence();
        conv_s1(dE, dO, tlo, nxt);
        wgmma_commit();
        wgmma_wait<1>();
    } else {
        wgmma_wait<0>();
#pragma unroll
        for (int i = 0; i < 32; ++i) { dE[i] = 0.f; dO[i] = 0.f; }
        fence_regs(dE); fence_regs(dO);
    }
    fence_regs4(xu);
    fence_regs4(fp);
    uint32_t zr[8], zi[8], wr[8], wi[8];
#pragma unroll
    for (int h = 0; h < 2; ++h) {
        uint32_t yr[4], yi[4];
#pragma unroll
        for (int r = 0; r < 4; ++r) { yr[r] = pack_bf16(xu[r][2 * h], xu[r][2 * h + 1]); yi[r] = pack_bf16(xu[r][4 + 2 * h], xu[r][5 + 2 * h]); }
        const uint32_t u0r = hadd(yr[0], yr[2]), u0i = hadd(yi[0], yi[2]), u1r = hsub(yr[0], yr[2]), u1i = hsub(yi[0], yi[2]);
        const uint32_t v0r = hadd(yr[1], yr[3]), v0i = hadd(yi[1], yi[3]), v1r = hsub(yr[1], yr[3]), v1i = hsub(yi[1], yi[3]);
        zr[h] = hadd(u0r, v0r); zi[h] = hadd(u0i, v0i); zr[4 + h] = hsub(u0r, v0r); zi[4 + h] = hsub(u0i, v0i);
        zr[2 + h] = hadd(u1r, v1i); zi[2 + h] = hsub(u1i, v1r); zr[6 + h] = hsub(u1r, v1i); zi[6 + h] = hadd(u1i, v1r);
    }
#pragma unroll
    for (int q = 0; q < 8; ++q) {
        wr[q] = hfma(zr[q], tw.r[q], hmul(zi[q], tw.n[q]));
        wi[q] = hfma(zr[q], tw.i[q], hmul(zi[q], tw.r[q]));
    }
    if (SECOND) named_bar(bar, 128);
    stsm_x4(wre, hadd(wr[0], wr[1]), hadd(wr[2], wr[3]), hadd(wr[4], wr[5]), hadd(wr[6], wr[7]));
    stsm_x4(wre + 512, hsub(wi[1], wi[0]), hsub(wi[3], wi[2]), hsub(wi[5], wi[4]), hsub(wi[7], wi[6]));
    stsm_x4(wim, hsub(wr[1], wr[0]), hsub(wr[3], wr[2]), hsub(wr[5], wr[4]), hsub(wr[7], wr[6]));
    stsm_x4(wim + 512, hadd(wi[0], wi[1]), hadd(wi[2], wi[3]), hadd(wi[4], wi[5]), hadd(wi[6], wi[7]));
}
template <class G>
__device__ __forceinline__ void conv_pair(float (&dE)[32], float (&dO)[32], const Twiddle& tw, uint32_t dd, uint32_t tlo, uint32_t u0, uint32_t un,
                                          uint32_t lo, int BAR, G before_next) {
    conv_channel<false>(dE, dO, tw, bf_lo(dd), tlo, desc_lo(u0 + 4096, 8192), u0 + lo, u0 + 8192 + lo, BAR, []() {});
    wgmma_wait<0>();
    fence_regs(dE); fence_regs(dO);
    conv_channel<true>(dE, dO, tw, bf_hi(dd), tlo, un == u0 ? 0 : desc_lo(un, 8192), u0 + 4096 + lo, u0 + 12288 + lo, BAR, before_next);
    fence_async_smem();
    named_bar(BAR, 128);
    float ye[16], yo[16];
    wgmma_fence();
    const uint32_t wlo = desc_lo(u0, 4096);
    wgmma_n32_tt<0, 1>(ye, wlo, tlo + 256);
    wgmma_n32_tt<0, -1>(yo, wlo + 512, tlo + 256 + 4);
#pragma unroll
    for (int k = 1; k < 4; ++k) {
        wgmma_n32_tt<1, 1>(ye, wlo + 64 * k, tlo + 256 + 128 * k);
        wgmma_n32_tt<1, -1>(yo, wlo + 512 + 64 * k, tlo + 256 + 4 + 128 * k);
    }
    wgmma_commit();
    wgmma_wait<0>();
    fence_regs(ye); fence_regs(yo);
    fence_regs(dE); fence_regs(dO);
    named_bar(BAR, 128);
    const int t = fresh_tid();
    const uint32_t ya = u0 + (t & 64) * 64 + (t & 31) * 64 + (((((t >> 4) & 2) ^ (t >> 1)) & 3) << 4);
#pragma unroll
    for (int h = 0; h < 2; ++h) {
        stsm_x4_t(ya ^ (16 * h), pack_bf16(ye[2 * h], ye[2 * h + 1]), pack_bf16(ye[4 + 2 * h], ye[5 + 2 * h]),
                  pack_bf16(ye[8 + 2 * h], ye[9 + 2 * h]), pack_bf16(ye[12 + 2 * h], ye[13 + 2 * h]));
        stsm_x4_t((ya ^ (16 * h)) + 2048, pack_bf16(yo[2 * h], yo[2 * h + 1]), pack_bf16(yo[4 + 2 * h], yo[5 + 2 * h]),
                  pack_bf16(yo[8 + 2 * h], yo[9 + 2 * h]), pack_bf16(yo[12 + 2 * h], yo[13 + 2 * h]));
    }
    fence_async_smem();
    __syncwarp();
}
}

namespace {

constexpr int S_LEN = 2048;
constexpr int D_DIM = 1024;

#define REG_P 24
#define REG_AB 168
#define REG_C 152
#define BWAIT 0
#define SLOT5 27
#define SKEW1 4
#define SKEW2 6
#define QD 4
#define QKB 18
#define QD2 6
#define SLOT4 16
#define EPF 2
#define PFD 7
#define TK_PF0 0
#define TK_KV0 2
#define TK_KV1 4
#define TK_C 8
#define GAP_PF 300
#define GAP_KV 50
#define GAP_ST 50
#define GAP_CV 100
#define GAP_HB 100
#define GAP_Y 100
#define GAP_X 150
#define ALTMAP 0

__device__ __align__(1024) __nv_bfloat16 g_H[2 * D_DIM * S_LEN];
__device__ __align__(1024) __nv_bfloat16 g_y2[D_DIM * S_LEN];
__device__ __align__(1024) __nv_bfloat16 g_kvT[D_DIM * S_LEN];
__device__ __align__(128) float g_gate[S_LEN];
__device__ __align__(128) unsigned long long g_agg[8 * D_DIM];
__device__ __align__(128) unsigned int g_cnt[56 * 32];

#define STAMP(k, s) do { } while (0)
#define SAMPLE(i) do { } while (0)

__device__ __forceinline__ void tma_store_5d(const CUtensorMap* map, uint32_t src, int c0, int c1, int c2, int c3, int c4) {
    asm volatile("cp.async.bulk.tensor.5d.global.shared::cta.bulk_group [%0, {%2, %3, %4, %5, %6}], [%1];"
                 ::"l"((uint64_t)map), "r"(src), "r"(c0), "r"(c1), "r"(c2), "r"(c3), "r"(c4) : "memory");
}
#define ELECT "{\n.reg .pred p;\nelect.sync _|p, 0xffffffff;\n@p "
__device__ __forceinline__ void e_expect_tx(uint32_t bar, uint32_t bytes) {
    asm volatile(ELECT "mbarrier.arrive.expect_tx.shared::cta.b64 _, [%0], %1;\n}" ::"r"(bar), "r"(bytes) : "memory");
}
__device__ __forceinline__ void e_arrive(uint32_t bar) {
    asm volatile(ELECT "mbarrier.arrive.shared::cta.b64 _, [%0];\n}" ::"r"(bar) : "memory");
}
__device__ __forceinline__ void e_load_4d(uint32_t dst, const CUtensorMap* map, uint32_t bar, int c0, int c1, int c2, int c3) {
    asm volatile(ELECT "cp.async.bulk.tensor.4d.shared::cluster.global.mbarrier::complete_tx::bytes [%0], [%1, {%3, %4, %5, %6}], [%2];\n}"
        ::"r"(dst), "l"((uint64_t)map), "r"(bar), "r"(c0), "r"(c1), "r"(c2), "r"(c3) : "memory");
}
__device__ __forceinline__ void e_load_5d(uint32_t dst, const CUtensorMap* map, uint32_t bar, int c0, int c1, int c2, int c3, int c4) {
    asm volatile(ELECT "cp.async.bulk.tensor.5d.shared::cluster.global.mbarrier::complete_tx::bytes [%0], [%1, {%3, %4, %5, %6, %7}], [%2];\n}"
        ::"r"(dst), "l"((uint64_t)map), "r"(bar), "r"(c0), "r"(c1), "r"(c2), "r"(c3), "r"(c4) : "memory");
}
__device__ __forceinline__ void e_bulk_load(uint32_t dst, const void* src, uint32_t bytes, uint32_t bar) {
    asm volatile(ELECT "cp.async.bulk.shared::cluster.global.mbarrier::complete_tx::bytes [%0], [%1], %2, [%3];\n}"
                 ::"r"(dst), "l"(src), "r"(bytes), "r"(bar) : "memory");
}
__device__ __forceinline__ void l2_prefetch(const void* p, uint32_t bytes) {
    asm volatile("cp.async.bulk.prefetch.L2.global [%0], %1;" ::"l"(p), "r"(bytes) : "memory");
}
__device__ __forceinline__ void l2_prefetch_4d(const CUtensorMap* map, int c0, int c1, int c2, int c3) {
    asm volatile("cp.async.bulk.prefetch.tensor.4d.L2.global [%0, {%1, %2, %3, %4}];" ::"l"((uint64_t)map), "r"(c0), "r"(c1), "r"(c2), "r"(c3) : "memory");
}
__device__ __forceinline__ void l2_prefetch_5d(const CUtensorMap* map, int c0, int c1, int c2, int c3, int c4) {
    asm volatile("cp.async.bulk.prefetch.tensor.5d.L2.global [%0, {%1, %2, %3, %4, %5}];" ::"l"((uint64_t)map), "r"(c0), "r"(c1), "r"(c2), "r"(c3), "r"(c4) : "memory");
}
__device__ __forceinline__ unsigned int ld_relaxed(const unsigned int* p) {
    unsigned int v;
    asm volatile("ld.relaxed.gpu.global.u32 %0, [%1];" : "=r"(v) : "l"(p) : "memory");
    return v;
}
__device__ __forceinline__ void fence_async_global() { asm volatile("fence.proxy.async.global;" ::: "memory"); }
__device__ __forceinline__ void wait_counter(const unsigned int* p, unsigned int target) {
    unsigned int v;
    int it = 0;
    do { asm volatile("ld.acquire.gpu.global.u32 %0, [%1];" : "=r"(v) : "l"(p) : "memory"); } while (v != target && ++it < (1 << 22));
    fence_async_global();
}
__device__ __forceinline__ void red_release(unsigned int* p, unsigned int n) {
    asm volatile("red.release.gpu.global.add.u32 [%0], %1;" ::"l"(p), "r"(n) : "memory");
}
__device__ __forceinline__ uint4 ldg128(const void* p) {
    uint4 v;
    asm volatile("ld.global.nc.v4.u32 {%0,%1,%2,%3}, [%4];" : "=r"(v.x), "=r"(v.y), "=r"(v.z), "=r"(v.w) : "l"(p));
    return v;
}
__device__ __forceinline__ void stg128(void* p, uint32_t a, uint32_t b, uint32_t c, uint32_t d) {
    asm volatile("st.global.v4.b32 [%0], {%1, %2, %3, %4};" ::"l"(p), "r"(a), "r"(b), "r"(c), "r"(d) : "memory");
}

template <int TA>
__device__ __forceinline__ void wgmma_n128(float (&d)[64], uint32_t alo, uint32_t blo, int acc) {
    asm volatile(
        "{\n.reg .pred p;\n.reg .b64 da, db;\nsetp.ne.b32 p, %67, 0;\nmov.b64 da, {%64, %69};\nmov.b64 db, {%65, %66};\n"
        "wgmma.mma_async.sync.aligned.m64n128k16.f32.bf16.bf16 "
        "{%0, %1, %2, %3, %4, %5, %6, %7, %8, %9, %10, %11, %12, %13, %14, %15, "
        "%16, %17, %18, %19, %20, %21, %22, %23, %24, %25, %26, %27, %28, %29, %30, %31, "
        "%32, %33, %34, %35, %36, %37, %38, %39, %40, %41, %42, %43, %44, %45, %46, %47, "
        "%48, %49, %50, %51, %52, %53, %54, %55, %56, %57, %58, %59, %60, %61, %62, %63}, "
        "da, db, p, 1, 1, %68, 0;\n"
        "}\n"
        : R8(d, 0), R8(d, 8), R8(d, 16), R8(d, 24), R8(d, 32), R8(d, 40), R8(d, 48), R8(d, 56)
        : "r"(alo), "r"(blo), "n"(HI128), "r"(acc), "n"(TA), "n"(TA ? HI64 : HI128));
}

constexpr int NST = 6;
constexpr int XTRA = SKEW1 - 4;
static_assert(SKEW1 >= 4 && SKEW1 <= 12, "skew");
constexpr int OFF_BB = 4 * 32768;
constexpr int OFF_CT = 5 * 32768;
constexpr int OFF_CU = OFF_CT + 32768;
__host__ __device__ constexpr uint32_t conv_buf(int p) { return OFF_CT + 16384 + (p == 3 ? 0 : p) * 16384; }
constexpr int OFF_PAR = OFF_CU + 32768;
constexpr int OFF_BAR = OFF_PAR + 2048;
constexpr int SMEM_BYTES = OFF_BAR + 896;
static_assert(SMEM_BYTES <= 232448, "smem layout");

struct Ring { unsigned long long w[2]; };
constexpr Ring make_ring() {
    Ring r{};
    int st = 0, uses[NST] = {};
    for (int kb = 0; kb < 32; ++kb) {
        r.w[kb >> 4] |= (unsigned long long)(st | (uses[st]++ & 1) << 3) << (4 * (kb & 15));
        if (++st >= (kb + 1 < SLOT4 ? 4 : kb + 1 < SLOT5 ? 5 : 6)) st = 0;
    }
    return r;
}
constexpr unsigned long long RING0 = make_ring().w[0], RING1 = make_ring().w[1];
__host__ __device__ constexpr uint32_t ring_code(int kb) { return (uint32_t)((kb < 16 ? RING0 : RING1) >> (4 * (kb & 15))) & 15u; }
__host__ __device__ constexpr int ring_slot(int kb) { return ring_code(kb) & 7; }
__host__ __device__ constexpr uint32_t ring_par(int kb) { return ring_code(kb) >> 3; }
constexpr int OFF_O1 = SLOT5 < 32 ? ring_slot(SKEW2 == 6 ? 26 : 31 - SKEW2) * 32768 : OFF_CT;

struct Maps {
    CUtensorMap x5, b4, cre, cim, sk, yt, yt3, out, kvst, bre, bim;
};

__device__ __forceinline__ void cmul(float& r, float& i, float ar, float ai, float br, float bi) {
    const float a = ar * br - ai * bi, b = ar * bi + ai * br;
    r = a; i = b;
}
__device__ __forceinline__ void csqr(float& r, float& i) { const float a = r * r - i * i, b = 2.f * r * i; r = a; i = b; }
__device__ __forceinline__ float after(float v, float dep) { return __float_as_uint(dep) == 0x7fedcba9u ? dep : v; }

template <int BMODE>
__global__ void __launch_bounds__(512, 1)
fused_kernel(const __nv_bfloat16* __restrict__ x, const __nv_bfloat16* __restrict__ b_re, const __nv_bfloat16* __restrict__ b_im,
             const __nv_bfloat16* __restrict__ kin, const __nv_bfloat16* __restrict__ vin, const __nv_bfloat16* __restrict__ ssm_k,
             const __nv_bfloat16* __restrict__ shift_k, const __nv_bfloat16* __restrict__ ssm_D,
             const __nv_bfloat16* __restrict__ lam_re, const __nv_bfloat16* __restrict__ lam_im,
             const __nv_bfloat16* __restrict__ log_dt, const __nv_bfloat16* __restrict__ gate_w,
             const __nv_bfloat16* __restrict__ dskip,
             const __nv_bfloat16* __restrict__ c_re, const __nv_bfloat16* __restrict__ c_im,
             const __grid_constant__ Maps maps) {
    constexpr bool MERGED = BMODE != 0, SW = BMODE == 2;
    extern __shared__ __align__(1024) unsigned char smem_raw[];
    const uint32_t sbase = smem_u32(smem_raw);
    const uint32_t bar_full = sbase + OFF_BAR;
    const uint32_t bar_empty = bar_full + 32;
    const uint32_t bar_full2 = bar_empty + 32;
    const uint32_t bar_empty2 = bar_full2 + 48;
    const uint32_t bar_k = bar_empty2 + 48;
    const uint32_t bar_tab = bar_k + 32;
    const uint32_t bar_ab = bar_tab + 8;
    const uint32_t bar_adone = bar_ab + 8;
    const uint32_t bar_par = bar_adone + 8;
    const uint32_t bar_y = bar_par + 8;
    const uint32_t bar_rel = bar_y + 8;
    const uint32_t bar_kvrel = bar_rel + 8;
    const uint32_t bar_yrel = bar_kvrel + 8;
    const uint32_t bar_y1 = bar_yrel + 8;
    const uint32_t bar_fh = bar_y1 + 8;
    const uint32_t bar_o1 = bar_fh + 8;
    const uint32_t bar_tick = bar_o1 + 8;
    const uint32_t bar_stg = bar_tick + 104;
    const uint32_t bar_bias = bar_stg + 112;
    const uint32_t bar_hw = bar_bias + 16;
    const uint32_t bar_gate = bar_hw + 8;
    const uint32_t bar_g2 = bar_gate + 8;
    const uint32_t bar_ascan = bar_g2 + 8;
    const uint32_t w_bid = bar_full + 600, w_dsk = bar_full + 608, w_ones = bar_full + 640;
    const int tid = threadIdx.x ^ (((threadIdx.x + 128) & 256) ? 0 : 384);
    if (tid == 384) { prefetch_map(&maps.x5); prefetch_map(&maps.b4); }
    if (EPF && (threadIdx.x >> 5) - 1u < EPF && blockIdx.x < 128) {
        const int ln = threadIdx.x & 31;
        const __nv_bfloat16* p = ln < 16 ? x + (size_t)(blockIdx.x * 16 + ln) * D_DIM : ((ln & 8) ? b_im : b_re) + (size_t)(blockIdx.x * 8 + (ln & 7)) * D_DIM;
        asm volatile("prefetch.global.L2 [%0];" ::"l"(p + ((threadIdx.x >> 5) - 1) * 64) : "memory");
    }
    int bid;
    {
        unsigned int sm, nsm;
        asm volatile("mov.u32 %0, %smid;" : "=r"(sm));
        asm volatile("mov.u32 %0, %nsmid;" : "=r"(nsm));
        const int tpc = sm >> 1, q7 = ((tpc - 32) * 37) >> 8;
        const int gp = tpc < 32 ? tpc & 7 : tpc < 60 ? tpc - 31 - 7 * q7 : 0;
        const int ix = tpc < 32 ? tpc >> 3 : tpc < 60 ? q7 + 4 : ALTMAP ? (tpc - 56) ^ 2 : tpc - 58;
        bid = (ALTMAP ? tpc >= 64 : (tpc | 1) == 61) ? 128 : (4 * (gp >> 1) + (ix >> 1)) * 8 + 4 * (gp & 1) + 2 * (ix & 1) + (sm & 1);
        if (gridDim.x != 132 || nsm != 132) bid = blockIdx.x;
    }
    const int tt = bid >> 3, dt = bid & 7;
    const int ti = tt >> 1;
    const int cg = (dt >> 2) * 8 + (tt & 1) * 4 + (dt & 3);
    if (MERGED && threadIdx.x == 0 && bid < 128) {
        mbar_init(bar_full, 1);
        asm volatile("fence.mbarrier_init.release.cluster;" ::: "memory");
        mbar_expect_tx(bar_full, 49152);
        tma_load_4d(sbase + OFF_CU, &maps.b4, bar_full, 0, 0, 0, cg * 4);
        tma_load_5d(sbase + ((0 - XTRA) & 3) * 32768, &maps.x5, bar_full, 0, 0, 0, 0, ti);
        tma_load_4d(sbase + OFF_BB, &maps.b4, bar_full, 0, 0, 0, 64 + cg * 4);
    }
    __syncwarp();
    const int warp = __shfl_sync(0xffffffffu, tid >> 5, 0), wg = warp >> 2, lane = tid & 31;
    if (warp == 12 && bid < 128) {
        if (lane == 0) {
#pragma unroll
            for (int s = MERGED; s < 4; ++s) mbar_init(bar_full + 8 * s, 1);
            asm volatile("fence.mbarrier_init.release.cluster;" ::: "memory");
        }
        __syncwarp();
        asm volatile("bar.arrive 4, 512;" ::: "memory");
        if (MERGED) {
#pragma unroll 1
            for (int it = 1; it < 4; ++it) {
                e_expect_tx(bar_full + 8 * it, 49152);
                e_load_4d(sbase + OFF_CU + it * 8192, &maps.b4, bar_full + 8 * it, it * 64, 0, 0, cg * 4);
                e_load_5d(sbase + ((it - XTRA) & 3) * 32768, &maps.x5, bar_full + 8 * it, it * 64, 0, 0, 0, ti);
                e_load_4d(sbase + OFF_BB + it * 8192, &maps.b4, bar_full + 8 * it, it * 64, 0, 0, 64 + cg * 4);
            }
        }
    }
    if (bid >= 128) {
        if (tid == 0) {
            __nanosleep(2000);
            const unsigned int target = (ld_relaxed(&g_cnt[32 * 32]) & ~63u) + 64u;
            for (int i = 0; i < 8; ++i)
                for (int it = 0; ld_relaxed(&g_cnt[(40 + i) * 32]) != target && it < (1 << 12); ++it) __nanosleep(500);
        }
        return;
    }
    if (wg == 0) {
        asm volatile("setmaxnreg.dec.sync.aligned.u32 %0;" ::"n"(REG_P));
        if (tid == 32) {
            if (sbase & 1023) __trap();
#pragma unroll
            for (int s = 0; s < 4; ++s) mbar_init(bar_empty + 8 * s, 2);
#pragma unroll
            for (int s = 0; s < NST; ++s) { mbar_init(bar_full2 + 8 * s, 1); mbar_init(bar_empty2 + 8 * s, 1); }
            mbar_init(bar_k, 1); mbar_init(bar_k + 8, 1); mbar_init(bar_k + 16, 1); mbar_init(bar_k + 24, 1);
            mbar_init(bar_tab, 1);
            mbar_init(bar_ab, 1);
            mbar_init(bar_adone, 4);
            mbar_init(bar_par, 2);
            asm volatile("fence.mbarrier_init.release.cluster;" ::: "memory");
        } else if (tid == 64) {
#pragma unroll
            for (int s = 0; s < 20; ++s) mbar_init(bar_y + 8 * s, 1);
        } else if (tid == 96) {
#pragma unroll
            for (int s = 0; s < 11; ++s) mbar_init(bar_stg + 8 * s, 4);
        } else if (tid == 0) {
#pragma unroll
            for (int s = 11; s < 20; ++s) mbar_init(bar_stg + 8 * s, 4);
            asm volatile("st.shared.b32 [%0], %1;" ::"r"(w_bid), "r"(bid) : "memory");
        }
        __syncwarp();
        asm volatile("bar.sync 4, 512;" ::: "memory");
        if (warp == 0) {
#pragma unroll 1
            for (int it = MERGED ? 4 : 0; it < 16 + XTRA; ++it) {
                const int st = it & 3, kb = it < 16 ? it : it - SKEW1;
                const bool fa = it < 16, fb = it < 16 - SKEW1 || it >= 12;
                const uint32_t bf = bar_full + 8 * st;
                mbar_wait(bar_empty + 8 * st, ((it >> 2) & 1) ^ 1);
                e_expect_tx(bf, fa && fb ? 49152 : 40960);
                e_load_5d(sbase + ((it - XTRA) & 3) * 32768, &maps.x5, bf, kb * 64, 0, 0, 0, ti);
                if (MERGED) {
                    if (fa) e_load_4d(sbase + OFF_CU + st * 8192, &maps.b4, bf, kb * 64, 0, 0, cg * 4);
                    if (fb) e_load_4d(sbase + OFF_BB + st * 8192, &maps.b4, bf, kb * 64, 0, 0, 64 + cg * 4);
                } else {
                    if (lane < 16 && ((lane & 8) ? fb : fa))
                        tma_load_2d(sbase + ((lane & 8) ? OFF_BB : OFF_CU) + st * 8192 + (lane & 7) * 1024, (lane & 1) ? &maps.bim : &maps.bre, bf,
                                    kb * 64, (lane >> 3) * 512 + cg * 32 + ((lane & 7) >> 1) * 8);
                    __syncwarp();
                }
                if (it >= 4 && it < 16) e_arrive(bar_tick + 8 * (it - 3));
                if (lane == 0) STAMP(1, 16 + it);
                if (lane == 0 && it < 16) SAMPLE(it - 3);
            }
#pragma unroll 1
            for (int kb = 0; kb < 32; ++kb) {
                const int st = ring_slot(kb);
                const uint32_t bf = bar_full2 + 8 * st;
                mbar_wait(bar_empty2 + 8 * st, ring_par(kb));
                e_expect_tx(bf, 32768);
                e_load_5d(sbase + st * 32768 + 16384, &maps.cre + ((kb >> 3) & 1), bf, ((kb >> 4) * 8 + (kb & 7)) * 64, 0, 0, 0, dt * 4);
                if (lane == 0) STAMP(2, 16 + kb);
                if (lane == 0 && (kb & 3) == 0) SAMPLE(13 + (kb >> 2));
            }
        } else if (warp == 1) {
            if (MERGED && PFD && lane == 0) {
#pragma unroll 1
                for (int n = 0; n + PFD < 16; ++n) {
                    mbar_wait(bar_tick + 8 * n, 0);
                    if (cg >= 4 && max(cg - PFD, 0) == n) l2_prefetch_5d(&maps.x5, cg * 64, 0, 0, 0, ti);
                    if (ti >= 2 && max(2 * ti - PFD, 0) == n) {
#pragma unroll 1
                        for (int i = 0; i < 4; ++i) l2_prefetch_4d(&maps.b4, (2 * ti + (i >> 1)) * 64, 0, 0, (i & 1) * 64 + cg * 4);
                    }
                }
            }
            __syncwarp();
            const char* hp = reinterpret_cast<const char*>(g_H) + (size_t)tt * 262144;
            mbar_wait(bar_adone, 0);
            e_expect_tx(bar_k + 8, 16384);
            e_expect_tx(bar_k + 16, 16384);
#pragma unroll 1
            for (int c = 2; c < 6; ++c) {
                e_load_4d(sbase + conv_buf(0) + (c >> 1) * 16384 + (c & 1) * 4096 + 8192, &maps.sk, bar_k + 8 * (c >> 1), 0, 0, 0, bid * 8 + c);
                if (GAP_CV) __nanosleep(GAP_CV);
            }
            mbar_wait(bar_kvrel, 0);
            const unsigned int target = lds32(w_bid + 4);
            mbar_wait(bar_rel, 0);
#pragma unroll 1
            for (int q = 0; q < 2; ++q) {
                if (lane == 0) STAMP(0, 8 + 4 * q);
                if (q == 0) wait_counter(&g_cnt[(2 * ti) * 32], target);
                else { mbar_wait(bar_fh, 0); fence_async_global(); }
                if (lane == 0) STAMP(0, 9 + 4 * q);
#pragma unroll 1
                for (int kb = 0; kb < 16; ++kb) {
                    const int st = ring_slot(16 * q + kb);
                    mbar_wait(bar_empty2 + 8 * st, ring_par(16 * q + kb));
                    e_bulk_load(sbase + st * 32768, hp + kb * 16384, 16384, bar_full2 + 8 * st);
                }
                hp += 4194304;
            }
        } else if (warp == 2) {
            if (lane == 0) {
                mbar_wait(bar_tick + 8, 0);
                const unsigned int target = (ld_relaxed(&g_cnt[(40 + dt) * 32]) & ~63u) + 64u;
                asm volatile("st.shared.b32 [%0], %1;" ::"r"(w_bid + 4), "r"(target) : "memory");
                prefetch_map(&maps.kvst); prefetch_map(&maps.sk);
#pragma unroll 1
                for (int bt = 0; bt < 2; ++bt) {
                    mbar_wait(bar_stg + 8 * bt, 0);
#pragma unroll 1
                    for (int i = 0; i < 4; ++i) {
                        if (i) __nanosleep(GAP_ST);
                        tma_store_3d(&maps.kvst, sbase + OFF_CT + bt * 16384 + i * 4096, (tt & 1) * 1024 + ti * 128 + 64 * bt, dt * 16, 2 * i);
                    }
                    bulk_commit();
                }
                bulk_wait0();
                fence_async_global();
                red_release(&g_cnt[(40 + dt) * 32], 4);
                mbar_arrive(bar_kvrel);
                STAMP(0, 23);
                mbar_expect_tx(bar_tab, 12288);
                bulk_load(sbase + OFF_CT, &g_conv_tab, 12288, bar_tab);
                mbar_expect_tx(bar_k, 16384);
                tma_load_4d(sbase + conv_buf(0) + 8192, &maps.sk, bar_k, 0, 0, 0, bid * 8);
                tma_load_4d(sbase + conv_buf(0) + 12288, &maps.sk, bar_k, 0, 0, 0, bid * 8 + 1);
                wait_counter(&g_cnt[(40 + (bid >> 4)) * 32], target);
                STAMP(0, 19);
#pragma unroll 1
                for (int p = 0; p < 3; ++p) {
                    if (p == 1) mbar_wait(bar_adone, 0);
                    bulk_load(sbase + conv_buf(p), g_kvT + (size_t)(bid * 8 + 2 * p) * 2048, 8192, bar_k + 8 * p);
                    if (GAP_CV) __nanosleep(GAP_CV);
                }
                prefetch_map(&maps.out); prefetch_map(&maps.yt); prefetch_map(&maps.yt3);
#pragma unroll 1
                for (int p = 0; p < 4; ++p) {
                    mbar_wait(bar_stg + 16 + 8 * p, 0);
                    if (p == 0) {
                        mbar_expect_tx(bar_k + 24, 16384);
                        tma_load_4d(sbase + conv_buf(3) + 8192, &maps.sk, bar_k + 24, 0, 0, 0, bid * 8 + 6);
                        mbar_wait(bar_g2, 0);
                        tma_load_4d(sbase + conv_buf(3) + 12288, &maps.sk, bar_k + 24, 0, 0, 0, bid * 8 + 7);
                    }
#pragma unroll 1
                    for (int i = 0; i < 2; ++i) {
                        if (i) __nanosleep(GAP_Y);
                        asm volatile("cp.async.bulk.global.shared::cta.bulk_group [%0], [%1], 4096;"
                                     ::"l"(g_y2 + (size_t)(bid * 8 + 2 * p + i) * 2048), "r"(sbase + conv_buf(p) + i * 4096) : "memory");
                    }
                    bulk_commit();
                    STAMP(0, 24 + p);
                    if (p == 0) {
                        bulk_wait_read0();
                        bulk_load(sbase + conv_buf(3), g_kvT + (size_t)(bid * 8 + 6) * 2048, 8192, bar_k + 24);
                    }
                    if (p == 2) {
                        bulk_wait0();
                        fence_async_global();
                        red_release(&g_cnt[(48 + (bid >> 4)) * 32], 4);
                        mbar_arrive(bar_yrel);
                        STAMP(0, 3);
                    }
                }
                bulk_wait0();
                mbar_arrive(bar_empty2 + 40);
                fence_async_global();
                red_release(&g_cnt[(32 + (bid >> 4)) * 32], 4);
                STAMP(0, 2);
                wait_counter(&g_cnt[(32 + dt) * 32], target);
                STAMP(0, 5);
                mbar_expect_tx(bar_y, 8192);
#pragma unroll 1
                for (int i = 6; i < 8; ++i)
                    tma_load_5d(sbase + OFF_CU + i * 4096, &maps.yt, bar_y, (tt & 1) * 1024 + ti * 128 + (i & 1) * 64, 0, 0, i >> 1, dt * 4);
#pragma unroll 1
                for (int i = 0; i < 8; ++i) {
                    mbar_wait(bar_stg + 48 + 8 * i, 0);
                    tma_store_5d(&maps.out, sbase + ((i & 4) ? OFF_O1 : OFF_CU) + (i & 3) * 8192, dt * 128 + (i & 3) * 32, 0, 0, (tt & 1) * 4 + ((i & 4) >> 1), ti);
                    bulk_commit();
                }
                bulk_wait_read0();
                STAMP(2, 3);
                SAMPLE(21);
            }
        } else if (lane == 0) {
            mbar_wait(bar_tick + 8 * TK_PF0, 0);
#pragma unroll 1
            for (int i = 0; i < 8; ++i) {
                l2_prefetch(((i & 1) ? vin : kin) + (size_t)(ti * 256 + 32 * (i & 4) + (bid & 15) * 8 + 2 * (i & 2)) * D_DIM, 8192);
                __nanosleep(GAP_PF);
            }
            if (bid < 3) l2_prefetch(reinterpret_cast<const char*>(&g_conv_tab) + bid * 4096, 4096);
            prefetch_map(&maps.cre); prefetch_map(&maps.cim);
            mbar_wait(bar_tick + 8 * TK_C, 0);
#pragma unroll 1
            for (int i = 0; i < 8; ++i) {
                l2_prefetch((i & 1) ? ((i & 4) ? c_im : c_re) + (size_t)bid * 8192 + (i & 2) * 2048 : ssm_k + (size_t)bid * 16384 + (i >> 1) * 4096, 8192);
                __nanosleep(GAP_PF);
            }
            const unsigned int target = (ld_relaxed(&g_cnt[(2 * ti + 1) * 32]) & ~63u) + 64u;
            mbar_wait(bar_gate, 0);
            mbar_wait(bar_hw, 0);
            mbar_wait(bar_g2, 0);
            char* hp = reinterpret_cast<char*>(g_H) + (size_t)((16 + 2 * ti) * 16 + (cg >> 1)) * 16384 + (cg & 1) * 2048;
#pragma unroll 1
            for (int i = 0; i < 16; ++i) {
                asm volatile("cp.async.bulk.global.shared::cta.bulk_group [%0], [%1], 2048;"
                             ::"l"(hp + (i & 3) * 4096 + ((i >> 2) & 1) * 262144 + (i >> 3) * 131072), "r"(sbase + OFF_BB + i * 2048) : "memory");
                __nanosleep(GAP_HB);
            }
            bulk_commit();
            bulk_wait0();
            mbar_arrive(bar_empty2 + 32);
            fence_async_global();
            red_release(&g_cnt[(2 * ti + 1) * 32], 4);
            STAMP(0, 38);
            wait_counter(&g_cnt[(2 * ti + 1) * 32], target);
            mbar_arrive(bar_fh);
        }
    } else {
    if (wg == 3) {
        if (warp != 12) asm volatile("bar.sync 4, 512;" ::: "memory");
        named_bar(3, 128);
        asm volatile("setmaxnreg.inc.sync.aligned.u32 %0;" ::"n"(REG_C));
        const int t = tid & 127, w4 = t >> 5;
        if (t == 0) SAMPLE(0);
        mbar_wait(bar_tick, 0);
        if (t < 64) {
            const int ch = (t >> 5) * 512 + cg * 32 + (t & 31);
            unsigned long long oldagg;
            asm volatile("ld.relaxed.gpu.global.u64 %0, [%1];" : "=l"(oldagg) : "l"(&g_agg[ti * D_DIM + ch]) : "memory");
            const float Lr = __bfloat162float(lam_re[ch]), Li = __bfloat162float(lam_im[ch]);
            const float dtv = bf16r(expf(__bfloat162float(log_dt[ch])));
            const unsigned int tag = ((((unsigned int)oldagg & 1u) | ((unsigned int)(oldagg >> 31) & 2u)) + 1u) & 3u;
            const float er = expf(dtv * Lr);
            float s, c;
            sincospif(dtv * Li * 0.318309886183790672f, &s, &c);
            const float lr = er * c, li = er * s;
            const float nr = lr - 1.f, ni = li;
            const float den = Lr * Lr + Li * Li;
            const float cr = 2.f * (nr * Lr + ni * Li) / den, ci = 2.f * (ni * Lr - nr * Li) / den;
            float pr = lr, pi = -li;
#pragma unroll
            for (int i = 0; i < 5; ++i) csqr(pr, pi);
            sts128(sbase + OFF_PAR + t * 32, __float_as_uint(lr), __float_as_uint(-li), __float_as_uint(cr), __float_as_uint(ci));
            sts128(sbase + OFF_PAR + t * 32 + 16, __float_as_uint(pr), __float_as_uint(pi), tag, 0);
            __syncwarp();
            if (lane == 0) mbar_arrive(bar_par);
        }
        if (t >= 120) asm volatile("st.shared.b32 [%0], %1;" ::"r"(w_dsk - 480 + 4 * t),
                                   "r"(t < 124 ? __ldg(reinterpret_cast<const uint32_t*>(ssm_D + bid * 8) + (t & 3)) : 0u) : "memory");
        if (t < 64) asm volatile("st.shared.b32 [%0], %1;" ::"r"(w_ones + 4 * t), "r"(0x3F803F80u) : "memory");
        {
            const int cq = lane & 15, rg = (lane >> 4) + 2 * w4;
            uint32_t sk[4][4];
#pragma unroll
            for (int c = 0; c < 4; ++c) {
                const uint4 w = ldg128(shift_k + (size_t)(dt * 128 + 8 * cq + 2 * c) * 4);
                sk[0][c] = __byte_perm(w.x, w.z, 0x5410); sk[1][c] = __byte_perm(w.x, w.z, 0x7632);
                sk[2][c] = __byte_perm(w.y, w.w, 0x5410); sk[3][c] = __byte_perm(w.y, w.w, 0x7632);
            }
#pragma unroll 1
            for (int bt = 0; bt < 2; ++bt) {
                const int t0 = ti * 256 + 128 * bt + 16 * (rg & 4) + 32 * (tt & 1) + 8 * (rg & 3);
                mbar_wait(bar_tick + 8 * (bt ? TK_KV1 : TK_KV0), 0);
                if (t == 0) STAMP(0, 30 + 3 * bt);
                uint4 kk[11], vv[8];
                const __nv_bfloat16* kp = kin + (size_t)t0 * D_DIM + dt * 128 + 8 * cq;
                const __nv_bfloat16* vp = vin + (size_t)t0 * D_DIM + dt * 128 + 8 * cq;
#pragma unroll
                for (int i = 0; i < 11; ++i) {
                    if (i < 3 && t0 == 0) kk[i] = make_uint4(0, 0, 0, 0);
                    else kk[i] = ldg128(kp + (i - 3) * D_DIM);
                    if (i == 6 || i == 10) __nanosleep(GAP_KV);
                }
#pragma unroll
                for (int i = 0; i < 8; ++i) { vv[i] = ldg128(vp + i * D_DIM); if (i == 3) __nanosleep(GAP_KV); }
                const uint32_t ua = sbase + OFF_CT + bt * 16384 + cq * 128 + ((rg ^ ((2 * ti + bt) & 3) ^ (cq & 7)) << 4);
#pragma unroll
                for (int c = 0; c < 4; ++c) {
                    uint32_t res[8];
#pragma unroll
                    for (int i = 0; i < 8; ++i) {
                        uint32_t ks = hmul((&kk[i].x)[c], sk[3][c]);
                        ks = hadd(ks, hmul((&kk[i + 1].x)[c], sk[2][c]));
                        ks = hadd(ks, hmul((&kk[i + 2].x)[c], sk[1][c]));
                        ks = hadd(ks, hmul((&kk[i + 3].x)[c], sk[0][c]));
                        res[i] = hmul(ks, (&vv[i].x)[c]);
                    }
                    sts128(ua + (2 * c) * 2048, __byte_perm(res[0], res[1], 0x5410), __byte_perm(res[2], res[3], 0x5410),
                           __byte_perm(res[4], res[5], 0x5410), __byte_perm(res[6], res[7], 0x5410));
                    sts128(ua + (2 * c + 1) * 2048, __byte_perm(res[0], res[1], 0x7632), __byte_perm(res[2], res[3], 0x7632),
                           __byte_perm(res[4], res[5], 0x7632), __byte_perm(res[6], res[7], 0x7632));
                }
                fence_async_smem();
                __syncwarp();
                if (lane == 0) mbar_arrive(bar_stg + 8 * bt);
                if (t == 0) STAMP(0, 21 + bt);
            }
        }
        {
            const int row = bid * 16 + (t >> 3);
            uint4 xv[16];
#pragma unroll
            for (int n = 0; n < 16; ++n) {
                xv[n] = ldg128(x + (size_t)row * D_DIM + ((t & 7) + 8 * n) * 8);
                if ((n & 3) == 3) __nanosleep(GAP_KV);
            }
#pragma unroll
            for (int n8 = 0; n8 < 16; n8 += 8) {
                uint4 wv[8];
#pragma unroll
                for (int n = 0; n < 8; ++n) wv[n] = ldg128(gate_w + ((t & 7) + 8 * (n8 + n)) * 8);
#pragma unroll
                for (int n = 0; n < 8; ++n) {
                    uint4& p = xv[n8 + n];
                    p.x = hmul(p.x, wv[n].x); p.y = hmul(p.y, wv[n].y); p.z = hmul(p.z, wv[n].z); p.w = hmul(p.w, wv[n].w);
                }
            }
            float d[4] = {0.f, 0.f, 0.f, 0.f};
            fence_regs(d);
            named_bar(3, 128);
            wgmma_fence();
#pragma unroll
            for (int n = 0; n < 16; ++n)
                asm volatile("{\n.reg .b64 db;\nmov.b64 db, {%8, 8};\n"
                             "wgmma.mma_async.sync.aligned.m64n8k16.f32.bf16.bf16 {%0, %1, %2, %3}, {%4, %5, %6, %7}, db, 1, 1, 1, 0;\n}\n"
                             : "+f"(d[0]), "+f"(d[1]), "+f"(d[2]), "+f"(d[3]) : "r"(xv[n].x), "r"(xv[n].y), "r"(xv[n].z), "r"(xv[n].w), "r"(desc_lo(w_ones, 128)));
            wgmma_commit();
            wgmma_wait<0>();
            fence_regs(d);
#pragma unroll
            for (int n = 0; n < 16; ++n) asm volatile("" ::"r"(xv[n].x), "r"(xv[n].y), "r"(xv[n].z), "r"(xv[n].w) : "memory");
            float sum = d[0] + d[2];
            sum += __shfl_xor_sync(0xffffffffu, sum, 4);
            if ((t & 7) == 0) g_gate[row] = bf16r(1.f / (1.f + expf(-bf16r(sum))));
            if (t == 0) STAMP(0, 4);
            __syncwarp();
            if (lane == 0) mbar_arrive(bar_gate);
        }
    } else {
        asm volatile("setmaxnreg.inc.sync.aligned.u32 %0;" ::"n"(REG_AB));
        if (tid == 128) STAMP(1, 54);
        asm volatile("bar.sync 4, 512;" ::: "memory");
        if (tid == 128) STAMP(1, 55);
        const int cw = wg - 1;
        const int t = tid & 127, w4 = t >> 5, g = lane >> 2, t4 = lane & 3;
        {
            float a0[64], a1[64];
            auto release = [&](int it) {
                if (it < 12 + XTRA && t <= ((it >= 16 - SKEW1 && it < 12) || it >= 16)) mbar_arrive(bar_empty + 8 * (it & 3));
            };
#pragma unroll 1
            for (int kb = 0; kb < 16; ++kb) {
                const int it = cw == 1 && kb >= 16 - SKEW1 ? kb + XTRA : kb, st = it & 3;
                if (cw == 1 && kb == 16 - SKEW1) mbar_wait(bar_ab, 0);
                mbar_wait(bar_full + 8 * st, (it >> 2) & 1);
                if (kb == 0 && tid == 288) mbar_arrive(bar_tick);
                if (kb == 0 && t == 0) STAMP(1, 14 + cw);
                const uint32_t alo = desc_lo(sbase + (cw ? OFF_BB : OFF_CU) + st * 8192, 16), blo = desc_lo(sbase + ((it - XTRA) & 3) * 32768, 16);
                wgmma_fence();
#pragma unroll
                for (int k = 0; k < 4; ++k) {
                    wgmma_n128<0>(a0, alo + 2 * k, blo + 2 * k, k ? 1 : kb);
                    wgmma_n128<0>(a1, alo + 2 * k, blo + 1024 + 2 * k, k ? 1 : kb);
                }
                wgmma_commit();
                wgmma_wait<1>();
                if (kb > 0 && !(cw == 1 && kb == 16 - SKEW1)) release(it - 1);
                if (cw == 1 && kb == 15 - SKEW1) {
                    wgmma_wait<0>();
                    release(it);
                }
                if (cw == 1 && kb > 12) {
                    if (kb == 13) mbar_wait(bar_adone, 0);
                    if (t == 0) mbar_arrive(bar_empty2 + 8 * (kb - 13));
                }
            }
            if (tid == 192) mbar_arrive(bar_ab);
            float mr, mi, cr, ci, p32r, p32i;
            uint32_t tag;
            mbar_wait(bar_par, 0);
            {
                const uint32_t par = sbase + OFF_PAR + (cw * 32 + w4 * 8 + g) * 32;
                uint32_t dummy;
                asm volatile("ld.shared.v4.f32 {%0,%1,%2,%3}, [%4];" : "=f"(mr), "=f"(mi), "=f"(cr), "=f"(ci) : "r"(par));
                asm volatile("ld.shared.v4.b32 {%0,%1,%2,%3}, [%4];" : "=f"(p32r), "=f"(p32i), "=r"(tag), "=r"(dummy) : "r"(par + 16));
            }
            const float l1i = SW ? mi : -mi;
            auto map = [&](float p, float q, float& r, float& i) {
                if (SW) { r = fmaf(cr, q, -ci * p); i = fmaf(-cr, p, -ci * q); }
                else { r = fmaf(cr, p, -ci * q); i = fmaf(-cr, q, -ci * p); }
            };
            float p64r = p32r, p64i = p32i;
            csqr(p64r, p64i);
            float p128r = p64r, p128i = p64i;
            csqr(p128r, p128i);
            wgmma_wait<0>();
            fence_regs(a0); fence_regs(a1);
            if (cw == 0) { release(15); if (lane == 0) mbar_arrive(bar_adone); }
            else if (t == 0) mbar_arrive(bar_empty2 + 24);
            if (t == 0) STAMP(1, 2 + 6 * cw);
            if (BWAIT == 1 && cw == 1) mbar_wait(bar_ascan, 0);
            float hr = 0.f, hi = 0.f, ar = 0.f, ai = 0.f;
#pragma unroll
            for (int j = 0; j < 16; ++j)
#pragma unroll
                for (int e = 0; e < 2; ++e) {
                    const float nr = fmaf(mr, ar, fmaf(-l1i, ai, a0[4 * j + e])), ni = fmaf(mr, ai, fmaf(l1i, ar, a0[4 * j + 2 + e]));
                    const float or_ = fmaf(mr, hr, fmaf(-l1i, hi, a1[4 * j + e])), oi = fmaf(mr, hi, fmaf(l1i, hr, a1[2 + 4 * j + e]));
                    ar = nr; ai = ni; hr = or_; hi = oi;
                }
            map(ar, ai, ar, ai);
            map(hr, hi, hr, hi);
            hr += p32r * ar - p32i * ai; hi += p32r * ai + p32i * ar;
            {
                float vr = __shfl_up_sync(0xffffffffu, hr, 1, 4), vi = __shfl_up_sync(0xffffffffu, hi, 1, 4);
                if (t4 >= 1) { hr += p64r * vr - p64i * vi; hi += p64r * vi + p64i * vr; }
                vr = __shfl_up_sync(0xffffffffu, hr, 2, 4); vi = __shfl_up_sync(0xffffffffu, hi, 2, 4);
                if (t4 >= 2) { hr += p128r * vr - p128i * vi; hi += p128r * vi + p128i * vr; }
            }
            unsigned long long* ap = &g_agg[ti * D_DIM + cw * 512 + cg * 32 + w4 * 8 + g];
            if (t4 == 3) asm volatile("{\n.reg .b64 a;\nmov.b64 a, {%1, %2};\nst.relaxed.gpu.global.u64 [%0], a;\n}\n" ::"l"(ap),
                                      "r"((__float_as_uint(hr) & ~1u) | (tag & 1u)), "r"((__float_as_uint(hi) & ~1u) | (tag >> 1)) : "memory");
            float exr = __shfl_up_sync(0xffffffffu, hr, 1, 4), exi = __shfl_up_sync(0xffffffffu, hi, 1, 4);
            if (t4 == 0) { exr = 0.f; exi = 0.f; }
            if (t == 0) STAMP(1, 3 + 6 * cw);
            if (BWAIT == 2 && cw == 1) mbar_wait(bar_ascan, 0);
            ci = after(ci, exr);
#pragma unroll
            for (int j = 0; j < 16; ++j)
#pragma unroll
                for (int e = 0; e < 2; ++e) {
                    map(a0[4 * j + e], a0[4 * j + 2 + e], a0[4 * j + e], a0[4 * j + 2 + e]);
                    map(a1[4 * j + e], a1[4 * j + 2 + e], a1[4 * j + e], a1[4 * j + 2 + e]);
                }
            float qr = 1.f, qi = 0.f, ur = 1.f, ui = 0.f;
            if (t4 & 1) { qr = p64r; qi = p64i; }
            if (t4 & 2) cmul(qr, qi, qr, qi, p128r, p128i);
            csqr(p128r, p128i);
            if (t4 & 1) { ur = p128r; ui = p128i; }
            csqr(p128r, p128i);
            if (t4 & 2) cmul(ur, ui, ur, ui, p128r, p128i);
            csqr(p128r, p128i);
            fence_regs(a0); fence_regs(a1);
            if (t == 0) STAMP(1, 7 + 6 * cw);
            if (ti > 0) {
                const unsigned long long tmask = 0x0000000100000001ull, tval = ((unsigned long long)(tag >> 1) << 32) | (tag & 1u);
                unsigned long long u0 = tval, u1 = tval;
                ap -= D_DIM * (1 + t4);
                int it = 0;
                do {
                    asm volatile("{\n.reg .pred p, q;\nsetp.gt.s32 p, %3, 0;\nsetp.gt.s32 q, %3, 4;\n@p ld.relaxed.gpu.global.u64 %0, [%2];\n"
                                 "@q ld.relaxed.gpu.global.u64 %1, [%2+-32768];\n}\n" : "+l"(u0), "+l"(u1) : "l"(ap), "r"(ti - t4) : "memory");
                } while (__any_sync(0xffffffffu, (((u0 ^ tval) | (u1 ^ tval)) & tmask) != 0) && ++it < (1 << 22));
                float Pr = __uint_as_float((unsigned)u1 & ~1u), Pi = __uint_as_float((unsigned)(u1 >> 32) & ~1u);
                cmul(Pr, Pi, Pr, Pi, p128r, p128i);
                Pr += __uint_as_float((unsigned)u0 & ~1u); Pi += __uint_as_float((unsigned)(u0 >> 32) & ~1u);
                cmul(Pr, Pi, Pr, Pi, ur, ui);
                Pr += __shfl_xor_sync(0xffffffffu, Pr, 1); Pi += __shfl_xor_sync(0xffffffffu, Pi, 1);
                Pr += __shfl_xor_sync(0xffffffffu, Pr, 2); Pi += __shfl_xor_sync(0xffffffffu, Pi, 2);
                exr += qr * Pr - qi * Pi;
                exi += qr * Pi + qi * Pr;
            }
            if (t == 0) STAMP(1, 4 + 6 * cw);
            char* hp = reinterpret_cast<char*>(g_H) + (size_t)((2 * ti) * 16 + (cg >> 1)) * 16384 + ((cg & 1) * 32 + w4 * 8 + g) * 64 + ((t4 ^ (g >> 1)) << 4);
            float fxr = ar + p32r * exr - p32i * exi, fxi = ai + p32r * exi + p32i * exr;
            const uint32_t hs = sbase + OFF_BB + (w4 * 8 + g) * 64 + ((t4 ^ (g >> 1)) << 4);
            if (cw == 1) named_bar(2, 128);
#pragma unroll
            for (int jj = 0; jj < 4; ++jj) {
                uint32_t pr[4], qq[4], pi[4], qi[4];
#pragma unroll
                for (int j4 = 0; j4 < 4; ++j4) {
                    const int j = jj * 4 + j4;
                    const float r0 = fmaf(mr, exr, fmaf(-mi, exi, a0[4 * j])), i0 = fmaf(mr, exi, fmaf(mi, exr, a0[4 * j + 2]));
                    const float r1 = fmaf(mr, fxr, fmaf(-mi, fxi, a1[4 * j])), i1 = fmaf(mr, fxi, fmaf(mi, fxr, a1[2 + 4 * j]));
                    exr = fmaf(mr, r0, fmaf(-mi, i0, a0[4 * j + 1]));
                    exi = fmaf(mr, i0, fmaf(mi, r0, a0[4 * j + 3]));
                    fxr = fmaf(mr, r1, fmaf(-mi, i1, a1[1 + 4 * j]));
                    fxi = fmaf(mr, i1, fmaf(mi, r1, a1[3 + 4 * j]));
                    pr[j4] = pack_bf16(r0, exr); pi[j4] = pack_bf16(i0, exi);
                    qq[j4] = pack_bf16(r1, fxr); qi[j4] = pack_bf16(i1, fxi);
                }
                if (cw == 0) {
                    stg128(hp + jj * 4096, pr[0], pr[1], pr[2], pr[3]);
                    stg128(hp + jj * 4096 + 262144, qq[0], qq[1], qq[2], qq[3]);
                    stg128(hp + jj * 4096 + 131072, pi[0], pi[1], pi[2], pi[3]);
                    stg128(hp + jj * 4096 + 393216, qi[0], qi[1], qi[2], qi[3]);
                } else {
                    sts128(hs + jj * 2048, pr[0], pr[1], pr[2], pr[3]);
                    sts128(hs + jj * 2048 + 8192, qq[0], qq[1], qq[2], qq[3]);
                    sts128(hs + jj * 2048 + 16384, pi[0], pi[1], pi[2], pi[3]);
                    sts128(hs + jj * 2048 + 24576, qi[0], qi[1], qi[2], qi[3]);
                }
            }
            if (t == 0) STAMP(1, 5 + 6 * cw);
            if (cw == 0) {
                if (BWAIT && lane == 0) mbar_arrive(bar_ascan);
                named_bar(1, 128);
                if (t == 0) { red_release(&g_cnt[(2 * ti) * 32], 4); mbar_arrive(bar_rel); }
                if (t == 0) STAMP(1, 6);
                __syncwarp();
            } else {
                fence_async_smem();
                __syncwarp();
                if (lane == 0) mbar_arrive(bar_hw);
            }
            if (t == 0) STAMP(1, 50 + cw);
        }
        if (cw == 0) {
            float c0[64], c1[64];
            int pst = 0;
            auto kblock = [&](int kb, auto shallow) {
                const int t = fresh_tid() & 127, lane = t & 31;
                const int st = ring_slot(kb);
                mbar_wait(bar_full2 + 8 * st, ring_par(kb));
                if (kb == 0 && t == 0) STAMP(2, 6);
                if (kb == 0 && lane == 0) mbar_arrive(bar_g2);
                const uint32_t alo = desc_lo(sbase + st * 32768, 4096), blo = desc_lo(sbase + st * 32768 + 16384, 16);
                constexpr int Q = decltype(shallow)::value;
#pragma unroll
                for (int j = 0; j < 8; ++j) {
                    wgmma_fence();
                    if (j & 1) wgmma_n128<1>(c1, alo + 512 + 64 * (j >> 1), blo + 2 * (j >> 1), j >> 1 ? 1 : kb);
                    else wgmma_n128<1>(c0, alo + 64 * (j >> 1), blo + 2 * (j >> 1), j >> 1 ? 1 : kb);
                    wgmma_commit();
                    wgmma_wait<Q>();
                    if (j == Q - 1 && kb > 0 && t == 0) mbar_arrive(bar_empty2 + 8 * pst);
                }
                pst = st;
            };
#pragma unroll 1
            for (int kb = 0; kb < QKB; ++kb) kblock(kb, std::integral_constant<int, QD>());
#pragma unroll 1
            for (int kb = QKB; kb < 32 - SKEW2; ++kb) kblock(kb, std::integral_constant<int, QD2>());
            static_assert(SKEW2 <= (SLOT5 < 32 ? 6 : 4), "slot release");
            const uint32_t alo = desc_lo(sbase, 4096), blo = desc_lo(sbase + 16384, 16);
#pragma unroll
            for (int kb = 32 - SKEW2; kb < 32; ++kb) {
                mbar_wait(bar_full2 + 8 * ring_slot(kb), ring_par(kb));
                wgmma_fence();
#pragma unroll
                for (int k = 0; k < 4; ++k) wgmma_n128<1>(c0, alo + ring_slot(kb) * 2048 + 64 * k, blo + ring_slot(kb) * 2048 + 2 * k, 1);
                wgmma_commit();
                if (SLOT5 < 32 && SKEW2 < 6 && kb == 33 - SKEW2) {
                    wgmma_wait<2>();
                    if ((fresh_tid() & 127) == 0) mbar_arrive(bar_o1);
                }
                if (SKEW2 == 6 && kb == 26) {
                    wgmma_wait<1>();
                    if ((fresh_tid() & 127) == 0) mbar_arrive(bar_empty2 + 8 * ring_slot(25));
                }
            }
            auto late = [&](int kb) {
                wgmma_fence();
#pragma unroll
                for (int k = 0; k < 4; ++k) wgmma_n128<1>(c1, alo + 512 + ring_slot(kb) * 2048 + 64 * k, blo + ring_slot(kb) * 2048 + 2 * k, 1);
                wgmma_commit();
            };
            late(32 - SKEW2);
            const int t = fresh_tid() & 127, lane = t & 31, w4 = t >> 5, g = lane >> 2, t4 = lane & 3;
            auto epilogue = [&](const float (&a)[64], int b) {
                const uint32_t ad0 = sbase + (b ? OFF_O1 : OFF_CU) + (w4 * 16 + g) * 128 + (((2 * t4) ^ g) << 4);
                float gt[2];
                uint32_t bv[4][4];
#pragma unroll
                for (int h = 0; h < 2; ++h) gt[h] = __uint_as_float(lds32(sbase + OFF_PAR + (64 * b + 16 * w4 + 8 * h + g) * 4));
#pragma unroll
                for (int i = 0; i < 4; ++i)
                    asm volatile("ld.shared.v4.b32 {%0,%1,%2,%3}, [%4];" : "=r"(bv[i][0]), "=r"(bv[i][1]), "=r"(bv[i][2]), "=r"(bv[i][3])
                                 : "r"(ad0 + (i & 1) * 1024 + (i >> 1) * 8192) : "memory");
                if (b == 0) wgmma_wait<1>(); else wgmma_wait<0>();
                if (b == 0) fence_regs(c0); else fence_regs(c1);
                if (t == 0) STAMP(2, b ? 2 : 5);
#pragma unroll
                for (int jq = 0; jq < 4; ++jq) {
#pragma unroll
                    for (int h = 0; h < 2; ++h) {
                        const uint32_t ad = ad0 + h * 1024 + jq * 8192;
                        uint32_t (&w)[4] = bv[2 * (jq & 1) + h];
                        const int r = 16 * jq + 2 * h;
                        sts128(ad, __float_as_uint(fmaf(gt[h], a[r], bf_lo(w[0]))), __float_as_uint(fmaf(gt[h], a[r + 1], bf_hi(w[0]))),
                               __float_as_uint(fmaf(gt[h], a[r + 4], bf_lo(w[1]))), __float_as_uint(fmaf(gt[h], a[r + 5], bf_hi(w[1]))));
                        sts128(ad ^ 16, __float_as_uint(fmaf(gt[h], a[r + 8], bf_lo(w[2]))), __float_as_uint(fmaf(gt[h], a[r + 9], bf_hi(w[2]))),
                               __float_as_uint(fmaf(gt[h], a[r + 12], bf_lo(w[3]))), __float_as_uint(fmaf(gt[h], a[r + 13], bf_hi(w[3]))));
                        if (jq < 2) asm volatile("ld.shared.v4.b32 {%0,%1,%2,%3}, [%4];" : "=r"(w[0]), "=r"(w[1]), "=r"(w[2]), "=r"(w[3]) : "r"(ad + 16384) : "memory");
                    }
                    fence_async_smem();
                    __syncwarp();
                    if (lane == 0) mbar_arrive(bar_stg + 48 + 32 * b + 8 * jq);
                    if (b == 0 && jq < SKEW2 - 1) late(33 - SKEW2 + jq);
                    if (SKEW2 == 6 && b == 0 && jq == 0) {
                        wgmma_wait<1>();
                        if (t == 0) mbar_arrive(bar_o1);
                    }
                    if (SKEW2 == 6 && b == 0 && jq == 3) late(31);
                }
            };
            mbar_wait(bar_bias, 0);
            if (t == 0) STAMP(2, 4);
            epilogue(c0, 0);
            mbar_wait(bar_bias + 8, 0);
            epilogue(c1, 1);
            if (t == 0) STAMP(2, 7);
            return;
        }
        asm volatile("setmaxnreg.dec.sync.aligned.u32 %0;" ::"n"(REG_C));
    }
    {
        {
            const int t = fresh_tid() & 127, lane = t & 31, w4 = t >> 5;
            Twiddle tw;
            load_twiddle(tw, reinterpret_cast<const uint4*>(g_tw_tab.w) + t);
            const uint32_t lo = (uint32_t)((16 * w4 + (lane & 7)) * 64 + (((lane >> 3) ^ ((lane >> 1) & 3)) << 4));
            const uint32_t tlo = desc_lo(sbase + OFF_CT, 16);
            float dE[32], dO[32];
            int p = wg == 2 ? 2 : 0;
            mbar_wait(bar_stg, 0);
            mbar_wait(bar_tab, 0);
            mbar_wait(bar_k + 8 * p, 0);
            if (BWAIT == 3) mbar_wait(bar_ascan, 0);
            if (t == 0) STAMP(0, wg == 2 ? 50 : 1);
            wgmma_fence();
            conv_s1(dE, dO, tlo, desc_lo(sbase + conv_buf(0) + p * 16384, 8192));
            wgmma_commit();
            wgmma_wait<0>();
            fence_regs(dE); fence_regs(dO);
            named_bar(wg, 128);
#pragma unroll 1
            for (; p < 4; p = 2 * p + 1) {
                const int pn = p < 2 ? 2 * p + 1 : p;
                if (t == 0) STAMP(0, 40 + 2 * p);
                conv_pair(dE, dO, tw, lds32(w_dsk + ((lane & 3) ? 16 : 4 * p)), tlo, sbase + conv_buf(p), sbase + conv_buf(pn), lo, wg,
                                [&]() { mbar_wait(bar_k + 8 * pn, 0); });
                if (lane == 0) mbar_arrive(bar_stg + 16 + 8 * p);
            }
            if (t == 0) STAMP(0, 57 + wg);
            __syncwarp();
        }
        if (wg == 2) {
            {
            const int t = fresh_tid() & 127, lane = t & 31, w4 = t >> 5, g = lane >> 2, t4 = lane & 3;
            const int bid = lds32(w_bid), dt = bid & 7;
            const int trow = (bid >> 4) * 256 + 4 * (bid & 8) + 128 * (w4 & 1) + 8 * (w4 >> 1) + g;
            uint4 xv[16], dk[4];
            const __nv_bfloat16* xp = x + (size_t)trow * D_DIM + dt * 128 + 8 * t4;
#pragma unroll
            for (int i = 0; i < 16; ++i) {
                xv[i] = ldg128(xp + (size_t)(16 * (i >> 3) + 64 * ((i >> 2) & 1)) * D_DIM + 32 * (i & 3));
                if (i & 1) __nanosleep(GAP_X);
            }
#pragma unroll
            for (int jq = 0; jq < 4; ++jq) dk[jq] = ldg128(dskip + dt * 128 + 32 * jq + 8 * t4);
            mbar_wait(bar_fh, 0);
            uint32_t omg[4], g2[4];
#pragma unroll
            for (int i = 0; i < 4; ++i) {
                const float gt = __ldcg(g_gate + trow + 16 * (i >> 1) + 64 * (i & 1));
                if (t4 == 0) asm volatile("st.shared.f32 [%0], %1;" ::"r"(sbase + OFF_PAR + (64 * (i >> 1) + 16 * w4 + 8 * (i & 1) + g) * 4), "f"(gt) : "memory");
                omg[i] = pack_bf16(2.f - 2.f * gt, 2.f - 2.f * gt); g2[i] = pack_bf16(gt, gt);
            }
            if (t == 0) {
                mbar_wait(bar_yrel, 0);
                wait_counter(&g_cnt[(48 + dt) * 32], lds32(w_bid + 4));
                STAMP(0, 16);
                mbar_expect_tx(bar_y1, 24576);
                tma_load_5d(sbase + OFF_CU, &maps.yt3, bar_y1, (bid & 8) * 128 + (bid >> 4) * 128, 0, 0, 0, dt * 4);
                tma_load_5d(sbase + OFF_CU + 12288, &maps.yt3, bar_y1, (bid & 8) * 128 + (bid >> 4) * 128 + 64, 0, 0, 0, dt * 4);
            }
            __syncwarp();
            uint32_t ya = sbase + OFF_CU + (w4 & 1) * 12288 + (lane >> 3) * 3072 + (lane & 7) * 128 + ((((w4 >> 1) ^ ((bid >> 3 & 2) + (w4 & 1))) ^ (lane & 7)) << 4);
#pragma unroll
            for (int p = 0; p < 4; ++p) {
                if (p == 0) { mbar_wait(bar_y1, 0); if (t == 0) STAMP(0, 18); }
                if (p == 3) {
                    if (t == 0) STAMP(0, 17);
                    ya += 21504 - (w4 & 1) * 8192 - (lane >> 3) * 2048;
                    mbar_wait(bar_y, 0);
                    if (t == 0) STAMP(0, 6);
                }
#pragma unroll
                for (int i = 0; i < 4; ++i) {
                    uint32_t yw[4];
                    ldsm_x4_t(yw[0], yw[1], yw[2], yw[3], (ya ^ ((i & 1) << 6) ^ ((i & 2) << 4)) + p * 1024);
#pragma unroll
                    for (int jq = 0; jq < 4; ++jq) {
                        uint32_t& w = (&xv[4 * i + jq].x)[p];
                        w = hfma(g2[i], hmul(w, (&dk[jq].x)[p]), hmul(omg[i], hmul(w, yw[jq])));
                    }
                }
            }
            named_bar(2, 128);
#pragma unroll
            for (int i = 0; i < 16; ++i) {
                if (SLOT5 < 32 && i == 8) mbar_wait(bar_o1, 0);
                sts128(sbase + (i & 8 ? OFF_O1 : OFF_CU) + (i & 3) * 8192 + (w4 * 16 + g + (i & 4) * 2) * 128 + (((2 * t4) ^ g) << 4), xv[i].x, xv[i].y, xv[i].z, xv[i].w);
                if ((i & 7) == 7) {
                    __syncwarp();
                    if (lane == 0) mbar_arrive(bar_bias + (i & 8));
                }
            }
            if (t == 0) STAMP(0, 7);
            }
        }
    }
    }
}

void make_map(CUtensorMap* m, const void* ptr, int rank, const cuuint64_t* dims, const cuuint64_t* strides, const cuuint32_t* box,
              CUtensorMapSwizzle swz, bool f32 = false) {
    cuuint32_t es[5] = {1, 1, 1, 1, 1};
    get_encode()(m, f32 ? CU_TENSOR_MAP_DATA_TYPE_FLOAT32 : CU_TENSOR_MAP_DATA_TYPE_BFLOAT16, rank, const_cast<void*>(ptr), dims, strides, box, es,
                 CU_TENSOR_MAP_INTERLEAVE_NONE, swz, CU_TENSOR_MAP_L2_PROMOTION_L2_256B, CU_TENSOR_MAP_FLOAT_OOB_FILL_NONE);
}
void make_map_2d(CUtensorMap* m, const void* ptr, uint64_t inner, uint64_t outer, uint32_t box_in, uint32_t box_out) {
    cuuint64_t dims[2] = {inner, outer};
    cuuint64_t strides[1] = {inner * 2};
    cuuint32_t box[2] = {box_in, box_out};
    make_map(m, ptr, 2, dims, strides, box, CU_TENSOR_MAP_SWIZZLE_128B);
}
void make_map_conv(CUtensorMap* m, const void* p, uint32_t nch = 2) {
    cuuint64_t dims[4] = {32, 32, 2, 1024};
    cuuint64_t strides[3] = {128, 64, 4096};
    cuuint32_t box[4] = {32, 32, 2, nch};
    make_map(m, p, 4, dims, strides, box, CU_TENSOR_MAP_SWIZZLE_64B);
}

}

extern "C" void kernel_launch(void* const* d_in, const int* in_sizes, int n_in, void* d_out, int out_size) {
    const __nv_bfloat16* x = (const __nv_bfloat16*)d_in[0];
    const __nv_bfloat16* lam_re = (const __nv_bfloat16*)d_in[1];
    const __nv_bfloat16* lam_im = (const __nv_bfloat16*)d_in[2];
    const __nv_bfloat16* b_re = (const __nv_bfloat16*)d_in[3];
    const __nv_bfloat16* b_im = (const __nv_bfloat16*)d_in[4];
    const __nv_bfloat16* c_re = (const __nv_bfloat16*)d_in[5];
    const __nv_bfloat16* c_im = (const __nv_bfloat16*)d_in[6];
    const __nv_bfloat16* log_dt = (const __nv_bfloat16*)d_in[7];
    const __nv_bfloat16* dskip = (const __nv_bfloat16*)d_in[8];
    const __nv_bfloat16* kin = (const __nv_bfloat16*)d_in[10];
    const __nv_bfloat16* vin = (const __nv_bfloat16*)d_in[11];
    const __nv_bfloat16* shift_k = (const __nv_bfloat16*)d_in[12];
    const __nv_bfloat16* ssm_k = (const __nv_bfloat16*)d_in[13];
    const __nv_bfloat16* ssm_D = (const __nv_bfloat16*)d_in[14];
    const __nv_bfloat16* gate_w = (const __nv_bfloat16*)d_in[15];
    float* out = (float*)d_out;

    void *yptr = nullptr, *kvtptr = nullptr;
    cudaGetSymbolAddress(&yptr, g_y2);
    cudaGetSymbolAddress(&kvtptr, g_kvT);

    Maps maps;
    {
        cuuint64_t dims[5] = {1024, 2, 4, 32, 8};
        cuuint64_t strides[4] = {2048, 64 * 2048, 2 * 2048, 256 * 2048};
        cuuint32_t box[5] = {64, 2, 4, 32, 1};
        make_map(&maps.x5, x, 5, dims, strides, box, CU_TENSOR_MAP_SWIZZLE_128B);
    }
    int bmode = 0;
    {
        const uint64_t a = (uint64_t)b_re, b = (uint64_t)b_im;
        const uint64_t delta = a < b ? b - a : a - b;
        if (delta != 0 && (delta & 15) == 0 && delta < (1ull << 40)) bmode = a < b ? 1 : 2;
        cuuint64_t dims[4] = {1024, 8, 2, 128};
        cuuint64_t strides[3] = {2048, bmode ? delta : 16, 16384};
        cuuint32_t box[4] = {64, 8, 2, 4};
        make_map(&maps.b4, a < b ? b_re : b_im, 4, dims, strides, box, CU_TENSOR_MAP_SWIZZLE_128B);
    }
    make_map_2d(&maps.bre, b_re, 1024, 1024, 64, 8);
    make_map_2d(&maps.bim, b_im, 1024, 1024, 64, 8);
    {
        cuuint64_t dims[3] = {S_LEN, 128, 8};
        cuuint64_t strides[2] = {8 * 4096, 4096};
        cuuint32_t box[3] = {64, 16, 2};
        make_map(&maps.kvst, kvtptr, 3, dims, strides, box, CU_TENSOR_MAP_SWIZZLE_128B);
    }
    make_map_conv(&maps.sk, ssm_k, 1);
    for (int i = 0; i < 2; ++i) {
        cuuint64_t dims[5] = {1024, 2, 4, 4, 32};
        cuuint64_t strides[4] = {2048, 8 * 2048, 2 * 2048, 32 * 2048};
        cuuint32_t box[5] = {64, 2, 4, 4, 4};
        make_map(i ? &maps.cim : &maps.cre, i ? c_im : c_re, 5, dims, strides, box, CU_TENSOR_MAP_SWIZZLE_128B);
    }
    {
        cuuint64_t dims[5] = {S_LEN, 2, 4, 4, 32};
        cuuint64_t strides[4] = {4096, 8 * 4096, 2 * 4096, 32 * 4096};
        cuuint32_t box[5] = {64, 2, 4, 1, 4};
        make_map(&maps.yt, yptr, 5, dims, strides, box, CU_TENSOR_MAP_SWIZZLE_128B);
        box[3] = 3;
        make_map(&maps.yt3, yptr, 5, dims, strides, box, CU_TENSOR_MAP_SWIZZLE_128B);
    }
    {
        cuuint64_t dims[5] = {D_DIM, 8, 4, 8, 8};
        cuuint64_t strides[4] = {4096, 64 * 4096, 8 * 4096, 256 * 4096};
        cuuint32_t box[5] = {32, 8, 4, 2, 1};
        make_map(&maps.out, out, 5, dims, strides, box, CU_TENSOR_MAP_SWIZZLE_128B, true);
    }

    auto kern = bmode == 1 ? fused_kernel<1> : bmode == 2 ? fused_kernel<2> : fused_kernel<0>;
    cudaFuncSetAttribute(kern, cudaFuncAttributeMaxDynamicSharedMemorySize, SMEM_BYTES);
    static int grid = 0;
    if (!grid) {
        int dev = 0, sms = 0;
        cudaGetDevice(&dev);
        cudaDeviceGetAttribute(&sms, cudaDevAttrMultiProcessorCount, dev);
        grid = sms == 132 ? 132 : 128;
    }
    kern<<<grid, 512, SMEM_BYTES>>>(x, b_re, b_im, kin, vin, ssm_k, shift_k, ssm_D, lam_re, lam_im, log_dt, gate_w, dskip, c_re, c_im, maps);
}
```

```cpp
#include <cuda_runtime.h>
#include <cuda_bf16.h>
#include <cuda.h>
#include <stdint.h>
#include <type_traits>

namespace {
__device__ __forceinline__ uint32_t smem_u32(const void* p) { return (uint32_t)__cvta_generic_to_shared(p); }
__device__ __forceinline__ void mbar_init(uint32_t bar, uint32_t count) {
    asm volatile("mbarrier.init.shared::cta.b64 [%0], %1;" ::"r"(bar), "r"(count) : "memory");
}
__device__ __forceinline__ void mbar_expect_tx(uint32_t bar, uint32_t bytes) {
    asm volatile("mbarrier.arrive.expect_tx.shared::cta.b64 _, [%0], %1;" ::"r"(bar), "r"(bytes) : "memory");
}
__device__ __forceinline__ void mbar_arrive(uint32_t bar) {
    asm volatile("mbarrier.arrive.shared::cta.b64 _, [%0];" ::"r"(bar) : "memory");
}
__device__ __forceinline__ void mbar_wait(uint32_t bar, uint32_t parity) {
    asm volatile(
        "{\n"
        ".reg .pred p;\n"
        ".reg .u32 n;\n"
        "mov.u32 n, 0;\n"
        "LAB_WAIT:\n"
        "mbarrier.try_wait.parity.shared::cta.b64 p, [%0], %1;\n"
        "@p bra LAB_DONE;\n"
        "add.u32 n, n, 1;\n"
        "setp.lt.u32 p, n, 0x400000;\n"
        "@p bra LAB_WAIT;\n"
        "trap;\n"
        "LAB_DONE:\n"
        "}\n" ::"r"(bar), "r"(parity) : "memory");
}
__device__ __forceinline__ void tma_load_2d(uint32_t dst, const CUtensorMap* map, uint32_t bar, int c0, int c1) {
    asm volatile(
        "cp.async.bulk.tensor.2d.shared::cluster.global.mbarrier::complete_tx::bytes [%0], [%1, {%3, %4}], [%2];"
        ::"r"(dst), "l"((uint64_t)map), "r"(bar), "r"(c0), "r"(c1) : "memory");
}
__device__ __forceinline__ void tma_load_4d(uint32_t dst, const CUtensorMap* map, uint32_t bar, int c0, int c1, int c2, int c3) {
    asm volatile(
        "cp.async.bulk.tensor.4d.shared::cluster.global.mbarrier::complete_tx::bytes [%0], [%1, {%3, %4, %5, %6}], [%2];"
        ::"r"(dst), "l"((uint64_t)map), "r"(bar), "r"(c0), "r"(c1), "r"(c2), "r"(c3) : "memory");
}
__device__ __forceinline__ void tma_load_5d(uint32_t dst, const CUtensorMap* map, uint32_t bar, int c0, int c1, int c2, int c3, int c4) {
    asm volatile(
        "cp.async.bulk.tensor.5d.shared::cluster.global.mbarrier::complete_tx::bytes [%0], [%1, {%3, %4, %5, %6, %7}], [%2];"
        ::"r"(dst), "l"((uint64_t)map), "r"(bar), "r"(c0), "r"(c1), "r"(c2), "r"(c3), "r"(c4) : "memory");
}
__device__ __forceinline__ void bulk_load(uint32_t dst, const void* src, uint32_t bytes, uint32_t bar) {
    asm volatile("cp.async.bulk.shared::cluster.global.mbarrier::complete_tx::bytes [%0], [%1], %2, [%3];"
                 ::"r"(dst), "l"(src), "r"(bytes), "r"(bar) : "memory");
}
__device__ __forceinline__ void tma_store_3d(const CUtensorMap* map, uint32_t src, int c0, int c1, int c2) {
    asm volatile("cp.async.bulk.tensor.3d.global.shared::cta.bulk_group [%0, {%2, %3, %4}], [%1];"
                 ::"l"((uint64_t)map), "r"(src), "r"(c0), "r"(c1), "r"(c2) : "memory");
}
__device__ __forceinline__ void bulk_commit() { asm volatile("cp.async.bulk.commit_group;" ::: "memory"); }
__device__ __forceinline__ void bulk_wait0() { asm volatile("cp.async.bulk.wait_group 0;" ::: "memory"); }
__device__ __forceinline__ void bulk_wait_read0() { asm volatile("cp.async.bulk.wait_group.read 0;" ::: "memory"); }
__device__ __forceinline__ void fence_async_smem() { asm volatile("fence.proxy.async.shared::cta;" ::: "memory"); }
__device__ __forceinline__ void named_bar(int id, int n) { asm volatile("bar.sync %0, %1;" ::"r"(id), "r"(n) : "memory"); }
__device__ __forceinline__ void sts128(uint32_t addr, uint32_t a, uint32_t b, uint32_t c, uint32_t d) {
    asm volatile("st.shared.v4.b32 [%0], {%1, %2, %3, %4};" ::"r"(addr), "r"(a), "r"(b), "r"(c), "r"(d) : "memory");
}
__device__ __forceinline__ void prefetch_map(const CUtensorMap* m) {
    asm volatile("prefetch.tensormap [%0];" ::"l"((uint64_t)m) : "memory");
}
__device__ __forceinline__ void wgmma_fence() { asm volatile("wgmma.fence.sync.aligned;" ::: "memory"); }
__device__ __forceinline__ void wgmma_commit() { asm volatile("wgmma.commit_group.sync.aligned;" ::: "memory"); }
template <int N>
__device__ __forceinline__ void wgmma_wait() { asm volatile("wgmma.wait_group.sync.aligned %0;" ::"n"(N) : "memory"); }
template <int N>
__device__ __forceinline__ void fence_regs(float (&a)[N]) {
#pragma unroll
    for (int i = 0; i < N; ++i) asm volatile("" : "+f"(a[i])::"memory");
}
template <int N>
__device__ __forceinline__ void fence_regs(uint32_t (&a)[N]) {
#pragma unroll
    for (int i = 0; i < N; ++i) asm volatile("" : "+r"(a[i])::"memory");
}
#define R8(a, i) "+f"(a[i + 0]), "+f"(a[i + 1]), "+f"(a[i + 2]), "+f"(a[i + 3]), "+f"(a[i + 4]), "+f"(a[i + 5]), "+f"(a[i + 6]), "+f"(a[i + 7])
#define REGS32 "{%0, %1, %2, %3, %4, %5, %6, %7, %8, %9, %10, %11, %12, %13, %14, %15, %16, %17, %18, %19, %20, %21, %22, %23, %24, %25, %26, %27, %28, %29, %30, %31}"
#define REGS16 "{%0, %1, %2, %3, %4, %5, %6, %7, %8, %9, %10, %11, %12, %13, %14, %15}"

__host__ __device__ constexpr uint32_t desc_hi(uint32_t sbo, uint32_t mode) { return (sbo >> 4) | (mode << 30); }
__device__ __forceinline__ uint32_t desc_lo(uint32_t saddr, uint32_t lbo) { return ((saddr & 0x3FFFF) >> 4) | ((lbo >> 4) << 16); }
constexpr uint32_t HI128 = desc_hi(1024, 1), HI64 = desc_hi(512, 2);
#define W8(a, i) "=f"(a[i + 0]), "=f"(a[i + 1]), "=f"(a[i + 2]), "=f"(a[i + 3]), "=f"(a[i + 4]), "=f"(a[i + 5]), "=f"(a[i + 6]), "=f"(a[i + 7])
template <int TA, int TB, int ACC, uint32_t AHI, uint32_t BHI>
__device__ __forceinline__ void wgmma_n64_ss(float (&d)[32], uint32_t alo, uint32_t blo) {
#define N64_TEXT "{\n.reg .pred p;\n.reg .b64 da, db;\nsetp.ne.b32 p, %36, 0;\nmov.b64 da, {%32, %37};\nmov.b64 db, {%33, %38};\n" \
        "wgmma.mma_async.sync.aligned.m64n64k16.f32.bf16.bf16 " REGS32 ", da, db, p, 1, 1, %34, %35;\n}\n"
    if (ACC) asm volatile(N64_TEXT : R8(d, 0), R8(d, 8), R8(d, 16), R8(d, 24) : "r"(alo), "r"(blo), "n"(TA), "n"(TB), "n"(ACC), "n"(AHI), "n"(BHI));
    else asm volatile(N64_TEXT : W8(d, 0), W8(d, 8), W8(d, 16), W8(d, 24) : "r"(alo), "r"(blo), "n"(TA), "n"(TB), "n"(ACC), "n"(AHI), "n"(BHI));
}
template <int ACC, int SA>
__device__ __forceinline__ void wgmma_n32_tt(float (&d)[16], uint32_t alo, uint32_t blo) {
#define N32T_TEXT "{\n.reg .pred p;\n.reg .b64 da, db;\nsetp.ne.b32 p, %18, 0;\nmov.b64 da, {%16, %19};\nmov.b64 db, {%17, %20};\n" \
        "wgmma.mma_async.sync.aligned.m64n32k16.f32.bf16.bf16 " REGS16 ", da, db, p, %21, 1, 1, 1;\n}\n"
    if (ACC) asm volatile(N32T_TEXT : R8(d, 0), R8(d, 8) : "r"(alo), "r"(blo), "n"(ACC), "n"(HI64), "n"(HI128), "n"(SA));
    else asm volatile(N32T_TEXT : W8(d, 0), W8(d, 8) : "r"(alo), "r"(blo), "n"(ACC), "n"(HI64), "n"(HI128), "n"(SA));
}
__device__ __forceinline__ void wgmma_n16_rs(float (&d)[8], const uint32_t (&a)[4], uint32_t blo) {
    asm volatile("{\n.reg .pred p;\n.reg .b64 db;\nsetp.ne.b32 p, 0, 0;\nmov.b64 db, {%12, %13};\n"
        "wgmma.mma_async.sync.aligned.m64n16k16.f32.bf16.bf16 {%0, %1, %2, %3, %4, %5, %6, %7}, {%8, %9, %10, %11}, db, p, 1, 1, 0;\n}\n"
        : W8(d, 0) : "r"(a[0]), "r"(a[1]), "r"(a[2]), "r"(a[3]), "r"(blo), "n"(HI128));
}

__device__ __forceinline__ float bf16r(float x) { return __bfloat162float(__float2bfloat16_rn(x)); }
__device__ __forceinline__ uint32_t pack_bf16(float lo, float hi) {
    __nv_bfloat162 v = __floats2bfloat162_rn(lo, hi);
    return *reinterpret_cast<uint32_t*>(&v);
}
__device__ __forceinline__ __nv_bfloat162 as_bf2(uint32_t w) { return *reinterpret_cast<__nv_bfloat162*>(&w); }
__device__ __forceinline__ uint32_t as_u32(__nv_bfloat162 v) { return *reinterpret_cast<uint32_t*>(&v); }
__device__ __forceinline__ float bf_lo(uint32_t w) { return __uint_as_float(w << 16); }
__device__ __forceinline__ float bf_hi(uint32_t w) { return __uint_as_float(w & 0xFFFF0000u); }
__device__ __forceinline__ void ldsm_x4_t(uint32_t& r0, uint32_t& r1, uint32_t& r2, uint32_t& r3, uint32_t addr) {
    asm volatile("ldmatrix.sync.aligned.m8n8.x4.trans.shared.b16 {%0,%1,%2,%3}, [%4];"
                 : "=r"(r0), "=r"(r1), "=r"(r2), "=r"(r3) : "r"(addr) : "memory");
}
__device__ __forceinline__ void stsm_x4(uint32_t addr, uint32_t r0, uint32_t r1, uint32_t r2, uint32_t r3) {
    asm volatile("stmatrix.sync.aligned.m8n8.x4.shared.b16 [%0], {%1,%2,%3,%4};"
                 ::"r"(addr), "r"(r0), "r"(r1), "r"(r2), "r"(r3) : "memory");
}
__device__ __forceinline__ void stsm_x4_t(uint32_t addr, uint32_t r0, uint32_t r1, uint32_t r2, uint32_t r3) {
    asm volatile("stmatrix.sync.aligned.m8n8.x4.trans.shared.b16 [%0], {%1,%2,%3,%4};"
                 ::"r"(addr), "r"(r0), "r"(r1), "r"(r2), "r"(r3) : "memory");
}
__device__ __forceinline__ uint32_t lds32(uint32_t addr) {
    uint32_t v;
    asm volatile("ld.shared.b32 %0, [%1];" : "=r"(v) : "r"(addr));
    return v;
}

typedef CUresult (*EncodeFn)(CUtensorMap*, CUtensorMapDataType, cuuint32_t, void*, const cuuint64_t*, const cuuint64_t*,
                             const cuuint32_t*, const cuuint32_t*, CUtensorMapInterleave, CUtensorMapSwizzle,
                             CUtensorMapL2promotion, CUtensorMapFloatOOBfill);
EncodeFn get_encode() {
    static EncodeFn fn = nullptr;
    if (!fn) {
        void* p = nullptr;
        cudaDriverEntryPointQueryResult qres;
        cudaGetDriverEntryPoint("cuTensorMapEncodeTiled", &p, cudaEnableDefault, &qres);
        fn = (EncodeFn)p;
    }
    return fn;
}
}
namespace {
constexpr double c_pi = 3.14159265358979323846;
constexpr double c_cos256(int i) {
    i &= 255;
    if (i > 128) i = 256 - i;
    double sgn = 1.0;
    if (i > 64) { i = 128 - i; sgn = -1.0; }
    if (i == 64) return 0.0;
    double x = 2.0 * c_pi * i / 256.0, x2 = x * x, term = 1.0, sum = 1.0;
    for (int k = 1; k < 20; ++k) { term *= -x2 / ((2 * k - 1) * (2 * k)); sum += term; }
    return sgn * sum;
}
constexpr uint32_t c_bf16(double v) {
    if (v == 0.0) return 0u;
    uint32_t s = v < 0 ? 0x8000u : 0u;
    double a = v < 0 ? -v : v;
    int e = 0;
    while (a >= 2.0) { a *= 0.5; ++e; }
    while (a < 1.0) { a *= 2.0; --e; }
    int r = (int)(a * 128.0 + 0.5);
    if (r == 256) { r = 128; ++e; }
    return s | (uint32_t)((e + 127) << 7) | (uint32_t)(r - 128);
}
__host__ __device__ constexpr int conv_k1(int r) { return (r & 8) ? 63 - (((r >> 4) << 3) | (r & 7)) : (((r >> 4) << 3) | (r & 7)); }
struct ConvTab { uint32_t w[96 * 32]; };
constexpr ConvTab make_conv_tab() {
    ConvTab t{};
    uint32_t cs[256] = {};
    for (int i = 0; i < 256; ++i) cs[i] = c_bf16(c_cos256(i));
    for (int n = 0; n < 96; ++n)
        for (int c = 0; c < 64; ++c) {
            int a = 0;
            if (n < 32) {
                const int ro = (n >> 3) & 1, ri = n & 7, co = (c >> 3) & 1, ci = c & 7;
                a = n < 16 ? 8 * ci * (4 * ri + (c >> 4)) : 8 * ri * (4 * ci + (c >> 4));
                a += (ro == co) ? 0 : (ro == 0) ? 192 : 64;
            } else {
                const int r = n - 32, n1 = 2 * (c & 31) + (c >> 5);
                a = n1 * (2 * (((r >> 4) << 3) | (r & 7)) + 1) + ((r & 8) ? 64 : 0);
            }
            const int off = n * 128 + (((c >> 3) ^ (n & 7)) << 4) + (c & 7) * 2;
            t.w[off >> 2] |= cs[a & 255] << ((off & 2) * 8);
        }
    return t;
}
__device__ __align__(128) constexpr ConvTab g_conv_tab = make_conv_tab();

struct Twiddle { uint32_t r[8], i[8], n[8]; };
constexpr double c_cospi(double x) {
    double sgn = 1.0;
    if (x > 0.5) { x = 1.0 - x; sgn = -1.0; }
    const double y = c_pi * x, y2 = y * y;
    double term = 1.0, sum = 1.0;
    for (int k = 1; k < 12; ++k) { term *= -y2 / ((2 * k - 1) * (2 * k)); sum += term; }
    return sgn * sum;
}
struct TwTab { uint32_t w[3072]; };
constexpr TwTab make_tw_tab() {
    TwTab t{};
    for (int th = 0; th < 128; ++th)
        for (int q = 0; q < 8; ++q)
            for (int e = 0; e < 2; ++e) {
                const int k1 = conv_k1(16 * (th >> 5) + 8 * (q & 1) + ((th & 31) >> 2)), n2 = 8 * (q >> 1) + 2 * (th & 3) + e;
                const double x = (double)(n2 * (2 * k1 + 1)) / 4096.0;
                const double cs = c_cospi(x), sn = n2 == 0 ? 0.0 : c_cospi(x > 0.5 ? x - 0.5 : 0.5 - x);
                t.w[((q >> 2) * 128 + th) * 4 + (q & 3)] |= c_bf16(cs * 0.0625) << (16 * e);
                t.w[((2 + (q >> 2)) * 128 + th) * 4 + (q & 3)] |= c_bf16(-sn * 0.0625) << (16 * e);
                t.w[((4 + (q >> 2)) * 128 + th) * 4 + (q & 3)] |= c_bf16(sn * 0.0625) << (16 * e);
            }
    return t;
}
__device__ __align__(128) constexpr TwTab g_tw_tab = make_tw_tab();
__device__ __forceinline__ void load_twiddle(Twiddle& tw, const uint4* p) {
#pragma unroll
    for (int q = 0; q < 2; ++q) {
        const uint4 a = __ldg(p + q * 128);
        const uint4 b = __ldg(p + (2 + q) * 128);
        tw.r[4 * q] = a.x; tw.r[4 * q + 1] = a.y; tw.r[4 * q + 2] = a.z; tw.r[4 * q + 3] = a.w;
        const uint4 n = __ldg(p + (4 + q) * 128);
        tw.n[4 * q] = n.x; tw.n[4 * q + 1] = n.y; tw.n[4 * q + 2] = n.z; tw.n[4 * q + 3] = n.w;
        tw.i[4 * q] = b.x; tw.i[4 * q + 1] = b.y; tw.i[4 * q + 2] = b.z; tw.i[4 * q + 3] = b.w;
    }
}

__device__ __forceinline__ int fresh_tid() { int v; asm volatile("mov.u32 %0, %tid.x;" : "=r"(v)); return v; }
__device__ __forceinline__ uint32_t hmul(uint32_t a, uint32_t b) { return as_u32(__hmul2_rn(as_bf2(a), as_bf2(b))); }
__device__ __forceinline__ uint32_t hadd(uint32_t a, uint32_t b) { return as_u32(__hadd2_rn(as_bf2(a), as_bf2(b))); }
__device__ __forceinline__ uint32_t hsub(uint32_t a, uint32_t b) { return as_u32(__hsub2_rn(as_bf2(a), as_bf2(b))); }
__device__ __forceinline__ uint32_t hfma(uint32_t a, uint32_t b, uint32_t c) { return as_u32(__hfma2(as_bf2(a), as_bf2(b), as_bf2(c))); }

__device__ __forceinline__ void conv_dft8(float (&x)[4][8], const uint32_t (&f)[4][4], uint32_t blo) {
#pragma unroll
    for (int r = 0; r < 4; ++r) wgmma_n16_rs(x[r], f[r], blo + 2 * r);
}
template <class T, int N>
__device__ __forceinline__ void fence_regs4(T (&a)[4][N]) { fence_regs(a[0]); fence_regs(a[1]); fence_regs(a[2]); fence_regs(a[3]); }
__device__ __forceinline__ void conv_s1(float (&dE)[32], float (&dO)[32], uint32_t tlo, uint32_t ulo) {
    wgmma_n64_ss<0, 1, 0, HI128, HI64>(dE, tlo + 256, ulo);
    wgmma_n64_ss<0, 1, 0, HI128, HI64>(dO, tlo + 256 + 4, ulo + 128);
    wgmma_n64_ss<0, 1, 1, HI128, HI64>(dE, tlo + 256 + 2, ulo + 64);
    wgmma_n64_ss<0, 1, 1, HI128, HI64>(dO, tlo + 256 + 6, ulo + 192);
}
template <int S>
__device__ __forceinline__ void conv_t1(const float (&dE)[32], const float (&dO)[32], const Twiddle& tw, float dsk, uint32_t (&f)[4][4]) {
    uint32_t ar[8], ai[8], fs[8], fd[8];
#pragma unroll
    for (int j = 0; j < 4; ++j) {
        const int i = 16 * S + 4 * j;
        const uint32_t e0 = pack_bf16(i == 16 ? dE[i] + dsk : dE[i], dE[i + 1]), e1 = pack_bf16(dE[i + 2], dE[i + 3]);
        const uint32_t o0 = pack_bf16(dO[i], dO[i + 1]), o1 = pack_bf16(dO[i + 2], dO[i + 3]);
        ar[2 * j] = hadd(e0, o0); ai[2 * j] = hadd(e1, o1);
        ar[2 * j + 1] = hsub(e0, o0); ai[2 * j + 1] = hsub(o1, e1);
    }
#pragma unroll
    for (int q = 0; q < 4; ++q) {
        const uint32_t pr = hfma(ar[q], tw.r[q], hmul(ai[q], tw.n[q])), pi = hfma(ar[q], tw.i[q], hmul(ai[q], tw.r[q]));
        fs[q] = hfma(ar[4 + q], tw.r[4 + q], hfma(ai[4 + q], tw.n[4 + q], pr));
        fs[4 + q] = hfma(ar[4 + q], tw.i[4 + q], hfma(ai[4 + q], tw.r[4 + q], pi));
        fd[q] = hfma(pr, 0xC000C000u, fs[q]);
        fd[4 + q] = hfma(pi, 0xC000C000u, fs[4 + q]);
    }
#pragma unroll
    for (int h = 0; h < 2; ++h) {
        f[0][h] = hadd(fs[h], fs[2 + h]); f[0][2 + h] = hadd(fs[4 + h], fs[6 + h]);
        f[2][h] = hsub(fs[h], fs[2 + h]); f[2][2 + h] = hsub(fs[4 + h], fs[6 + h]);
        f[1][h] = hadd(fd[h], fd[6 + h]); f[1][2 + h] = hsub(fd[4 + h], fd[2 + h]);
        f[3][h] = hsub(fd[h], fd[6 + h]); f[3][2 + h] = hadd(fd[4 + h], fd[2 + h]);
    }
}
__device__ __forceinline__ void conv_prod(const float (&xu)[8], const float (&xk)[8], uint32_t (&f)[4]) {
#pragma unroll
    for (int h = 0; h < 2; ++h) {
        float pr[2], pi[2];
#pragma unroll
        for (int e = 0; e < 2; ++e) {
            const float ur = xu[2 * h + e], ui = xu[4 + 2 * h + e], kr = xk[2 * h + e], ki = xk[4 + 2 * h + e];
            pr[e] = fmaf(ur, kr, -ui * ki);
            pi[e] = fmaf(-ur, ki, -ui * kr);
        }
        f[h] = pack_bf16(pr[0], pr[1]);
        f[2 + h] = pack_bf16(pi[0], pi[1]);
    }
}
template <bool SECOND, class G>
__device__ __forceinline__ void conv_channel(float (&dE)[32], float (&dO)[32], const Twiddle& tw, float dsk, uint32_t tlo, uint32_t nxt,
                                             uint32_t wre, uint32_t wim, int bar, G before_next) {
    float xu[4][8], xk[4][8];
    {
        uint32_t fu[4][4], fk[4][4];
        conv_t1<0>(dE, dO, tw, 0.f, fu);
        wgmma_fence();
        conv_dft8(xu, fu, tlo);
        wgmma_commit();
        conv_t1<1>(dE, dO, tw, dsk, fk);
        wgmma_fence();
        conv_dft8(xk, fk, tlo);
        wgmma_commit();
        before_next();
        wgmma_wait<0>();
        fence_regs4(xu); fence_regs4(xk);
        fence_regs4(fu); fence_regs4(fk);
    }
    uint32_t fp[4][4];
#pragma unroll
    for (int r = 0; r < 4; ++r) conv_prod(xu[r], xk[r], fp[r]);
    wgmma_fence();
    conv_dft8(xu, fp, tlo + 128);
    wgmma_commit();
    if (!SECOND || nxt) {
        if (SECOND) wgmma_fence();
        conv_s1(dE, dO, tlo, nxt);
        wgmma_commit();
        wgmma_wait<1>();
    } else {
        wgmma_wait<0>();
#pragma unroll
        for (int i = 0; i < 32; ++i) { dE[i] = 0.f; dO[i] = 0.f; }
        fence_regs(dE); fence_regs(dO);
    }
    fence_regs4(xu);
    fence_regs4(fp);
    uint32_t zr[8], zi[8], wr[8], wi[8];
#pragma unroll
    for (int h = 0; h < 2; ++h) {
        uint32_t yr[4], yi[4];
#pragma unroll
        for (int r = 0; r < 4; ++r) { yr[r] = pack_bf16(xu[r][2 * h], xu[r][2 * h + 1]); yi[r] = pack_bf16(xu[r][4 + 2 * h], xu[r][5 + 2 * h]); }
        const uint32_t u0r = hadd(yr[0], yr[2]), u0i = hadd(yi[0], yi[2]), u1r = hsub(yr[0], yr[2]), u1i = hsub(yi[0], yi[2]);
        const uint32_t v0r = hadd(yr[1], yr[3]), v0i = hadd(yi[1], yi[3]), v1r = hsub(yr[1], yr[3]), v1i = hsub(yi[1], yi[3]);
        zr[h] = hadd(u0r, v0r); zi[h] = hadd(u0i, v0i); zr[4 + h] = hsub(u0r, v0r); zi[4 + h] = hsub(u0i, v0i);
        zr[2 + h] = hadd(u1r, v1i); zi[2 + h] = hsub(u1i, v1r); zr[6 + h] = hsub(u1r, v1i); zi[6 + h] = hadd(u1i, v1r);
    }
#pragma unroll
    for (int q = 0; q < 8; ++q) {
        wr[q] = hfma(zr[q], tw.r[q], hmul(zi[q], tw.n[q]));
        wi[q] = hfma(zr[q], tw.i[q], hmul(zi[q], tw.r[q]));
    }
    if (SECOND) named_bar(bar, 128);
    stsm_x4(wre, hadd(wr[0], wr[1]), hadd(wr[2], wr[3]), hadd(wr[4], wr[5]), hadd(wr[6], wr[7]));
    stsm_x4(wre + 512, hsub(wi[1], wi[0]), hsub(wi[3], wi[2]), hsub(wi[5], wi[4]), hsub(wi[7], wi[6]));
    stsm_x4(wim, hsub(wr[1], wr[0]), hsub(wr[3], wr[2]), hsub(wr[5], wr[4]), hsub(wr[7], wr[6]));
    stsm_x4(wim + 512, hadd(wi[0], wi[1]), hadd(wi[2], wi[3]), hadd(wi[4], wi[5]), hadd(wi[6], wi[7]));
}
template <class G>
__device__ __forceinline__ void conv_pair(float (&dE)[32], float (&dO)[32], const Twiddle& tw, uint32_t dd, uint32_t tlo, uint32_t u0, uint32_t un,
                                          uint32_t lo, int BAR, G before_next) {
    conv_channel<false>(dE, dO, tw, bf_lo(dd), tlo, desc_lo(u0 + 4096, 8192), u0 + lo, u0 + 8192 + lo, BAR, []() {});
    wgmma_wait<0>();
    fence_regs(dE); fence_regs(dO);
    conv_channel<true>(dE, dO, tw, bf_hi(dd), tlo, un == u0 ? 0 : desc_lo(un, 8192), u0 + 4096 + lo, u0 + 12288 + lo, BAR, before_next);
    fence_async_smem();
    named_bar(BAR, 128);
    float ye[16], yo[16];
    wgmma_fence();
    const uint32_t wlo = desc_lo(u0, 4096);
    wgmma_n32_tt<0, 1>(ye, wlo, tlo + 256);
    wgmma_n32_tt<0, -1>(yo, wlo + 512, tlo + 256 + 4);
#pragma unroll
    for (int k = 1; k < 4; ++k) {
        wgmma_n32_tt<1, 1>(ye, wlo + 64 * k, tlo + 256 + 128 * k);
        wgmma_n32_tt<1, -1>(yo, wlo + 512 + 64 * k, tlo + 256 + 4 + 128 * k);
    }
    wgmma_commit();
    wgmma_wait<0>();
    fence_regs(ye); fence_regs(yo);
    fence_regs(dE); fence_regs(dO);
    named_bar(BAR, 128);
    const int t = fresh_tid();
    const uint32_t ya = u0 + (t & 64) * 64 + (t & 31) * 64 + (((((t >> 4) & 2) ^ (t >> 1)) & 3) << 4);
#pragma unroll
    for (int h = 0; h < 2; ++h) {
        stsm_x4_t(ya ^ (16 * h), pack_bf16(ye[2 * h], ye[2 * h + 1]), pack_bf16(ye[4 + 2 * h], ye[5 + 2 * h]),
                  pack_bf16(ye[8 + 2 * h], ye[9 + 2 * h]), pack_bf16(ye[12 + 2 * h], ye[13 + 2 * h]));
        stsm_x4_t((ya ^ (16 * h)) + 2048, pack_bf16(yo[2 * h], yo[2 * h + 1]), pack_bf16(yo[4 + 2 * h], yo[5 + 2 * h]),
                  pack_bf16(yo[8 + 2 * h], yo[9 + 2 * h]), pack_bf16(yo[12 + 2 * h], yo[13 + 2 * h]));
    }
    fence_async_smem();
    __syncwarp();
}
}

namespace {

constexpr int S_LEN = 2048;
constexpr int D_DIM = 1024;

#define REG_P 24
#define REG_AB 168
#define REG_C 152
#define SKEW1 4
#define SKEW2 6
#define QD 4
#define QKB 18
#define QD2 6
#define SLOT4 16
#define SLOT5 27
#define EPF 2
#define PFD 7
#define TK_PF0 0
#define TK_KV0 2
#define TK_KV1 4
#define TK_C 8
#define GAP_PF 300
#define GAP_KV 50
#define GAP_ST 50
#define GAP_CV 100
#define GAP_HB 100
#define GAP_Y 100
#define GAP_X 150
#define ALTMAP 0

__device__ __align__(1024) __nv_bfloat16 g_H[2 * D_DIM * S_LEN];
__device__ __align__(1024) __nv_bfloat16 g_y2[D_DIM * S_LEN];
__device__ __align__(1024) __nv_bfloat16 g_kvT[D_DIM * S_LEN];
__device__ __align__(128) float g_gate[S_LEN];
__device__ __align__(128) unsigned long long g_agg[8 * D_DIM];
__device__ __align__(128) unsigned int g_cnt[56 * 32];

#define STAMP(k, s) do { } while (0)
#define SAMPLE(i) do { } while (0)

__device__ __forceinline__ void tma_store_5d(const CUtensorMap* map, uint32_t src, int c0, int c1, int c2, int c3, int c4) {
    asm volatile("cp.async.bulk.tensor.5d.global.shared::cta.bulk_group [%0, {%2, %3, %4, %5, %6}], [%1];"
                 ::"l"((uint64_t)map), "r"(src), "r"(c0), "r"(c1), "r"(c2), "r"(c3), "r"(c4) : "memory");
}
#define ELECT "{\n.reg .pred p;\nelect.sync _|p, 0xffffffff;\n@p "
__device__ __forceinline__ void e_expect_tx(uint32_t bar, uint32_t bytes) {
    asm volatile(ELECT "mbarrier.arrive.expect_tx.shared::cta.b64 _, [%0], %1;\n}" ::"r"(bar), "r"(bytes) : "memory");
}
__device__ __forceinline__ void e_arrive(uint32_t bar) {
    asm volatile(ELECT "mbarrier.arrive.shared::cta.b64 _, [%0];\n}" ::"r"(bar) : "memory");
}
__device__ __forceinline__ void e_load_4d(uint32_t dst, const CUtensorMap* map, uint32_t bar, int c0, int c1, int c2, int c3) {
    asm volatile(ELECT "cp.async.bulk.tensor.4d.shared::cluster.global.mbarrier::complete_tx::bytes [%0], [%1, {%3, %4, %5, %6}], [%2];\n}"
        ::"r"(dst), "l"((uint64_t)map), "r"(bar), "r"(c0), "r"(c1), "r"(c2), "r"(c3) : "memory");
}
__device__ __forceinline__ void e_load_5d(uint32_t dst, const CUtensorMap* map, uint32_t bar, int c0, int c1, int c2, int c3, int c4) {
    asm volatile(ELECT "cp.async.bulk.tensor.5d.shared::cluster.global.mbarrier::complete_tx::bytes [%0], [%1, {%3, %4, %5, %6, %7}], [%2];\n}"
        ::"r"(dst), "l"((uint64_t)map), "r"(bar), "r"(c0), "r"(c1), "r"(c2), "r"(c3), "r"(c4) : "memory");
}
__device__ __forceinline__ void e_bulk_load(uint32_t dst, const void* src, uint32_t bytes, uint32_t bar) {
    asm volatile(ELECT "cp.async.bulk.shared::cluster.global.mbarrier::complete_tx::bytes [%0], [%1], %2, [%3];\n}"
                 ::"r"(dst), "l"(src), "r"(bytes), "r"(bar) : "memory");
}
__device__ __forceinline__ void l2_prefetch(const void* p, uint32_t bytes) {
    asm volatile("cp.async.bulk.prefetch.L2.global [%0], %1;" ::"l"(p), "r"(bytes) : "memory");
}
__device__ __forceinline__ void l2_prefetch_4d(const CUtensorMap* map, int c0, int c1, int c2, int c3) {
    asm volatile("cp.async.bulk.prefetch.tensor.4d.L2.global [%0, {%1, %2, %3, %4}];" ::"l"((uint64_t)map), "r"(c0), "r"(c1), "r"(c2), "r"(c3) : "memory");
}
__device__ __forceinline__ void l2_prefetch_5d(const CUtensorMap* map, int c0, int c1, int c2, int c3, int c4) {
    asm volatile("cp.async.bulk.prefetch.tensor.5d.L2.global [%0, {%1, %2, %3, %4, %5}];" ::"l"((uint64_t)map), "r"(c0), "r"(c1), "r"(c2), "r"(c3), "r"(c4) : "memory");
}
__device__ __forceinline__ unsigned int ld_relaxed(const unsigned int* p) {
    unsigned int v;
    asm volatile("ld.relaxed.gpu.global.u32 %0, [%1];" : "=r"(v) : "l"(p) : "memory");
    return v;
}
__device__ __forceinline__ void fence_async_global() { asm volatile("fence.proxy.async.global;" ::: "memory"); }
__device__ __forceinline__ void wait_counter(const unsigned int* p, unsigned int target) {
    unsigned int v;
    int it = 0;
    do { asm volatile("ld.acquire.gpu.global.u32 %0, [%1];" : "=r"(v) : "l"(p) : "memory"); } while (v != target && ++it < (1 << 22));
    fence_async_global();
}
__device__ __forceinline__ void red_release(unsigned int* p, unsigned int n) {
    asm volatile("red.release.gpu.global.add.u32 [%0], %1;" ::"l"(p), "r"(n) : "memory");
}
__device__ __forceinline__ uint4 ldg128(const void* p) {
    uint4 v;
    asm volatile("ld.global.nc.v4.u32 {%0,%1,%2,%3}, [%4];" : "=r"(v.x), "=r"(v.y), "=r"(v.z), "=r"(v.w) : "l"(p));
    return v;
}
__device__ __forceinline__ void stg128(void* p, uint32_t a, uint32_t b, uint32_t c, uint32_t d) {
    asm volatile("st.global.v4.b32 [%0], {%1, %2, %3, %4};" ::"l"(p), "r"(a), "r"(b), "r"(c), "r"(d) : "memory");
}

template <int TA>
__device__ __forceinline__ void wgmma_n128(float (&d)[64], uint32_t alo, uint32_t blo, int acc) {
    asm volatile(
        "{\n.reg .pred p;\n.reg .b64 da, db;\nsetp.ne.b32 p, %67, 0;\nmov.b64 da, {%64, %69};\nmov.b64 db, {%65, %66};\n"
        "wgmma.mma_async.sync.aligned.m64n128k16.f32.bf16.bf16 "
        "{%0, %1, %2, %3, %4, %5, %6, %7, %8, %9, %10, %11, %12, %13, %14, %15, "
        "%16, %17, %18, %19, %20, %21, %22, %23, %24, %25, %26, %27, %28, %29, %30, %31, "
        "%32, %33, %34, %35, %36, %37, %38, %39, %40, %41, %42, %43, %44, %45, %46, %47, "
        "%48, %49, %50, %51, %52, %53, %54, %55, %56, %57, %58, %59, %60, %61, %62, %63}, "
        "da, db, p, 1, 1, %68, 0;\n"
        "}\n"
        : R8(d, 0), R8(d, 8), R8(d, 16), R8(d, 24), R8(d, 32), R8(d, 40), R8(d, 48), R8(d, 56)
        : "r"(alo), "r"(blo), "n"(HI128), "r"(acc), "n"(TA), "n"(TA ? HI64 : HI128));
}

constexpr int NST = 6;
constexpr int XTRA = SKEW1 - 4;
static_assert(SKEW1 >= 4 && SKEW1 <= 12, "skew");
constexpr int OFF_BB = 4 * 32768;
constexpr int OFF_CT = 5 * 32768;
constexpr int OFF_CU = OFF_CT + 32768;
__host__ __device__ constexpr uint32_t conv_buf(int p) { return OFF_CT + 16384 + (p == 3 ? 0 : p) * 16384; }
constexpr int OFF_PAR = OFF_CU + 32768;
constexpr int OFF_BAR = OFF_PAR + 2048;
constexpr int SMEM_BYTES = OFF_BAR + 896;
static_assert(SMEM_BYTES <= 232448, "smem layout");

struct Ring { unsigned long long w[2]; };
constexpr Ring make_ring() {
    Ring r{};
    int st = 0, uses[NST] = {};
    for (int kb = 0; kb < 32; ++kb) {
        r.w[kb >> 4] |= (unsigned long long)(st | (uses[st]++ & 1) << 3) << (4 * (kb & 15));
        if (++st >= (kb + 1 < SLOT4 ? 4 : kb + 1 < SLOT5 ? 5 : 6)) st = 0;
    }
    return r;
}
constexpr unsigned long long RING0 = make_ring().w[0], RING1 = make_ring().w[1];
__host__ __device__ constexpr uint32_t ring_code(int kb) { return (uint32_t)((kb < 16 ? RING0 : RING1) >> (4 * (kb & 15))) & 15u; }
__host__ __device__ constexpr int ring_slot(int kb) { return ring_code(kb) & 7; }
__host__ __device__ constexpr uint32_t ring_par(int kb) { return ring_code(kb) >> 3; }
constexpr int OFF_O1 = SLOT5 < 32 ? ring_slot(SKEW2 == 6 ? 26 : 31 - SKEW2) * 32768 : OFF_CT;

struct Maps {
    CUtensorMap x5, b4, cre, cim, sk, yt, yt3, out, kvst, bre, bim;
};

__device__ __forceinline__ void cmul(float& r, float& i, float ar, float ai, float br, float bi) {
    const float a = ar * br - ai * bi, b = ar * bi + ai * br;
    r = a; i = b;
}
__device__ __forceinline__ void csqr(float& r, float& i) { const float a = r * r - i * i, b = 2.f * r * i; r = a; i = b; }
__device__ __forceinline__ float after(float v, float dep) { return __float_as_uint(dep) == 0x7fedcba9u ? dep : v; }

template <int BMODE>
__global__ void __launch_bounds__(512, 1)
fused_kernel(const __nv_bfloat16* __restrict__ x, const __nv_bfloat16* __restrict__ b_re, const __nv_bfloat16* __restrict__ b_im,
             const __nv_bfloat16* __restrict__ kin, const __nv_bfloat16* __restrict__ vin, const __nv_bfloat16* __restrict__ ssm_k,
             const __nv_bfloat16* __restrict__ shift_k, const __nv_bfloat16* __restrict__ ssm_D,
             const __nv_bfloat16* __restrict__ lam_re, const __nv_bfloat16* __restrict__ lam_im,
             const __nv_bfloat16* __restrict__ log_dt, const __nv_bfloat16* __restrict__ gate_w,
             const __nv_bfloat16* __restrict__ dskip,
             const __nv_bfloat16* __restrict__ c_re, const __nv_bfloat16* __restrict__ c_im,
             const __grid_constant__ Maps maps) {
    constexpr bool MERGED = BMODE != 0, SW = BMODE == 2;
    extern __shared__ __align__(1024) unsigned char smem_raw[];
    const uint32_t sbase = smem_u32(smem_raw);
    const uint32_t bar_full = sbase + OFF_BAR;
    const uint32_t bar_empty = bar_full + 32;
    const uint32_t bar_full2 = bar_empty + 32;
    const uint32_t bar_empty2 = bar_full2 + 48;
    const uint32_t bar_k = bar_empty2 + 48;
    const uint32_t bar_tab = bar_k + 32;
    const uint32_t bar_ab = bar_tab + 8;
    const uint32_t bar_adone = bar_ab + 8;
    const uint32_t bar_par = bar_adone + 8;
    const uint32_t bar_y = bar_par + 8;
    const uint32_t bar_rel = bar_y + 8;
    const uint32_t bar_kvrel = bar_rel + 8;
    const uint32_t bar_yrel = bar_kvrel + 8;
    const uint32_t bar_y1 = bar_yrel + 8;
    const uint32_t bar_fh = bar_y1 + 8;
    const uint32_t bar_o1 = bar_fh + 8;
    const uint32_t bar_tick = bar_o1 + 8;
    const uint32_t bar_stg = bar_tick + 104;
    const uint32_t bar_bias = bar_stg + 112;
    const uint32_t bar_hw = bar_bias + 16;
    const uint32_t bar_gate = bar_hw + 8;
    const uint32_t bar_g2 = bar_gate + 8;
    const uint32_t w_bid = bar_full + 600, w_dsk = bar_full + 608, w_ones = bar_full + 640;
    const int tid = threadIdx.x ^ (((threadIdx.x + 128) & 256) ? 0 : 384);
    if (tid == 384) { prefetch_map(&maps.x5); prefetch_map(&maps.b4); }
    if (EPF && (threadIdx.x >> 5) - 1u < EPF && blockIdx.x < 128) {
        const int ln = threadIdx.x & 31;
        const __nv_bfloat16* p = ln < 16 ? x + (size_t)(blockIdx.x * 16 + ln) * D_DIM : ((ln & 8) ? b_im : b_re) + (size_t)(blockIdx.x * 8 + (ln & 7)) * D_DIM;
        asm volatile("prefetch.global.L2 [%0];" ::"l"(p + ((threadIdx.x >> 5) - 1) * 64) : "memory");
    }
    int bid;
    {
        unsigned int sm, nsm;
        asm volatile("mov.u32 %0, %smid;" : "=r"(sm));
        asm volatile("mov.u32 %0, %nsmid;" : "=r"(nsm));
        const int tpc = sm >> 1, q7 = ((tpc - 32) * 37) >> 8;
        const int gp = tpc < 32 ? tpc & 7 : tpc < 60 ? tpc - 31 - 7 * q7 : 0;
        const int ix = tpc < 32 ? tpc >> 3 : tpc < 60 ? q7 + 4 : ALTMAP ? (tpc - 56) ^ 2 : tpc - 58;
        bid = (ALTMAP ? tpc >= 64 : (tpc | 1) == 61) ? 128 : (4 * (gp >> 1) + (ix >> 1)) * 8 + 4 * (gp & 1) + 2 * (ix & 1) + (sm & 1);
        if (gridDim.x != 132 || nsm != 132) bid = blockIdx.x;
    }
    const int tt = bid >> 3, dt = bid & 7;
    const int ti = tt >> 1;
    const int cg = (dt >> 2) * 8 + (tt & 1) * 4 + (dt & 3);
    if (MERGED && threadIdx.x == 0 && bid < 128) {
        mbar_init(bar_full, 1);
        asm volatile("fence.mbarrier_init.release.cluster;" ::: "memory");
        mbar_expect_tx(bar_full, 49152);
        tma_load_4d(sbase + OFF_CU, &maps.b4, bar_full, 0, 0, 0, cg * 4);
        tma_load_5d(sbase + ((0 - XTRA) & 3) * 32768, &maps.x5, bar_full, 0, 0, 0, 0, ti);
        tma_load_4d(sbase + OFF_BB, &maps.b4, bar_full, 0, 0, 0, 64 + cg * 4);
    }
    __syncwarp();
    const int warp = __shfl_sync(0xffffffffu, tid >> 5, 0), wg = warp >> 2, lane = tid & 31;
    if (warp == 12 && bid < 128) {
        if (lane == 0) {
#pragma unroll
            for (int s = MERGED; s < 4; ++s) mbar_init(bar_full + 8 * s, 1);
            asm volatile("fence.mbarrier_init.release.cluster;" ::: "memory");
        }
        __syncwarp();
        asm volatile("bar.arrive 4, 512;" ::: "memory");
        if (MERGED) {
#pragma unroll 1
            for (int it = 1; it < 4; ++it) {
                e_expect_tx(bar_full + 8 * it, 49152);
                e_load_4d(sbase + OFF_CU + it * 8192, &maps.b4, bar_full + 8 * it, it * 64, 0, 0, cg * 4);
                e_load_5d(sbase + ((it - XTRA) & 3) * 32768, &maps.x5, bar_full + 8 * it, it * 64, 0, 0, 0, ti);
                e_load_4d(sbase + OFF_BB + it * 8192, &maps.b4, bar_full + 8 * it, it * 64, 0, 0, 64 + cg * 4);
            }
        }
    }
    if (bid >= 128) {
        if (tid == 0) {
            __nanosleep(2000);
            const unsigned int target = (ld_relaxed(&g_cnt[32 * 32]) & ~63u) + 64u;
            for (int i = 0; i < 8; ++i)
                for (int it = 0; ld_relaxed(&g_cnt[(40 + i) * 32]) != target && it < (1 << 12); ++it) __nanosleep(500);
        }
        return;
    }
    if (wg == 0) {
        asm volatile("setmaxnreg.dec.sync.aligned.u32 %0;" ::"n"(REG_P));
        if (tid == 32) {
            if (sbase & 1023) __trap();
#pragma unroll
            for (int s = 0; s < 4; ++s) mbar_init(bar_empty + 8 * s, 2);
#pragma unroll
            for (int s = 0; s < NST; ++s) { mbar_init(bar_full2 + 8 * s, 1); mbar_init(bar_empty2 + 8 * s, 1); }
            mbar_init(bar_k, 1); mbar_init(bar_k + 8, 1); mbar_init(bar_k + 16, 1); mbar_init(bar_k + 24, 1);
            mbar_init(bar_tab, 1);
            mbar_init(bar_ab, 1);
            mbar_init(bar_adone, 4);
            mbar_init(bar_par, 2);
            asm volatile("fence.mbarrier_init.release.cluster;" ::: "memory");
        } else if (tid == 64) {
#pragma unroll
            for (int s = 0; s < 20; ++s) mbar_init(bar_y + 8 * s, 1);
        } else if (tid == 96) {
#pragma unroll
            for (int s = 0; s < 11; ++s) mbar_init(bar_stg + 8 * s, 4);
        } else if (tid == 0) {
#pragma unroll
            for (int s = 11; s < 19; ++s) mbar_init(bar_stg + 8 * s, 4);
            asm volatile("st.shared.b32 [%0], %1;" ::"r"(w_bid), "r"(bid) : "memory");
        }
        __syncwarp();
        asm volatile("bar.sync 4, 512;" ::: "memory");
        if (warp == 0) {
#pragma unroll 1
            for (int it = MERGED ? 4 : 0; it < 16 + XTRA; ++it) {
                const int st = it & 3, kb = it < 16 ? it : it - SKEW1;
                const bool fa = it < 16, fb = it < 16 - SKEW1 || it >= 12;
                const uint32_t bf = bar_full + 8 * st;
                mbar_wait(bar_empty + 8 * st, ((it >> 2) & 1) ^ 1);
                e_expect_tx(bf, fa && fb ? 49152 : 40960);
                e_load_5d(sbase + ((it - XTRA) & 3) * 32768, &maps.x5, bf, kb * 64, 0, 0, 0, ti);
                if (MERGED) {
                    if (fa) e_load_4d(sbase + OFF_CU + st * 8192, &maps.b4, bf, kb * 64, 0, 0, cg * 4);
                    if (fb) e_load_4d(sbase + OFF_BB + st * 8192, &maps.b4, bf, kb * 64, 0, 0, 64 + cg * 4);
                } else {
                    if (lane < 16 && ((lane & 8) ? fb : fa))
                        tma_load_2d(sbase + ((lane & 8) ? OFF_BB : OFF_CU) + st * 8192 + (lane & 7) * 1024, (lane & 1) ? &maps.bim : &maps.bre, bf,
                                    kb * 64, (lane >> 3) * 512 + cg * 32 + ((lane & 7) >> 1) * 8);
                    __syncwarp();
                }
                if (it >= 4 && it < 16) e_arrive(bar_tick + 8 * (it - 3));
                if (lane == 0) STAMP(1, 16 + it);
                if (lane == 0 && it < 16) SAMPLE(it - 3);
            }
#pragma unroll 1
            for (int kb = 0; kb < 32; ++kb) {
                const int st = ring_slot(kb);
                const uint32_t bf = bar_full2 + 8 * st;
                mbar_wait(bar_empty2 + 8 * st, ring_par(kb));
                e_expect_tx(bf, 32768);
                e_load_5d(sbase + st * 32768 + 16384, &maps.cre + ((kb >> 3) & 1), bf, ((kb >> 4) * 8 + (kb & 7)) * 64, 0, 0, 0, dt * 4);
                if (lane == 0) STAMP(2, 16 + kb);
                if (lane == 0 && (kb & 3) == 0) SAMPLE(13 + (kb >> 2));
            }
        } else if (warp == 1) {
            if (MERGED && PFD && lane == 0) {
#pragma unroll 1
                for (int n = 0; n + PFD < 16; ++n) {
                    mbar_wait(bar_tick + 8 * n, 0);
                    if (cg >= 4 && max(cg - PFD, 0) == n) l2_prefetch_5d(&maps.x5, cg * 64, 0, 0, 0, ti);
                    if (ti >= 2 && max(2 * ti - PFD, 0) == n) {
#pragma unroll 1
                        for (int i = 0; i < 4; ++i) l2_prefetch_4d(&maps.b4, (2 * ti + (i >> 1)) * 64, 0, 0, (i & 1) * 64 + cg * 4);
                    }
                }
            }
            __syncwarp();
            const char* hp = reinterpret_cast<const char*>(g_H) + (size_t)tt * 262144;
            mbar_wait(bar_adone, 0);
            e_expect_tx(bar_k + 8, 16384);
            e_expect_tx(bar_k + 16, 16384);
#pragma unroll 1
            for (int c = 2; c < 6; ++c) {
                e_load_4d(sbase + conv_buf(0) + (c >> 1) * 16384 + (c & 1) * 4096 + 8192, &maps.sk, bar_k + 8 * (c >> 1), 0, 0, 0, bid * 8 + c);
                if (GAP_CV) __nanosleep(GAP_CV);
            }
            mbar_wait(bar_kvrel, 0);
            const unsigned int target = lds32(w_bid + 4);
            mbar_wait(bar_rel, 0);
#pragma unroll 1
            for (int q = 0; q < 2; ++q) {
                if (lane == 0) STAMP(0, 8 + 4 * q);
                if (q == 0) wait_counter(&g_cnt[(2 * ti) * 32], target);
                else { mbar_wait(bar_fh, 0); fence_async_global(); }
                if (lane == 0) STAMP(0, 9 + 4 * q);
#pragma unroll 1
                for (int kb = 0; kb < 16; ++kb) {
                    const int st = ring_slot(16 * q + kb);
                    mbar_wait(bar_empty2 + 8 * st, ring_par(16 * q + kb));
                    e_bulk_load(sbase + st * 32768, hp + kb * 16384, 16384, bar_full2 + 8 * st);
                }
                hp += 4194304;
            }
        } else if (warp == 2) {
            if (lane == 0) {
                mbar_wait(bar_tick + 8, 0);
                const unsigned int target = (ld_relaxed(&g_cnt[(40 + dt) * 32]) & ~63u) + 64u;
                asm volatile("st.shared.b32 [%0], %1;" ::"r"(w_bid + 4), "r"(target) : "memory");
                prefetch_map(&maps.kvst); prefetch_map(&maps.sk);
#pragma unroll 1
                for (int bt = 0; bt < 2; ++bt) {
                    mbar_wait(bar_stg + 8 * bt, 0);
#pragma unroll 1
                    for (int i = 0; i < 4; ++i) {
                        if (i) __nanosleep(GAP_ST);
                        tma_store_3d(&maps.kvst, sbase + OFF_CT + bt * 16384 + i * 4096, (tt & 1) * 1024 + ti * 128 + 64 * bt, dt * 16, 2 * i);
                    }
                    bulk_commit();
                }
                bulk_wait0();
                fence_async_global();
                red_release(&g_cnt[(40 + dt) * 32], 4);
                mbar_arrive(bar_kvrel);
                STAMP(0, 23);
                mbar_expect_tx(bar_tab, 12288);
                bulk_load(sbase + OFF_CT, &g_conv_tab, 12288, bar_tab);
                mbar_expect_tx(bar_k, 16384);
                tma_load_4d(sbase + conv_buf(0) + 8192, &maps.sk, bar_k, 0, 0, 0, bid * 8);
                tma_load_4d(sbase + conv_buf(0) + 12288, &maps.sk, bar_k, 0, 0, 0, bid * 8 + 1);
                wait_counter(&g_cnt[(40 + (bid >> 4)) * 32], target);
                STAMP(0, 19);
#pragma unroll 1
                for (int p = 0; p < 3; ++p) {
                    if (p == 1) mbar_wait(bar_adone, 0);
                    bulk_load(sbase + conv_buf(p), g_kvT + (size_t)(bid * 8 + 2 * p) * 2048, 8192, bar_k + 8 * p);
                    if (GAP_CV) __nanosleep(GAP_CV);
                }
                prefetch_map(&maps.out); prefetch_map(&maps.yt); prefetch_map(&maps.yt3);
#pragma unroll 1
                for (int p = 0; p < 4; ++p) {
                    mbar_wait(bar_stg + 16 + 8 * p, 0);
                    if (p == 0) {
                        mbar_expect_tx(bar_k + 24, 16384);
                        tma_load_4d(sbase + conv_buf(3) + 8192, &maps.sk, bar_k + 24, 0, 0, 0, bid * 8 + 6);
                        mbar_wait(bar_g2, 0);
                        tma_load_4d(sbase + conv_buf(3) + 12288, &maps.sk, bar_k + 24, 0, 0, 0, bid * 8 + 7);
                    }
#pragma unroll 1
                    for (int i = 0; i < 2; ++i) {
                        if (i) __nanosleep(GAP_Y);
                        asm volatile("cp.async.bulk.global.shared::cta.bulk_group [%0], [%1], 4096;"
                                     ::"l"(g_y2 + (size_t)(bid * 8 + 2 * p + i) * 2048), "r"(sbase + conv_buf(p) + i * 4096) : "memory");
                    }
                    bulk_commit();
                    STAMP(0, 24 + p);
                    if (p == 0) {
                        bulk_wait_read0();
                        bulk_load(sbase + conv_buf(3), g_kvT + (size_t)(bid * 8 + 6) * 2048, 8192, bar_k + 24);
                    }
                    if (p == 2) {
                        bulk_wait0();
                        fence_async_global();
                        red_release(&g_cnt[(48 + (bid >> 4)) * 32], 4);
                        mbar_arrive(bar_yrel);
                        STAMP(0, 3);
                    }
                }
                bulk_wait0();
                mbar_arrive(bar_empty2 + 40);
                fence_async_global();
                red_release(&g_cnt[(32 + (bid >> 4)) * 32], 4);
                STAMP(0, 2);
                wait_counter(&g_cnt[(32 + dt) * 32], target);
                STAMP(0, 5);
                mbar_expect_tx(bar_y, 8192);
#pragma unroll 1
                for (int i = 6; i < 8; ++i)
                    tma_load_5d(sbase + OFF_CU + i * 4096, &maps.yt, bar_y, (tt & 1) * 1024 + ti * 128 + (i & 1) * 64, 0, 0, i >> 1, dt * 4);
#pragma unroll 1
                for (int i = 0; i < 8; ++i) {
                    mbar_wait(bar_stg + 48 + 8 * i, 0);
                    tma_store_5d(&maps.out, sbase + ((i & 4) ? OFF_O1 : OFF_CU) + (i & 3) * 8192, dt * 128 + (i & 3) * 32, 0, 0, (tt & 1) * 4 + ((i & 4) >> 1), ti);
                    bulk_commit();
                }
                bulk_wait_read0();
                STAMP(2, 3);
                SAMPLE(21);
            }
        } else if (lane == 0) {
            mbar_wait(bar_tick + 8 * TK_PF0, 0);
#pragma unroll 1
            for (int i = 0; i < 8; ++i) {
                l2_prefetch(((i & 1) ? vin : kin) + (size_t)(ti * 256 + 32 * (i & 4) + (bid & 15) * 8 + 2 * (i & 2)) * D_DIM, 8192);
                __nanosleep(GAP_PF);
            }
            if (bid < 3) l2_prefetch(reinterpret_cast<const char*>(&g_conv_tab) + bid * 4096, 4096);
            prefetch_map(&maps.cre); prefetch_map(&maps.cim);
            mbar_wait(bar_tick + 8 * TK_C, 0);
#pragma unroll 1
            for (int i = 0; i < 8; ++i) {
                l2_prefetch((i & 1) ? ((i & 4) ? c_im : c_re) + (size_t)bid * 8192 + (i & 2) * 2048 : ssm_k + (size_t)bid * 16384 + (i >> 1) * 4096, 8192);
                __nanosleep(GAP_PF);
            }
            const unsigned int target = (ld_relaxed(&g_cnt[(2 * ti + 1) * 32]) & ~63u) + 64u;
            mbar_wait(bar_gate, 0);
            mbar_wait(bar_hw, 0);
            mbar_wait(bar_g2, 0);
            char* hp = reinterpret_cast<char*>(g_H) + (size_t)((16 + 2 * ti) * 16 + (cg >> 1)) * 16384 + (cg & 1) * 2048;
#pragma unroll 1
            for (int i = 0; i < 16; ++i) {
                asm volatile("cp.async.bulk.global.shared::cta.bulk_group [%0], [%1], 2048;"
                             ::"l"(hp + (i & 3) * 4096 + ((i >> 2) & 1) * 262144 + (i >> 3) * 131072), "r"(sbase + OFF_BB + i * 2048) : "memory");
                __nanosleep(GAP_HB);
            }
            bulk_commit();
            bulk_wait0();
            mbar_arrive(bar_empty2 + 32);
            fence_async_global();
            red_release(&g_cnt[(2 * ti + 1) * 32], 4);
            STAMP(0, 38);
            wait_counter(&g_cnt[(2 * ti + 1) * 32], target);
            mbar_arrive(bar_fh);
        }
    } else {
    if (wg == 3) {
        if (warp != 12) asm volatile("bar.sync 4, 512;" ::: "memory");
        named_bar(3, 128);
        asm volatile("setmaxnreg.inc.sync.aligned.u32 %0;" ::"n"(REG_C));
        const int t = tid & 127, w4 = t >> 5;
        if (t == 0) SAMPLE(0);
        mbar_wait(bar_tick, 0);
        if (t < 64) {
            const int ch = (t >> 5) * 512 + cg * 32 + (t & 31);
            unsigned long long oldagg;
            asm volatile("ld.relaxed.gpu.global.u64 %0, [%1];" : "=l"(oldagg) : "l"(&g_agg[ti * D_DIM + ch]) : "memory");
            const float Lr = __bfloat162float(lam_re[ch]), Li = __bfloat162float(lam_im[ch]);
            const float dtv = bf16r(expf(__bfloat162float(log_dt[ch])));
            const unsigned int tag = ((((unsigned int)oldagg & 1u) | ((unsigned int)(oldagg >> 31) & 2u)) + 1u) & 3u;
            const float er = expf(dtv * Lr);
            float s, c;
            sincospif(dtv * Li * 0.318309886183790672f, &s, &c);
            const float lr = er * c, li = er * s;
            const float nr = lr - 1.f, ni = li;
            const float den = Lr * Lr + Li * Li;
            const float cr = 2.f * (nr * Lr + ni * Li) / den, ci = 2.f * (ni * Lr - nr * Li) / den;
            float pr = lr, pi = -li;
#pragma unroll
            for (int i = 0; i < 5; ++i) csqr(pr, pi);
            sts128(sbase + OFF_PAR + t * 32, __float_as_uint(lr), __float_as_uint(-li), __float_as_uint(cr), __float_as_uint(ci));
            sts128(sbase + OFF_PAR + t * 32 + 16, __float_as_uint(pr), __float_as_uint(pi), tag, 0);
            __syncwarp();
            if (lane == 0) mbar_arrive(bar_par);
        }
        if (t >= 120) asm volatile("st.shared.b32 [%0], %1;" ::"r"(w_dsk - 480 + 4 * t),
                                   "r"(t < 124 ? __ldg(reinterpret_cast<const uint32_t*>(ssm_D + bid * 8) + (t & 3)) : 0u) : "memory");
        if (t < 64) asm volatile("st.shared.b32 [%0], %1;" ::"r"(w_ones + 4 * t), "r"(0x3F803F80u) : "memory");
        {
            const int cq = lane & 15, rg = (lane >> 4) + 2 * w4;
            uint32_t sk[4][4];
#pragma unroll
            for (int c = 0; c < 4; ++c) {
                const uint4 w = ldg128(shift_k + (size_t)(dt * 128 + 8 * cq + 2 * c) * 4);
                sk[0][c] = __byte_perm(w.x, w.z, 0x5410); sk[1][c] = __byte_perm(w.x, w.z, 0x7632);
                sk[2][c] = __byte_perm(w.y, w.w, 0x5410); sk[3][c] = __byte_perm(w.y, w.w, 0x7632);
            }
#pragma unroll 1
            for (int bt = 0; bt < 2; ++bt) {
                const int t0 = ti * 256 + 128 * bt + 16 * (rg & 4) + 32 * (tt & 1) + 8 * (rg & 3);
                mbar_wait(bar_tick + 8 * (bt ? TK_KV1 : TK_KV0), 0);
                if (t == 0) STAMP(0, 30 + 3 * bt);
                uint4 kk[11], vv[8];
                const __nv_bfloat16* kp = kin + (size_t)t0 * D_DIM + dt * 128 + 8 * cq;
                const __nv_bfloat16* vp = vin + (size_t)t0 * D_DIM + dt * 128 + 8 * cq;
#pragma unroll
                for (int i = 0; i < 11; ++i) {
                    if (i < 3 && t0 == 0) kk[i] = make_uint4(0, 0, 0, 0);
                    else kk[i] = ldg128(kp + (i - 3) * D_DIM);
                    if (i == 6 || i == 10) __nanosleep(GAP_KV);
                }
#pragma unroll
                for (int i = 0; i < 8; ++i) { vv[i] = ldg128(vp + i * D_DIM); if (i == 3) __nanosleep(GAP_KV); }
                const uint32_t ua = sbase + OFF_CT + bt * 16384 + cq * 128 + ((rg ^ ((2 * ti + bt) & 3) ^ (cq & 7)) << 4);
#pragma unroll
                for (int c = 0; c < 4; ++c) {
                    uint32_t res[8];
#pragma unroll
                    for (int i = 0; i < 8; ++i) {
                        uint32_t ks = hmul((&kk[i].x)[c], sk[3][c]);
                        ks = hadd(ks, hmul((&kk[i + 1].x)[c], sk[2][c]));
                        ks = hadd(ks, hmul((&kk[i + 2].x)[c], sk[1][c]));
                        ks = hadd(ks, hmul((&kk[i + 3].x)[c], sk[0][c]));
                        res[i] = hmul(ks, (&vv[i].x)[c]);
                    }
                    sts128(ua + (2 * c) * 2048, __byte_perm(res[0], res[1], 0x5410), __byte_perm(res[2], res[3], 0x5410),
                           __byte_perm(res[4], res[5], 0x5410), __byte_perm(res[6], res[7], 0x5410));
                    sts128(ua + (2 * c + 1) * 2048, __byte_perm(res[0], res[1], 0x7632), __byte_perm(res[2], res[3], 0x7632),
                           __byte_perm(res[4], res[5], 0x7632), __byte_perm(res[6], res[7], 0x7632));
                }
                fence_async_smem();
                __syncwarp();
                if (lane == 0) mbar_arrive(bar_stg + 8 * bt);
                if (t == 0) STAMP(0, 21 + bt);
            }
        }
        {
            const int row = bid * 16 + (t >> 3);
            uint4 xv[16];
#pragma unroll
            for (int n = 0; n < 16; ++n) {
                xv[n] = ldg128(x + (size_t)row * D_DIM + ((t & 7) + 8 * n) * 8);
                if ((n & 3) == 3) __nanosleep(GAP_KV);
            }
#pragma unroll
            for (int n8 = 0; n8 < 16; n8 += 8) {
                uint4 wv[8];
#pragma unroll
                for (int n = 0; n < 8; ++n) wv[n] = ldg128(gate_w + ((t & 7) + 8 * (n8 + n)) * 8);
#pragma unroll
                for (int n = 0; n < 8; ++n) {
                    uint4& p = xv[n8 + n];
                    p.x = hmul(p.x, wv[n].x); p.y = hmul(p.y, wv[n].y); p.z = hmul(p.z, wv[n].z); p.w = hmul(p.w, wv[n].w);
                }
            }
            float d[4] = {0.f, 0.f, 0.f, 0.f};
            fence_regs(d);
            named_bar(3, 128);
            wgmma_fence();
#pragma unroll
            for (int n = 0; n < 16; ++n)
                asm volatile("{\n.reg .b64 db;\nmov.b64 db, {%8, 8};\n"
                             "wgmma.mma_async.sync.aligned.m64n8k16.f32.bf16.bf16 {%0, %1, %2, %3}, {%4, %5, %6, %7}, db, 1, 1, 1, 0;\n}\n"
                             : "+f"(d[0]), "+f"(d[1]), "+f"(d[2]), "+f"(d[3]) : "r"(xv[n].x), "r"(xv[n].y), "r"(xv[n].z), "r"(xv[n].w), "r"(desc_lo(w_ones, 128)));
            wgmma_commit();
            wgmma_wait<0>();
            fence_regs(d);
#pragma unroll
            for (int n = 0; n < 16; ++n) asm volatile("" ::"r"(xv[n].x), "r"(xv[n].y), "r"(xv[n].z), "r"(xv[n].w) : "memory");
            float sum = d[0] + d[2];
            sum += __shfl_xor_sync(0xffffffffu, sum, 4);
            if ((t & 7) == 0) g_gate[row] = bf16r(1.f / (1.f + expf(-bf16r(sum))));
            if (t == 0) STAMP(0, 4);
            __syncwarp();
            if (lane == 0) mbar_arrive(bar_gate);
        }
    } else {
        asm volatile("setmaxnreg.inc.sync.aligned.u32 %0;" ::"n"(REG_AB));
        if (tid == 128) STAMP(1, 54);
        asm volatile("bar.sync 4, 512;" ::: "memory");
        if (tid == 128) STAMP(1, 55);
        const int cw = wg - 1;
        const int t = tid & 127, w4 = t >> 5, g = lane >> 2, t4 = lane & 3;
        {
            float a0[64], a1[64];
            auto release = [&](int it) {
                if (it < 12 + XTRA && t <= ((it >= 16 - SKEW1 && it < 12) || it >= 16)) mbar_arrive(bar_empty + 8 * (it & 3));
            };
#pragma unroll 1
            for (int kb = 0; kb < 16; ++kb) {
                const int it = cw == 1 && kb >= 16 - SKEW1 ? kb + XTRA : kb, st = it & 3;
                if (cw == 1 && kb == 16 - SKEW1) mbar_wait(bar_ab, 0);
                mbar_wait(bar_full + 8 * st, (it >> 2) & 1);
                if (kb == 0 && tid == 288) mbar_arrive(bar_tick);
                if (kb == 0 && t == 0) STAMP(1, 14 + cw);
                const uint32_t alo = desc_lo(sbase + (cw ? OFF_BB : OFF_CU) + st * 8192, 16), blo = desc_lo(sbase + ((it - XTRA) & 3) * 32768, 16);
                wgmma_fence();
#pragma unroll
                for (int k = 0; k < 4; ++k) {
                    wgmma_n128<0>(a0, alo + 2 * k, blo + 2 * k, k ? 1 : kb);
                    wgmma_n128<0>(a1, alo + 2 * k, blo + 1024 + 2 * k, k ? 1 : kb);
                }
                wgmma_commit();
                wgmma_wait<1>();
                if (kb > 0 && !(cw == 1 && kb == 16 - SKEW1)) release(it - 1);
                if (cw == 1 && kb == 15 - SKEW1) {
                    wgmma_wait<0>();
                    release(it);
                }
                if (cw == 1 && kb > 12) {
                    if (kb == 13) mbar_wait(bar_adone, 0);
                    if (t == 0) mbar_arrive(bar_empty2 + 8 * (kb - 13));
                }
            }
            if (tid == 192) mbar_arrive(bar_ab);
            float mr, mi, cr, ci, p32r, p32i;
            uint32_t tag;
            mbar_wait(bar_par, 0);
            {
                const uint32_t par = sbase + OFF_PAR + (cw * 32 + w4 * 8 + g) * 32;
                uint32_t dummy;
                asm volatile("ld.shared.v4.f32 {%0,%1,%2,%3}, [%4];" : "=f"(mr), "=f"(mi), "=f"(cr), "=f"(ci) : "r"(par));
                asm volatile("ld.shared.v4.b32 {%0,%1,%2,%3}, [%4];" : "=f"(p32r), "=f"(p32i), "=r"(tag), "=r"(dummy) : "r"(par + 16));
            }
            const float l1i = SW ? mi : -mi;
            auto map = [&](float p, float q, float& r, float& i) {
                if (SW) { r = fmaf(cr, q, -ci * p); i = fmaf(-cr, p, -ci * q); }
                else { r = fmaf(cr, p, -ci * q); i = fmaf(-cr, q, -ci * p); }
            };
            float p64r = p32r, p64i = p32i;
            csqr(p64r, p64i);
            float p128r = p64r, p128i = p64i;
            csqr(p128r, p128i);
            wgmma_wait<0>();
            fence_regs(a0); fence_regs(a1);
            if (cw == 0) { release(15); if (lane == 0) mbar_arrive(bar_adone); }
            else if (t == 0) mbar_arrive(bar_empty2 + 24);
            if (t == 0) STAMP(1, 2 + 6 * cw);
            float hr = 0.f, hi = 0.f, ar = 0.f, ai = 0.f;
#pragma unroll
            for (int j = 0; j < 16; ++j)
#pragma unroll
                for (int e = 0; e < 2; ++e) {
                    const float nr = fmaf(mr, ar, fmaf(-l1i, ai, a0[4 * j + e])), ni = fmaf(mr, ai, fmaf(l1i, ar, a0[4 * j + 2 + e]));
                    const float or_ = fmaf(mr, hr, fmaf(-l1i, hi, a1[4 * j + e])), oi = fmaf(mr, hi, fmaf(l1i, hr, a1[2 + 4 * j + e]));
                    ar = nr; ai = ni; hr = or_; hi = oi;
                }
            map(ar, ai, ar, ai);
            map(hr, hi, hr, hi);
            hr += p32r * ar - p32i * ai; hi += p32r * ai + p32i * ar;
            {
                float vr = __shfl_up_sync(0xffffffffu, hr, 1, 4), vi = __shfl_up_sync(0xffffffffu, hi, 1, 4);
                if (t4 >= 1) { hr += p64r * vr - p64i * vi; hi += p64r * vi + p64i * vr; }
                vr = __shfl_up_sync(0xffffffffu, hr, 2, 4); vi = __shfl_up_sync(0xffffffffu, hi, 2, 4);
                if (t4 >= 2) { hr += p128r * vr - p128i * vi; hi += p128r * vi + p128i * vr; }
            }
            unsigned long long* ap = &g_agg[ti * D_DIM + cw * 512 + cg * 32 + w4 * 8 + g];
            if (t4 == 3) asm volatile("{\n.reg .b64 a;\nmov.b64 a, {%1, %2};\nst.relaxed.gpu.global.u64 [%0], a;\n}\n" ::"l"(ap),
                                      "r"((__float_as_uint(hr) & ~1u) | (tag & 1u)), "r"((__float_as_uint(hi) & ~1u) | (tag >> 1)) : "memory");
            float exr = __shfl_up_sync(0xffffffffu, hr, 1, 4), exi = __shfl_up_sync(0xffffffffu, hi, 1, 4);
            if (t4 == 0) { exr = 0.f; exi = 0.f; }
            if (t == 0) STAMP(1, 3 + 6 * cw);
            ci = after(ci, exr);
#pragma unroll
            for (int j = 0; j < 16; ++j)
#pragma unroll
                for (int e = 0; e < 2; ++e) {
                    map(a0[4 * j + e], a0[4 * j + 2 + e], a0[4 * j + e], a0[4 * j + 2 + e]);
                    map(a1[4 * j + e], a1[4 * j + 2 + e], a1[4 * j + e], a1[4 * j + 2 + e]);
                }
            float qr = 1.f, qi = 0.f, ur = 1.f, ui = 0.f;
            if (t4 & 1) { qr = p64r; qi = p64i; }
            if (t4 & 2) cmul(qr, qi, qr, qi, p128r, p128i);
            csqr(p128r, p128i);
            if (t4 & 1) { ur = p128r; ui = p128i; }
            csqr(p128r, p128i);
            if (t4 & 2) cmul(ur, ui, ur, ui, p128r, p128i);
            csqr(p128r, p128i);
            fence_regs(a0); fence_regs(a1);
            if (t == 0) STAMP(1, 7 + 6 * cw);
            if (ti > 0) {
                const unsigned long long tmask = 0x0000000100000001ull, tval = ((unsigned long long)(tag >> 1) << 32) | (tag & 1u);
                unsigned long long u0 = tval, u1 = tval;
                ap -= D_DIM * (1 + t4);
                int it = 0;
                do {
                    asm volatile("{\n.reg .pred p, q;\nsetp.gt.s32 p, %3, 0;\nsetp.gt.s32 q, %3, 4;\n@p ld.relaxed.gpu.global.u64 %0, [%2];\n"
                                 "@q ld.relaxed.gpu.global.u64 %1, [%2+-32768];\n}\n" : "+l"(u0), "+l"(u1) : "l"(ap), "r"(ti - t4) : "memory");
                } while (__any_sync(0xffffffffu, (((u0 ^ tval) | (u1 ^ tval)) & tmask) != 0) && ++it < (1 << 22));
                float Pr = __uint_as_float((unsigned)u1 & ~1u), Pi = __uint_as_float((unsigned)(u1 >> 32) & ~1u);
                cmul(Pr, Pi, Pr, Pi, p128r, p128i);
                Pr += __uint_as_float((unsigned)u0 & ~1u); Pi += __uint_as_float((unsigned)(u0 >> 32) & ~1u);
                cmul(Pr, Pi, Pr, Pi, ur, ui);
                Pr += __shfl_xor_sync(0xffffffffu, Pr, 1); Pi += __shfl_xor_sync(0xffffffffu, Pi, 1);
                Pr += __shfl_xor_sync(0xffffffffu, Pr, 2); Pi += __shfl_xor_sync(0xffffffffu, Pi, 2);
                exr += qr * Pr - qi * Pi;
                exi += qr * Pi + qi * Pr;
            }
            if (t == 0) STAMP(1, 4 + 6 * cw);
            char* hp = reinterpret_cast<char*>(g_H) + (size_t)((2 * ti) * 16 + (cg >> 1)) * 16384 + ((cg & 1) * 32 + w4 * 8 + g) * 64 + ((t4 ^ (g >> 1)) << 4);
            float fxr = ar + p32r * exr - p32i * exi, fxi = ai + p32r * exi + p32i * exr;
            const uint32_t hs = sbase + OFF_BB + (w4 * 8 + g) * 64 + ((t4 ^ (g >> 1)) << 4);
            if (cw == 1) named_bar(2, 128);
#pragma unroll
            for (int jj = 0; jj < 4; ++jj) {
                uint32_t pr[4], qq[4], pi[4], qi[4];
#pragma unroll
                for (int j4 = 0; j4 < 4; ++j4) {
                    const int j = jj * 4 + j4;
                    const float r0 = fmaf(mr, exr, fmaf(-mi, exi, a0[4 * j])), i0 = fmaf(mr, exi, fmaf(mi, exr, a0[4 * j + 2]));
                    const float r1 = fmaf(mr, fxr, fmaf(-mi, fxi, a1[4 * j])), i1 = fmaf(mr, fxi, fmaf(mi, fxr, a1[2 + 4 * j]));
                    exr = fmaf(mr, r0, fmaf(-mi, i0, a0[4 * j + 1]));
                    exi = fmaf(mr, i0, fmaf(mi, r0, a0[4 * j + 3]));
                    fxr = fmaf(mr, r1, fmaf(-mi, i1, a1[1 + 4 * j]));
                    fxi = fmaf(mr, i1, fmaf(mi, r1, a1[3 + 4 * j]));
                    pr[j4] = pack_bf16(r0, exr); pi[j4] = pack_bf16(i0, exi);
                    qq[j4] = pack_bf16(r1, fxr); qi[j4] = pack_bf16(i1, fxi);
                }
                if (cw == 0) {
                    stg128(hp + jj * 4096, pr[0], pr[1], pr[2], pr[3]);
                    stg128(hp + jj * 4096 + 262144, qq[0], qq[1], qq[2], qq[3]);
                    stg128(hp + jj * 4096 + 131072, pi[0], pi[1], pi[2], pi[3]);
                    stg128(hp + jj * 4096 + 393216, qi[0], qi[1], qi[2], qi[3]);
                } else {
                    sts128(hs + jj * 2048, pr[0], pr[1], pr[2], pr[3]);
                    sts128(hs + jj * 2048 + 8192, qq[0], qq[1], qq[2], qq[3]);
                    sts128(hs + jj * 2048 + 16384, pi[0], pi[1], pi[2], pi[3]);
                    sts128(hs + jj * 2048 + 24576, qi[0], qi[1], qi[2], qi[3]);
                }
            }
            if (t == 0) STAMP(1, 5 + 6 * cw);
            if (cw == 0) {
                named_bar(1, 128);
                if (t == 0) { red_release(&g_cnt[(2 * ti) * 32], 4); mbar_arrive(bar_rel); }
                if (t == 0) STAMP(1, 6);
                __syncwarp();
            } else {
                fence_async_smem();
                __syncwarp();
                if (lane == 0) mbar_arrive(bar_hw);
            }
            if (t == 0) STAMP(1, 50 + cw);
        }
        if (cw == 0) {
            float c0[64], c1[64];
            int pst = 0;
            auto kblock = [&](int kb, auto shallow) {
                const int t = fresh_tid() & 127, lane = t & 31;
                const int st = ring_slot(kb);
                mbar_wait(bar_full2 + 8 * st, ring_par(kb));
                if (kb == 0 && t == 0) STAMP(2, 6);
                if (kb == 0 && lane == 0) mbar_arrive(bar_g2);
                const uint32_t alo = desc_lo(sbase + st * 32768, 4096), blo = desc_lo(sbase + st * 32768 + 16384, 16);
                constexpr int Q = decltype(shallow)::value;
#pragma unroll
                for (int j = 0; j < 8; ++j) {
                    wgmma_fence();
                    if (j & 1) wgmma_n128<1>(c1, alo + 512 + 64 * (j >> 1), blo + 2 * (j >> 1), j >> 1 ? 1 : kb);
                    else wgmma_n128<1>(c0, alo + 64 * (j >> 1), blo + 2 * (j >> 1), j >> 1 ? 1 : kb);
                    wgmma_commit();
                    wgmma_wait<Q>();
                    if (j == Q - 1 && kb > 0 && t == 0) mbar_arrive(bar_empty2 + 8 * pst);
                }
                pst = st;
            };
#pragma unroll 1
            for (int kb = 0; kb < QKB; ++kb) kblock(kb, std::integral_constant<int, QD>());
#pragma unroll 1
            for (int kb = QKB; kb < 32 - SKEW2; ++kb) kblock(kb, std::integral_constant<int, QD2>());
            static_assert(SKEW2 <= (SLOT5 < 32 ? 6 : 4), "slot release");
            const uint32_t alo = desc_lo(sbase, 4096), blo = desc_lo(sbase + 16384, 16);
#pragma unroll
            for (int kb = 32 - SKEW2; kb < 32; ++kb) {
                mbar_wait(bar_full2 + 8 * ring_slot(kb), ring_par(kb));
                wgmma_fence();
#pragma unroll
                for (int k = 0; k < 4; ++k) wgmma_n128<1>(c0, alo + ring_slot(kb) * 2048 + 64 * k, blo + ring_slot(kb) * 2048 + 2 * k, 1);
                wgmma_commit();
                if (SLOT5 < 32 && SKEW2 < 6 && kb == 33 - SKEW2) {
                    wgmma_wait<2>();
                    if ((fresh_tid() & 127) == 0) mbar_arrive(bar_o1);
                }
                if (SKEW2 == 6 && kb == 26) {
                    wgmma_wait<1>();
                    if ((fresh_tid() & 127) == 0) mbar_arrive(bar_empty2 + 8 * ring_slot(25));
                }
            }
            auto late = [&](int kb) {
                wgmma_fence();
#pragma unroll
                for (int k = 0; k < 4; ++k) wgmma_n128<1>(c1, alo + 512 + ring_slot(kb) * 2048 + 64 * k, blo + ring_slot(kb) * 2048 + 2 * k, 1);
                wgmma_commit();
            };
            late(32 - SKEW2);
            const int t = fresh_tid() & 127, lane = t & 31, w4 = t >> 5, g = lane >> 2, t4 = lane & 3;
            auto epilogue = [&](const float (&a)[64], int b) {
                const uint32_t ad0 = sbase + (b ? OFF_O1 : OFF_CU) + (w4 * 16 + g) * 128 + (((2 * t4) ^ g) << 4);
                float gt[2];
                uint32_t bv[4][4];
#pragma unroll
                for (int h = 0; h < 2; ++h) gt[h] = __uint_as_float(lds32(sbase + OFF_PAR + (64 * b + 16 * w4 + 8 * h + g) * 4));
#pragma unroll
                for (int i = 0; i < 4; ++i)
                    asm volatile("ld.shared.v4.b32 {%0,%1,%2,%3}, [%4];" : "=r"(bv[i][0]), "=r"(bv[i][1]), "=r"(bv[i][2]), "=r"(bv[i][3])
                                 : "r"(ad0 + (i & 1) * 1024 + (i >> 1) * 8192) : "memory");
                if (b == 0) wgmma_wait<1>(); else wgmma_wait<0>();
                if (b == 0) fence_regs(c0); else fence_regs(c1);
                if (t == 0) STAMP(2, b ? 2 : 5);
#pragma unroll
                for (int jq = 0; jq < 4; ++jq) {
#pragma unroll
                    for (int h = 0; h < 2; ++h) {
                        const uint32_t ad = ad0 + h * 1024 + jq * 8192;
                        uint32_t (&w)[4] = bv[2 * (jq & 1) + h];
                        const int r = 16 * jq + 2 * h;
                        sts128(ad, __float_as_uint(fmaf(gt[h], a[r], bf_lo(w[0]))), __float_as_uint(fmaf(gt[h], a[r + 1], bf_hi(w[0]))),
                               __float_as_uint(fmaf(gt[h], a[r + 4], bf_lo(w[1]))), __float_as_uint(fmaf(gt[h], a[r + 5], bf_hi(w[1]))));
                        sts128(ad ^ 16, __float_as_uint(fmaf(gt[h], a[r + 8], bf_lo(w[2]))), __float_as_uint(fmaf(gt[h], a[r + 9], bf_hi(w[2]))),
                               __float_as_uint(fmaf(gt[h], a[r + 12], bf_lo(w[3]))), __float_as_uint(fmaf(gt[h], a[r + 13], bf_hi(w[3]))));
                        if (jq < 2) asm volatile("ld.shared.v4.b32 {%0,%1,%2,%3}, [%4];" : "=r"(w[0]), "=r"(w[1]), "=r"(w[2]), "=r"(w[3]) : "r"(ad + 16384) : "memory");
                    }
                    fence_async_smem();
                    __syncwarp();
                    if (lane == 0) mbar_arrive(bar_stg + 48 + 32 * b + 8 * jq);
                    if (b == 0 && jq < SKEW2 - 1) late(33 - SKEW2 + jq);
                    if (SKEW2 == 6 && b == 0 && jq == 0) {
                        wgmma_wait<1>();
                        if (t == 0) mbar_arrive(bar_o1);
                    }
                    if (SKEW2 == 6 && b == 0 && jq == 3) late(31);
                }
            };
            mbar_wait(bar_bias, 0);
            if (t == 0) STAMP(2, 4);
            epilogue(c0, 0);
            mbar_wait(bar_bias + 8, 0);
            epilogue(c1, 1);
            if (t == 0) STAMP(2, 7);
            return;
        }
        asm volatile("setmaxnreg.dec.sync.aligned.u32 %0;" ::"n"(REG_C));
    }
    {
        {
            const int t = fresh_tid() & 127, lane = t & 31, w4 = t >> 5;
            Twiddle tw;
            load_twiddle(tw, reinterpret_cast<const uint4*>(g_tw_tab.w) + t);
            const uint32_t lo = (uint32_t)((16 * w4 + (lane & 7)) * 64 + (((lane >> 3) ^ ((lane >> 1) & 3)) << 4));
            const uint32_t tlo = desc_lo(sbase + OFF_CT, 16);
            float dE[32], dO[32];
            int p = wg == 2 ? 2 : 0;
            mbar_wait(bar_stg, 0);
            mbar_wait(bar_tab, 0);
            mbar_wait(bar_k + 8 * p, 0);
            if (t == 0) STAMP(0, wg == 2 ? 50 : 1);
            wgmma_fence();
            conv_s1(dE, dO, tlo, desc_lo(sbase + conv_buf(0) + p * 16384, 8192));
            wgmma_commit();
            wgmma_wait<0>();
            fence_regs(dE); fence_regs(dO);
            named_bar(wg, 128);
#pragma unroll 1
            for (; p < 4; p = 2 * p + 1) {
                const int pn = p < 2 ? 2 * p + 1 : p;
                if (t == 0) STAMP(0, 40 + 2 * p);
                conv_pair(dE, dO, tw, lds32(w_dsk + ((lane & 3) ? 16 : 4 * p)), tlo, sbase + conv_buf(p), sbase + conv_buf(pn), lo, wg,
                                [&]() { mbar_wait(bar_k + 8 * pn, 0); });
                if (lane == 0) mbar_arrive(bar_stg + 16 + 8 * p);
            }
            if (t == 0) STAMP(0, 57 + wg);
            __syncwarp();
        }
        if (wg == 2) {
            {
            const int t = fresh_tid() & 127, lane = t & 31, w4 = t >> 5, g = lane >> 2, t4 = lane & 3;
            const int bid = lds32(w_bid), dt = bid & 7;
            const int trow = (bid >> 4) * 256 + 4 * (bid & 8) + 128 * (w4 & 1) + 8 * (w4 >> 1) + g;
            uint4 xv[16], dk[4];
            const __nv_bfloat16* xp = x + (size_t)trow * D_DIM + dt * 128 + 8 * t4;
#pragma unroll
            for (int i = 0; i < 16; ++i) {
                xv[i] = ldg128(xp + (size_t)(16 * (i >> 3) + 64 * ((i >> 2) & 1)) * D_DIM + 32 * (i & 3));
                if (i & 1) __nanosleep(GAP_X);
            }
#pragma unroll
            for (int jq = 0; jq < 4; ++jq) dk[jq] = ldg128(dskip + dt * 128 + 32 * jq + 8 * t4);
            mbar_wait(bar_fh, 0);
            uint32_t omg[4], g2[4];
#pragma unroll
            for (int i = 0; i < 4; ++i) {
                const float gt = __ldcg(g_gate + trow + 16 * (i >> 1) + 64 * (i & 1));
                if (t4 == 0) asm volatile("st.shared.f32 [%0], %1;" ::"r"(sbase + OFF_PAR + (64 * (i >> 1) + 16 * w4 + 8 * (i & 1) + g) * 4), "f"(gt) : "memory");
                omg[i] = pack_bf16(2.f - 2.f * gt, 2.f - 2.f * gt); g2[i] = pack_bf16(gt, gt);
            }
            if (t == 0) {
                mbar_wait(bar_yrel, 0);
                wait_counter(&g_cnt[(48 + dt) * 32], lds32(w_bid + 4));
                STAMP(0, 16);
                mbar_expect_tx(bar_y1, 24576);
                tma_load_5d(sbase + OFF_CU, &maps.yt3, bar_y1, (bid & 8) * 128 + (bid >> 4) * 128, 0, 0, 0, dt * 4);
                tma_load_5d(sbase + OFF_CU + 12288, &maps.yt3, bar_y1, (bid & 8) * 128 + (bid >> 4) * 128 + 64, 0, 0, 0, dt * 4);
            }
            __syncwarp();
            uint32_t ya = sbase + OFF_CU + (w4 & 1) * 12288 + (lane >> 3) * 3072 + (lane & 7) * 128 + ((((w4 >> 1) ^ ((bid >> 3 & 2) + (w4 & 1))) ^ (lane & 7)) << 4);
            mbar_wait(bar_y1, 0);
            if (t == 0) STAMP(0, 18);
#pragma unroll
            for (int p = 0; p < 3; ++p)
#pragma unroll
                for (int i = 0; i < 4; ++i) {
                    uint32_t yw[4];
                    ldsm_x4_t(yw[0], yw[1], yw[2], yw[3], (ya ^ ((i & 1) << 6) ^ ((i & 2) << 4)) + p * 1024);
#pragma unroll
                    for (int jq = 0; jq < 4; ++jq) {
                        uint32_t& w = (&xv[4 * i + jq].x)[p];
                        w = hfma(g2[i], hmul(w, (&dk[jq].x)[p]), hmul(omg[i], hmul(w, yw[jq])));
                    }
                }
            uint32_t xd[16], yw[16];
#pragma unroll
            for (int i = 0; i < 16; ++i) { xd[i] = hmul(xv[i].w, dk[i & 3].w); asm volatile("" : "+r"(xd[i]), "+r"(xv[i].x), "+r"(xv[i].y), "+r"(xv[i].z)); }
            if (t == 0) STAMP(0, 17);
            ya += 24576 - (w4 & 1) * 8192 - (lane >> 3) * 2048;
            mbar_wait(bar_y, 0);
            if (t == 0) STAMP(0, 6);
#pragma unroll
            for (int i = 0; i < 4; ++i) ldsm_x4_t(yw[4 * i], yw[4 * i + 1], yw[4 * i + 2], yw[4 * i + 3], ya ^ ((i & 1) << 6) ^ ((i & 2) << 4));
            named_bar(2, 128);
#pragma unroll
            for (int i = 0; i < 16; ++i) {
                if (SLOT5 < 32 && i == 8) mbar_wait(bar_o1, 0);
                sts128(sbase + (i & 8 ? OFF_O1 : OFF_CU) + (i & 3) * 8192 + (w4 * 16 + g + (i & 4) * 2) * 128 + (((2 * t4) ^ g) << 4), xv[i].x, xv[i].y, xv[i].z,
                       hfma(g2[i >> 2], xd[i], hmul(omg[i >> 2], hmul(xv[i].w, yw[i]))));
                if ((i & 7) == 7) {
                    __syncwarp();
                    if (lane == 0) mbar_arrive(bar_bias + (i & 8));
                }
            }
            if (t == 0) STAMP(0, 7);
            }
        }
    }
    }
}

void make_map(CUtensorMap* m, const void* ptr, int rank, const cuuint64_t* dims, const cuuint64_t* strides, const cuuint32_t* box,
              CUtensorMapSwizzle swz, bool f32 = false) {
    cuuint32_t es[5] = {1, 1, 1, 1, 1};
    get_encode()(m, f32 ? CU_TENSOR_MAP_DATA_TYPE_FLOAT32 : CU_TENSOR_MAP_DATA_TYPE_BFLOAT16, rank, const_cast<void*>(ptr), dims, strides, box, es,
                 CU_TENSOR_MAP_INTERLEAVE_NONE, swz, CU_TENSOR_MAP_L2_PROMOTION_L2_256B, CU_TENSOR_MAP_FLOAT_OOB_FILL_NONE);
}
void make_map_2d(CUtensorMap* m, const void* ptr, uint64_t inner, uint64_t outer, uint32_t box_in, uint32_t box_out) {
    cuuint64_t dims[2] = {inner, outer};
    cuuint64_t strides[1] = {inner * 2};
    cuuint32_t box[2] = {box_in, box_out};
    make_map(m, ptr, 2, dims, strides, box, CU_TENSOR_MAP_SWIZZLE_128B);
}
void make_map_conv(CUtensorMap* m, const void* p, uint32_t nch = 2) {
    cuuint64_t dims[4] = {32, 32, 2, 1024};
    cuuint64_t strides[3] = {128, 64, 4096};
    cuuint32_t box[4] = {32, 32, 2, nch};
    make_map(m, p, 4, dims, strides, box, CU_TENSOR_MAP_SWIZZLE_64B);
}

}

extern "C" void kernel_launch(void* const* d_in, const int* in_sizes, int n_in, void* d_out, int out_size) {
    const __nv_bfloat16* x = (const __nv_bfloat16*)d_in[0];
    const __nv_bfloat16* lam_re = (const __nv_bfloat16*)d_in[1];
    const __nv_bfloat16* lam_im = (const __nv_bfloat16*)d_in[2];
    const __nv_bfloat16* b_re = (const __nv_bfloat16*)d_in[3];
    const __nv_bfloat16* b_im = (const __nv_bfloat16*)d_in[4];
    const __nv_bfloat16* c_re = (const __nv_bfloat16*)d_in[5];
    const __nv_bfloat16* c_im = (const __nv_bfloat16*)d_in[6];
    const __nv_bfloat16* log_dt = (const __nv_bfloat16*)d_in[7];
    const __nv_bfloat16* dskip = (const __nv_bfloat16*)d_in[8];
    const __nv_bfloat16* kin = (const __nv_bfloat16*)d_in[10];
    const __nv_bfloat16* vin = (const __nv_bfloat16*)d_in[11];
    const __nv_bfloat16* shift_k = (const __nv_bfloat16*)d_in[12];
    const __nv_bfloat16* ssm_k = (const __nv_bfloat16*)d_in[13];
    const __nv_bfloat16* ssm_D = (const __nv_bfloat16*)d_in[14];
    const __nv_bfloat16* gate_w = (const __nv_bfloat16*)d_in[15];
    float* out = (float*)d_out;

    void *yptr = nullptr, *kvtptr = nullptr;
    cudaGetSymbolAddress(&yptr, g_y2);
    cudaGetSymbolAddress(&kvtptr, g_kvT);

    Maps maps;
    {
        cuuint64_t dims[5] = {1024, 2, 4, 32, 8};
        cuuint64_t strides[4] = {2048, 64 * 2048, 2 * 2048, 256 * 2048};
        cuuint32_t box[5] = {64, 2, 4, 32, 1};
        make_map(&maps.x5, x, 5, dims, strides, box, CU_TENSOR_MAP_SWIZZLE_128B);
    }
    int bmode = 0;
    {
        const uint64_t a = (uint64_t)b_re, b = (uint64_t)b_im;
        const uint64_t delta = a < b ? b - a : a - b;
        if (delta != 0 && (delta & 15) == 0 && delta < (1ull << 40)) bmode = a < b ? 1 : 2;
        cuuint64_t dims[4] = {1024, 8, 2, 128};
        cuuint64_t strides[3] = {2048, bmode ? delta : 16, 16384};
        cuuint32_t box[4] = {64, 8, 2, 4};
        make_map(&maps.b4, a < b ? b_re : b_im, 4, dims, strides, box, CU_TENSOR_MAP_SWIZZLE_128B);
    }
    make_map_2d(&maps.bre, b_re, 1024, 1024, 64, 8);
    make_map_2d(&maps.bim, b_im, 1024, 1024, 64, 8);
    {
        cuuint64_t dims[3] = {S_LEN, 128, 8};
        cuuint64_t strides[2] = {8 * 4096, 4096};
        cuuint32_t box[3] = {64, 16, 2};
        make_map(&maps.kvst, kvtptr, 3, dims, strides, box, CU_TENSOR_MAP_SWIZZLE_128B);
    }
    make_map_conv(&maps.sk, ssm_k, 1);
    for (int i = 0; i < 2; ++i) {
        cuuint64_t dims[5] = {1024, 2, 4, 4, 32};
        cuuint64_t strides[4] = {2048, 8 * 2048, 2 * 2048, 32 * 2048};
        cuuint32_t box[5] = {64, 2, 4, 4, 4};
        make_map(i ? &maps.cim : &maps.cre, i ? c_im : c_re, 5, dims, strides, box, CU_TENSOR_MAP_SWIZZLE_128B);
    }
    {
        cuuint64_t dims[5] = {S_LEN, 2, 4, 4, 32};
        cuuint64_t strides[4] = {4096, 8 * 4096, 2 * 4096, 32 * 4096};
        cuuint32_t box[5] = {64, 2, 4, 1, 4};
        make_map(&maps.yt, yptr, 5, dims, strides, box, CU_TENSOR_MAP_SWIZZLE_128B);
        box[3] = 3;
        make_map(&maps.yt3, yptr, 5, dims, strides, box, CU_TENSOR_MAP_SWIZZLE_128B);
    }
    {
        cuuint64_t dims[5] = {D_DIM, 8, 4, 8, 8};
        cuuint64_t strides[4] = {4096, 64 * 4096, 8 * 4096, 256 * 4096};
        cuuint32_t box[5] = {32, 8, 4, 2, 1};
        make_map(&maps.out, out, 5, dims, strides, box, CU_TENSOR_MAP_SWIZZLE_128B, true);
    }

    auto kern = bmode == 1 ? fused_kernel<1> : bmode == 2 ? fused_kernel<2> : fused_kernel<0>;
    cudaFuncSetAttribute(kern, cudaFuncAttributeMaxDynamicSharedMemorySize, SMEM_BYTES);
    static int grid = 0;
    if (!grid) {
        int dev = 0, sms = 0;
        cudaGetDevice(&dev);
        cudaDeviceGetAttribute(&sms, cudaDevAttrMultiProcessorCount, dev);
        grid = sms == 132 ? 132 : 128;
    }
    kern<<<grid, 512, SMEM_BYTES>>>(x, b_re, b_im, kin, vin, ssm_k, shift_k, ssm_D, lam_re, lam_im, log_dt, gate_w, dskip, c_re, c_im, maps);
}
```

```cpp
#include <cuda_runtime.h>
#include <cuda_bf16.h>
#include <cuda.h>
#include <stdint.h>
#include <type_traits>

namespace {
__device__ __forceinline__ uint32_t smem_u32(const void* p) { return (uint32_t)__cvta_generic_to_shared(p); }
__device__ __forceinline__ void mbar_init(uint32_t bar, uint32_t count) {
    asm volatile("mbarrier.init.shared::cta.b64 [%0], %1;" ::"r"(bar), "r"(count) : "memory");
}
__device__ __forceinline__ void mbar_expect_tx(uint32_t bar, uint32_t bytes) {
    asm volatile("mbarrier.arrive.expect_tx.shared::cta.b64 _, [%0], %1;" ::"r"(bar), "r"(bytes) : "memory");
}
__device__ __forceinline__ void mbar_arrive(uint32_t bar) {
    asm volatile("mbarrier.arrive.shared::cta.b64 _, [%0];" ::"r"(bar) : "memory");
}
__device__ __forceinline__ void mbar_wait(uint32_t bar, uint32_t parity) {
    asm volatile(
        "{\n"
        ".reg .pred p;\n"
        ".reg .u32 n;\n"
        "mov.u32 n, 0;\n"
        "LAB_WAIT:\n"
        "mbarrier.try_wait.parity.shared::cta.b64 p, [%0], %1;\n"
        "@p bra LAB_DONE;\n"
        "add.u32 n, n, 1;\n"
        "setp.lt.u32 p, n, 0x400000;\n"
        "@p bra LAB_WAIT;\n"
        "trap;\n"
        "LAB_DONE:\n"
        "}\n" ::"r"(bar), "r"(parity) : "memory");
}
__device__ __forceinline__ void tma_load_2d(uint32_t dst, const CUtensorMap* map, uint32_t bar, int c0, int c1) {
    asm volatile(
        "cp.async.bulk.tensor.2d.shared::cluster.global.mbarrier::complete_tx::bytes [%0], [%1, {%3, %4}], [%2];"
        ::"r"(dst), "l"((uint64_t)map), "r"(bar), "r"(c0), "r"(c1) : "memory");
}
__device__ __forceinline__ void tma_load_4d(uint32_t dst, const CUtensorMap* map, uint32_t bar, int c0, int c1, int c2, int c3) {
    asm volatile(
        "cp.async.bulk.tensor.4d.shared::cluster.global.mbarrier::complete_tx::bytes [%0], [%1, {%3, %4, %5, %6}], [%2];"
        ::"r"(dst), "l"((uint64_t)map), "r"(bar), "r"(c0), "r"(c1), "r"(c2), "r"(c3) : "memory");
}
__device__ __forceinline__ void tma_load_5d(uint32_t dst, const CUtensorMap* map, uint32_t bar, int c0, int c1, int c2, int c3, int c4) {
    asm volatile(
        "cp.async.bulk.tensor.5d.shared::cluster.global.mbarrier::complete_tx::bytes [%0], [%1, {%3, %4, %5, %6, %7}], [%2];"
        ::"r"(dst), "l"((uint64_t)map), "r"(bar), "r"(c0), "r"(c1), "r"(c2), "r"(c3), "r"(c4) : "memory");
}
__device__ __forceinline__ void bulk_load(uint32_t dst, const void* src, uint32_t bytes, uint32_t bar) {
    asm volatile("cp.async.bulk.shared::cluster.global.mbarrier::complete_tx::bytes [%0], [%1], %2, [%3];"
                 ::"r"(dst), "l"(src), "r"(bytes), "r"(bar) : "memory");
}
__device__ __forceinline__ void tma_store_3d(const CUtensorMap* map, uint32_t src, int c0, int c1, int c2) {
    asm volatile("cp.async.bulk.tensor.3d.global.shared::cta.bulk_group [%0, {%2, %3, %4}], [%1];"
                 ::"l"((uint64_t)map), "r"(src), "r"(c0), "r"(c1), "r"(c2) : "memory");
}
__device__ __forceinline__ void bulk_commit() { asm volatile("cp.async.bulk.commit_group;" ::: "memory"); }
__device__ __forceinline__ void bulk_wait0() { asm volatile("cp.async.bulk.wait_group 0;" ::: "memory"); }
__device__ __forceinline__ void bulk_wait_read0() { asm volatile("cp.async.bulk.wait_group.read 0;" ::: "memory"); }
__device__ __forceinline__ void fence_async_smem() { asm volatile("fence.proxy.async.shared::cta;" ::: "memory"); }
__device__ __forceinline__ void named_bar(int id, int n) { asm volatile("bar.sync %0, %1;" ::"r"(id), "r"(n) : "memory"); }
__device__ __forceinline__ void sts128(uint32_t addr, uint32_t a, uint32_t b, uint32_t c, uint32_t d) {
    asm volatile("st.shared.v4.b32 [%0], {%1, %2, %3, %4};" ::"r"(addr), "r"(a), "r"(b), "r"(c), "r"(d) : "memory");
}
__device__ __forceinline__ void prefetch_map(const CUtensorMap* m) {
    asm volatile("prefetch.tensormap [%0];" ::"l"((uint64_t)m) : "memory");
}
__device__ __forceinline__ void wgmma_fence() { asm volatile("wgmma.fence.sync.aligned;" ::: "memory"); }
__device__ __forceinline__ void wgmma_commit() { asm volatile("wgmma.commit_group.sync.aligned;" ::: "memory"); }
template <int N>
__device__ __forceinline__ void wgmma_wait() { asm volatile("wgmma.wait_group.sync.aligned %0;" ::"n"(N) : "memory"); }
template <int N>
__device__ __forceinline__ void fence_regs(float (&a)[N]) {
#pragma unroll
    for (int i = 0; i < N; ++i) asm volatile("" : "+f"(a[i])::"memory");
}
template <int N>
__device__ __forceinline__ void fence_regs(uint32_t (&a)[N]) {
#pragma unroll
    for (int i = 0; i < N; ++i) asm volatile("" : "+r"(a[i])::"memory");
}
#define R8(a, i) "+f"(a[i + 0]), "+f"(a[i + 1]), "+f"(a[i + 2]), "+f"(a[i + 3]), "+f"(a[i + 4]), "+f"(a[i + 5]), "+f"(a[i + 6]), "+f"(a[i + 7])
#define REGS32 "{%0, %1, %2, %3, %4, %5, %6, %7, %8, %9, %10, %11, %12, %13, %14, %15, %16, %17, %18, %19, %20, %21, %22, %23, %24, %25, %26, %27, %28, %29, %30, %31}"
#define REGS16 "{%0, %1, %2, %3, %4, %5, %6, %7, %8, %9, %10, %11, %12, %13, %14, %15}"

__host__ __device__ constexpr uint32_t desc_hi(uint32_t sbo, uint32_t mode) { return (sbo >> 4) | (mode << 30); }
__device__ __forceinline__ uint32_t desc_lo(uint32_t saddr, uint32_t lbo) { return ((saddr & 0x3FFFF) >> 4) | ((lbo >> 4) << 16); }
constexpr uint32_t HI128 = desc_hi(1024, 1), HI64 = desc_hi(512, 2);
#define W8(a, i) "=f"(a[i + 0]), "=f"(a[i + 1]), "=f"(a[i + 2]), "=f"(a[i + 3]), "=f"(a[i + 4]), "=f"(a[i + 5]), "=f"(a[i + 6]), "=f"(a[i + 7])
template <int TA, int TB, int ACC, uint32_t AHI, uint32_t BHI>
__device__ __forceinline__ void wgmma_n64_ss(float (&d)[32], uint32_t alo, uint32_t blo) {
#define N64_TEXT "{\n.reg .pred p;\n.reg .b64 da, db;\nsetp.ne.b32 p, %36, 0;\nmov.b64 da, {%32, %37};\nmov.b64 db, {%33, %38};\n" \
        "wgmma.mma_async.sync.aligned.m64n64k16.f32.bf16.bf16 " REGS32 ", da, db, p, 1, 1, %34, %35;\n}\n"
    if (ACC) asm volatile(N64_TEXT : R8(d, 0), R8(d, 8), R8(d, 16), R8(d, 24) : "r"(alo), "r"(blo), "n"(TA), "n"(TB), "n"(ACC), "n"(AHI), "n"(BHI));
    else asm volatile(N64_TEXT : W8(d, 0), W8(d, 8), W8(d, 16), W8(d, 24) : "r"(alo), "r"(blo), "n"(TA), "n"(TB), "n"(ACC), "n"(AHI), "n"(BHI));
}
template <int ACC, int SA>
__device__ __forceinline__ void wgmma_n32_tt(float (&d)[16], uint32_t alo, uint32_t blo) {
#define N32T_TEXT "{\n.reg .pred p;\n.reg .b64 da, db;\nsetp.ne.b32 p, %18, 0;\nmov.b64 da, {%16, %19};\nmov.b64 db, {%17, %20};\n" \
        "wgmma.mma_async.sync.aligned.m64n32k16.f32.bf16.bf16 " REGS16 ", da, db, p, %21, 1, 1, 1;\n}\n"
    if (ACC) asm volatile(N32T_TEXT : R8(d, 0), R8(d, 8) : "r"(alo), "r"(blo), "n"(ACC), "n"(HI64), "n"(HI128), "n"(SA));
    else asm volatile(N32T_TEXT : W8(d, 0), W8(d, 8) : "r"(alo), "r"(blo), "n"(ACC), "n"(HI64), "n"(HI128), "n"(SA));
}
__device__ __forceinline__ void wgmma_n16_rs(float (&d)[8], const uint32_t (&a)[4], uint32_t blo) {
    asm volatile("{\n.reg .pred p;\n.reg .b64 db;\nsetp.ne.b32 p, 0, 0;\nmov.b64 db, {%12, %13};\n"
        "wgmma.mma_async.sync.aligned.m64n16k16.f32.bf16.bf16 {%0, %1, %2, %3, %4, %5, %6, %7}, {%8, %9, %10, %11}, db, p, 1, 1, 0;\n}\n"
        : W8(d, 0) : "r"(a[0]), "r"(a[1]), "r"(a[2]), "r"(a[3]), "r"(blo), "n"(HI128));
}

__device__ __forceinline__ float bf16r(float x) { return __bfloat162float(__float2bfloat16_rn(x)); }
__device__ __forceinline__ uint32_t pack_bf16(float lo, float hi) {
    __nv_bfloat162 v = __floats2bfloat162_rn(lo, hi);
    return *reinterpret_cast<uint32_t*>(&v);
}
__device__ __forceinline__ __nv_bfloat162 as_bf2(uint32_t w) { return *reinterpret_cast<__nv_bfloat162*>(&w); }
__device__ __forceinline__ uint32_t as_u32(__nv_bfloat162 v) { return *reinterpret_cast<uint32_t*>(&v); }
__device__ __forceinline__ float bf_lo(uint32_t w) { return __uint_as_float(w << 16); }
__device__ __forceinline__ float bf_hi(uint32_t w) { return __uint_as_float(w & 0xFFFF0000u); }
__device__ __forceinline__ void ldsm_x4_t(uint32_t& r0, uint32_t& r1, uint32_t& r2, uint32_t& r3, uint32_t addr) {
    asm volatile("ldmatrix.sync.aligned.m8n8.x4.trans.shared.b16 {%0,%1,%2,%3}, [%4];"
                 : "=r"(r0), "=r"(r1), "=r"(r2), "=r"(r3) : "r"(addr) : "memory");
}
__device__ __forceinline__ void stsm_x4(uint32_t addr, uint32_t r0, uint32_t r1, uint32_t r2, uint32_t r3) {
    asm volatile("stmatrix.sync.aligned.m8n8.x4.shared.b16 [%0], {%1,%2,%3,%4};"
                 ::"r"(addr), "r"(r0), "r"(r1), "r"(r2), "r"(r3) : "memory");
}
__device__ __forceinline__ void stsm_x4_t(uint32_t addr, uint32_t r0, uint32_t r1, uint32_t r2, uint32_t r3) {
    asm volatile("stmatrix.sync.aligned.m8n8.x4.trans.shared.b16 [%0], {%1,%2,%3,%4};"
                 ::"r"(addr), "r"(r0), "r"(r1), "r"(r2), "r"(r3) : "memory");
}
__device__ __forceinline__ uint32_t lds32(uint32_t addr) {
    uint32_t v;
    asm volatile("ld.shared.b32 %0, [%1];" : "=r"(v) : "r"(addr));
    return v;
}

typedef CUresult (*EncodeFn)(CUtensorMap*, CUtensorMapDataType, cuuint32_t, void*, const cuuint64_t*, const cuuint64_t*,
                             const cuuint32_t*, const cuuint32_t*, CUtensorMapInterleave, CUtensorMapSwizzle,
                             CUtensorMapL2promotion, CUtensorMapFloatOOBfill);
EncodeFn get_encode() {
    static EncodeFn fn = nullptr;
    if (!fn) {
        void* p = nullptr;
        cudaDriverEntryPointQueryResult qres;
        cudaGetDriverEntryPoint("cuTensorMapEncodeTiled", &p, cudaEnableDefault, &qres);
        fn = (EncodeFn)p;
    }
    return fn;
}
}
namespace {
constexpr double c_pi = 3.14159265358979323846;
constexpr double c_cos256(int i) {
    i &= 255;
    if (i > 128) i = 256 - i;
    double sgn = 1.0;
    if (i > 64) { i = 128 - i; sgn = -1.0; }
    if (i == 64) return 0.0;
    double x = 2.0 * c_pi * i / 256.0, x2 = x * x, term = 1.0, sum = 1.0;
    for (int k = 1; k < 20; ++k) { term *= -x2 / ((2 * k - 1) * (2 * k)); sum += term; }
    return sgn * sum;
}
constexpr uint32_t c_bf16(double v) {
    if (v == 0.0) return 0u;
    uint32_t s = v < 0 ? 0x8000u : 0u;
    double a = v < 0 ? -v : v;
    int e = 0;
    while (a >= 2.0) { a *= 0.5; ++e; }
    while (a < 1.0) { a *= 2.0; --e; }
    int r = (int)(a * 128.0 + 0.5);
    if (r == 256) { r = 128; ++e; }
    return s | (uint32_t)((e + 127) << 7) | (uint32_t)(r - 128);
}
__host__ __device__ constexpr int conv_k1(int r) { return (r & 8) ? 63 - (((r >> 4) << 3) | (r & 7)) : (((r >> 4) << 3) | (r & 7)); }
struct ConvTab { uint32_t w[96 * 32]; };
constexpr ConvTab make_conv_tab() {
    ConvTab t{};
    uint32_t cs[256] = {};
    for (int i = 0; i < 256; ++i) cs[i] = c_bf16(c_cos256(i));
    for (int n = 0; n < 96; ++n)
        for (int c = 0; c < 64; ++c) {
            int a = 0;
            if (n < 32) {
                const int ro = (n >> 3) & 1, ri = n & 7, co = (c >> 3) & 1, ci = c & 7;
                a = n < 16 ? 8 * ci * (4 * ri + (c >> 4)) : 8 * ri * (4 * ci + (c >> 4));
                a += (ro == co) ? 0 : (ro == 0) ? 192 : 64;
            } else {
                const int r = n - 32, n1 = 2 * (c & 31) + (c >> 5);
                a = n1 * (2 * (((r >> 4) << 3) | (r & 7)) + 1) + ((r & 8) ? 64 : 0);
            }
            const int off = n * 128 + (((c >> 3) ^ (n & 7)) << 4) + (c & 7) * 2;
            t.w[off >> 2] |= cs[a & 255] << ((off & 2) * 8);
        }
    return t;
}
__device__ __align__(128) constexpr ConvTab g_conv_tab = make_conv_tab();

struct Twiddle { uint32_t r[8], i[8], n[8]; };
constexpr double c_cospi(double x) {
    double sgn = 1.0;
    if (x > 0.5) { x = 1.0 - x; sgn = -1.0; }
    const double y = c_pi * x, y2 = y * y;
    double term = 1.0, sum = 1.0;
    for (int k = 1; k < 12; ++k) { term *= -y2 / ((2 * k - 1) * (2 * k)); sum += term; }
    return sgn * sum;
}
struct TwTab { uint32_t w[3072]; };
constexpr TwTab make_tw_tab() {
    TwTab t{};
    for (int th = 0; th < 128; ++th)
        for (int q = 0; q < 8; ++q)
            for (int e = 0; e < 2; ++e) {
                const int k1 = conv_k1(16 * (th >> 5) + 8 * (q & 1) + ((th & 31) >> 2)), n2 = 8 * (q >> 1) + 2 * (th & 3) + e;
                const double x = (double)(n2 * (2 * k1 + 1)) / 4096.0;
                const double cs = c_cospi(x), sn = n2 == 0 ? 0.0 : c_cospi(x > 0.5 ? x - 0.5 : 0.5 - x);
                t.w[((q >> 2) * 128 + th) * 4 + (q & 3)] |= c_bf16(cs * 0.0625) << (16 * e);
                t.w[((2 + (q >> 2)) * 128 + th) * 4 + (q & 3)] |= c_bf16(-sn * 0.0625) << (16 * e);
                t.w[((4 + (q >> 2)) * 128 + th) * 4 + (q & 3)] |= c_bf16(sn * 0.0625) << (16 * e);
            }
    return t;
}
__device__ __align__(128) constexpr TwTab g_tw_tab = make_tw_tab();
__device__ __forceinline__ void load_twiddle(Twiddle& tw, const uint4* p) {
#pragma unroll
    for (int q = 0; q < 2; ++q) {
        const uint4 a = __ldg(p + q * 128);
        const uint4 b = __ldg(p + (2 + q) * 128);
        tw.r[4 * q] = a.x; tw.r[4 * q + 1] = a.y; tw.r[4 * q + 2] = a.z; tw.r[4 * q + 3] = a.w;
        const uint4 n = __ldg(p + (4 + q) * 128);
        tw.n[4 * q] = n.x; tw.n[4 * q + 1] = n.y; tw.n[4 * q + 2] = n.z; tw.n[4 * q + 3] = n.w;
        tw.i[4 * q] = b.x; tw.i[4 * q + 1] = b.y; tw.i[4 * q + 2] = b.z; tw.i[4 * q + 3] = b.w;
    }
}

__device__ __forceinline__ int fresh_tid() { int v; asm volatile("mov.u32 %0, %tid.x;" : "=r"(v)); return v; }
__device__ __forceinline__ uint32_t hmul(uint32_t a, uint32_t b) { return as_u32(__hmul2_rn(as_bf2(a), as_bf2(b))); }
__device__ __forceinline__ uint32_t hadd(uint32_t a, uint32_t b) { return as_u32(__hadd2_rn(as_bf2(a), as_bf2(b))); }
__device__ __forceinline__ uint32_t hsub(uint32_t a, uint32_t b) { return as_u32(__hsub2_rn(as_bf2(a), as_bf2(b))); }
__device__ __forceinline__ uint32_t hfma(uint32_t a, uint32_t b, uint32_t c) { return as_u32(__hfma2(as_bf2(a), as_bf2(b), as_bf2(c))); }

__device__ __forceinline__ void conv_dft8(float (&x)[4][8], const uint32_t (&f)[4][4], uint32_t blo) {
#pragma unroll
    for (int r = 0; r < 4; ++r) wgmma_n16_rs(x[r], f[r], blo + 2 * r);
}
template <class T, int N>
__device__ __forceinline__ void fence_regs4(T (&a)[4][N]) { fence_regs(a[0]); fence_regs(a[1]); fence_regs(a[2]); fence_regs(a[3]); }
__device__ __forceinline__ void conv_s1(float (&dE)[32], float (&dO)[32], uint32_t tlo, uint32_t ulo) {
    wgmma_n64_ss<0, 1, 0, HI128, HI64>(dE, tlo + 256, ulo);
    wgmma_n64_ss<0, 1, 0, HI128, HI64>(dO, tlo + 256 + 4, ulo + 128);
    wgmma_n64_ss<0, 1, 1, HI128, HI64>(dE, tlo + 256 + 2, ulo + 64);
    wgmma_n64_ss<0, 1, 1, HI128, HI64>(dO, tlo + 256 + 6, ulo + 192);
}
template <int S>
__device__ __forceinline__ void conv_t1(const float (&dE)[32], const float (&dO)[32], const Twiddle& tw, float dsk, uint32_t (&f)[4][4]) {
    uint32_t ar[8], ai[8], fs[8], fd[8];
#pragma unroll
    for (int j = 0; j < 4; ++j) {
        const int i = 16 * S + 4 * j;
        const uint32_t e0 = pack_bf16(i == 16 ? dE[i] + dsk : dE[i], dE[i + 1]), e1 = pack_bf16(dE[i + 2], dE[i + 3]);
        const uint32_t o0 = pack_bf16(dO[i], dO[i + 1]), o1 = pack_bf16(dO[i + 2], dO[i + 3]);
        ar[2 * j] = hadd(e0, o0); ai[2 * j] = hadd(e1, o1);
        ar[2 * j + 1] = hsub(e0, o0); ai[2 * j + 1] = hsub(o1, e1);
    }
#pragma unroll
    for (int q = 0; q < 4; ++q) {
        const uint32_t pr = hfma(ar[q], tw.r[q], hmul(ai[q], tw.n[q])), pi = hfma(ar[q], tw.i[q], hmul(ai[q], tw.r[q]));
        fs[q] = hfma(ar[4 + q], tw.r[4 + q], hfma(ai[4 + q], tw.n[4 + q], pr));
        fs[4 + q] = hfma(ar[4 + q], tw.i[4 + q], hfma(ai[4 + q], tw.r[4 + q], pi));
        fd[q] = hfma(pr, 0xC000C000u, fs[q]);
        fd[4 + q] = hfma(pi, 0xC000C000u, fs[4 + q]);
    }
#pragma unroll
    for (int h = 0; h < 2; ++h) {
        f[0][h] = hadd(fs[h], fs[2 + h]); f[0][2 + h] = hadd(fs[4 + h], fs[6 + h]);
        f[2][h] = hsub(fs[h], fs[2 + h]); f[2][2 + h] = hsub(fs[4 + h], fs[6 + h]);
        f[1][h] = hadd(fd[h], fd[6 + h]); f[1][2 + h] = hsub(fd[4 + h], fd[2 + h]);
        f[3][h] = hsub(fd[h], fd[6 + h]); f[3][2 + h] = hadd(fd[4 + h], fd[2 + h]);
    }
}
__device__ __forceinline__ void conv_prod(const float (&xu)[8], const float (&xk)[8], uint32_t (&f)[4]) {
#pragma unroll
    for (int h = 0; h < 2; ++h) {
        float pr[2], pi[2];
#pragma unroll
        for (int e = 0; e < 2; ++e) {
            const float ur = xu[2 * h + e], ui = xu[4 + 2 * h + e], kr = xk[2 * h + e], ki = xk[4 + 2 * h + e];
            pr[e] = fmaf(ur, kr, -ui * ki);
            pi[e] = fmaf(-ur, ki, -ui * kr);
        }
        f[h] = pack_bf16(pr[0], pr[1]);
        f[2 + h] = pack_bf16(pi[0], pi[1]);
    }
}
template <bool SECOND, class G>
__device__ __forceinline__ void conv_channel(float (&dE)[32], float (&dO)[32], const Twiddle& tw, float dsk, uint32_t tlo, uint32_t nxt,
                                             uint32_t wre, uint32_t wim, int bar, G before_next) {
    float xu[4][8], xk[4][8];
    {
        uint32_t fu[4][4], fk[4][4];
        conv_t1<0>(dE, dO, tw, 0.f, fu);
        wgmma_fence();
        conv_dft8(xu, fu, tlo);
        wgmma_commit();
        conv_t1<1>(dE, dO, tw, dsk, fk);
        wgmma_fence();
        conv_dft8(xk, fk, tlo);
        wgmma_commit();
        before_next();
        wgmma_wait<0>();
        fence_regs4(xu); fence_regs4(xk);
        fence_regs4(fu); fence_regs4(fk);
    }
    uint32_t fp[4][4];
#pragma unroll
    for (int r = 0; r < 4; ++r) conv_prod(xu[r], xk[r], fp[r]);
    wgmma_fence();
    conv_dft8(xu, fp, tlo + 128);
    wgmma_commit();
    if (!SECOND || nxt) {
        if (SECOND) wgmma_fence();
        conv_s1(dE, dO, tlo, nxt);
        wgmma_commit();
        wgmma_wait<1>();
    } else {
        wgmma_wait<0>();
#pragma unroll
        for (int i = 0; i < 32; ++i) { dE[i] = 0.f; dO[i] = 0.f; }
        fence_regs(dE); fence_regs(dO);
    }
    fence_regs4(xu);
    fence_regs4(fp);
    uint32_t zr[8], zi[8], wr[8], wi[8];
#pragma unroll
    for (int h = 0; h < 2; ++h) {
        uint32_t yr[4], yi[4];
#pragma unroll
        for (int r = 0; r < 4; ++r) { yr[r] = pack_bf16(xu[r][2 * h], xu[r][2 * h + 1]); yi[r] = pack_bf16(xu[r][4 + 2 * h], xu[r][5 + 2 * h]); }
        const uint32_t u0r = hadd(yr[0], yr[2]), u0i = hadd(yi[0], yi[2]), u1r = hsub(yr[0], yr[2]), u1i = hsub(yi[0], yi[2]);
        const uint32_t v0r = hadd(yr[1], yr[3]), v0i = hadd(yi[1], yi[3]), v1r = hsub(yr[1], yr[3]), v1i = hsub(yi[1], yi[3]);
        zr[h] = hadd(u0r, v0r); zi[h] = hadd(u0i, v0i); zr[4 + h] = hsub(u0r, v0r); zi[4 + h] = hsub(u0i, v0i);
        zr[2 + h] = hadd(u1r, v1i); zi[2 + h] = hsub(u1i, v1r); zr[6 + h] = hsub(u1r, v1i); zi[6 + h] = hadd(u1i, v1r);
    }
#pragma unroll
    for (int q = 0; q < 8; ++q) {
        wr[q] = hfma(zr[q], tw.r[q], hmul(zi[q], tw.n[q]));
        wi[q] = hfma(zr[q], tw.i[q], hmul(zi[q], tw.r[q]));
    }
    if (SECOND) named_bar(bar, 128);
    stsm_x4(wre, hadd(wr[0], wr[1]), hadd(wr[2], wr[3]), hadd(wr[4], wr[5]), hadd(wr[6], wr[7]));
    stsm_x4(wre + 512, hsub(wi[1], wi[0]), hsub(wi[3], wi[2]), hsub(wi[5], wi[4]), hsub(wi[7], wi[6]));
    stsm_x4(wim, hsub(wr[1], wr[0]), hsub(wr[3], wr[2]), hsub(wr[5], wr[4]), hsub(wr[7], wr[6]));
    stsm_x4(wim + 512, hadd(wi[0], wi[1]), hadd(wi[2], wi[3]), hadd(wi[4], wi[5]), hadd(wi[6], wi[7]));
}
template <class G>
__device__ __forceinline__ void conv_pair(float (&dE)[32], float (&dO)[32], const Twiddle& tw, uint32_t dd, uint32_t tlo, uint32_t u0, uint32_t un,
                                          uint32_t lo, int BAR, G before_next) {
    conv_channel<false>(dE, dO, tw, bf_lo(dd), tlo, desc_lo(u0 + 4096, 8192), u0 + lo, u0 + 8192 + lo, BAR, []() {});
    wgmma_wait<0>();
    fence_regs(dE); fence_regs(dO);
    conv_channel<true>(dE, dO, tw, bf_hi(dd), tlo, un == u0 ? 0 : desc_lo(un, 8192), u0 + 4096 + lo, u0 + 12288 + lo, BAR, before_next);
    fence_async_smem();
    named_bar(BAR, 128);
    float ye[16], yo[16];
    wgmma_fence();
    const uint32_t wlo = desc_lo(u0, 4096);
    wgmma_n32_tt<0, 1>(ye, wlo, tlo + 256);
    wgmma_n32_tt<0, -1>(yo, wlo + 512, tlo + 256 + 4);
#pragma unroll
    for (int k = 1; k < 4; ++k) {
        wgmma_n32_tt<1, 1>(ye, wlo + 64 * k, tlo + 256 + 128 * k);
        wgmma_n32_tt<1, -1>(yo, wlo + 512 + 64 * k, tlo + 256 + 4 + 128 * k);
    }
    wgmma_commit();
    wgmma_wait<0>();
    fence_regs(ye); fence_regs(yo);
    fence_regs(dE); fence_regs(dO);
    named_bar(BAR, 128);
    const int t = fresh_tid();
    const uint32_t ya = u0 + (t & 64) * 64 + (t & 31) * 64 + (((((t >> 4) & 2) ^ (t >> 1)) & 3) << 4);
#pragma unroll
    for (int h = 0; h < 2; ++h) {
        stsm_x4_t(ya ^ (16 * h), pack_bf16(ye[2 * h], ye[2 * h + 1]), pack_bf16(ye[4 + 2 * h], ye[5 + 2 * h]),
                  pack_bf16(ye[8 + 2 * h], ye[9 + 2 * h]), pack_bf16(ye[12 + 2 * h], ye[13 + 2 * h]));
        stsm_x4_t((ya ^ (16 * h)) + 2048, pack_bf16(yo[2 * h], yo[2 * h + 1]), pack_bf16(yo[4 + 2 * h], yo[5 + 2 * h]),
                  pack_bf16(yo[8 + 2 * h], yo[9 + 2 * h]), pack_bf16(yo[12 + 2 * h], yo[13 + 2 * h]));
    }
    fence_async_smem();
    __syncwarp();
}
}

namespace {

constexpr int S_LEN = 2048;
constexpr int D_DIM = 1024;

#define REG_P 24
#define REG_AB 168
#define REG_C 152
#define SKEW1 4
#define SKEW2 6
#define QD 4
#define QKB 18
#define QD2 6
#define SLOT4 16
#define SLOT5 27
#define EPF 2
#define PFD 7
#define TK_PF0 0
#define TK_KV0 2
#define TK_KV1 4
#define TK_C 8
#define GAP_PF 300
#define GAP_KV 50
#define GAP_ST 50
#define GAP_CV 100
#define GAP_HB 100
#define GAP_Y 100
#define GAP_X 150
#define ALTMAP 0

__device__ __align__(1024) __nv_bfloat16 g_H[2 * D_DIM * S_LEN];
__device__ __align__(1024) __nv_bfloat16 g_y2[D_DIM * S_LEN];
__device__ __align__(1024) __nv_bfloat16 g_kvT[D_DIM * S_LEN];
__device__ __align__(128) float g_gate[S_LEN];
__device__ __align__(128) unsigned long long g_agg[8 * D_DIM];
__device__ __align__(128) unsigned int g_cnt[56 * 32];

#define STAMP(k, s) do { } while (0)
#define SAMPLE(i) do { } while (0)

__device__ __forceinline__ void tma_store_5d(const CUtensorMap* map, uint32_t src, int c0, int c1, int c2, int c3, int c4) {
    asm volatile("cp.async.bulk.tensor.5d.global.shared::cta.bulk_group [%0, {%2, %3, %4, %5, %6}], [%1];"
                 ::"l"((uint64_t)map), "r"(src), "r"(c0), "r"(c1), "r"(c2), "r"(c3), "r"(c4) : "memory");
}
#define ELECT "{\n.reg .pred p;\nelect.sync _|p, 0xffffffff;\n@p "
__device__ __forceinline__ void e_expect_tx(uint32_t bar, uint32_t bytes) {
    asm volatile(ELECT "mbarrier.arrive.expect_tx.shared::cta.b64 _, [%0], %1;\n}" ::"r"(bar), "r"(bytes) : "memory");
}
__device__ __forceinline__ void e_arrive(uint32_t bar) {
    asm volatile(ELECT "mbarrier.arrive.shared::cta.b64 _, [%0];\n}" ::"r"(bar) : "memory");
}
__device__ __forceinline__ void e_load_4d(uint32_t dst, const CUtensorMap* map, uint32_t bar, int c0, int c1, int c2, int c3) {
    asm volatile(ELECT "cp.async.bulk.tensor.4d.shared::cluster.global.mbarrier::complete_tx::bytes [%0], [%1, {%3, %4, %5, %6}], [%2];\n}"
        ::"r"(dst), "l"((uint64_t)map), "r"(bar), "r"(c0), "r"(c1), "r"(c2), "r"(c3) : "memory");
}
__device__ __forceinline__ void e_load_5d(uint32_t dst, const CUtensorMap* map, uint32_t bar, int c0, int c1, int c2, int c3, int c4) {
    asm volatile(ELECT "cp.async.bulk.tensor.5d.shared::cluster.global.mbarrier::complete_tx::bytes [%0], [%1, {%3, %4, %5, %6, %7}], [%2];\n}"
        ::"r"(dst), "l"((uint64_t)map), "r"(bar), "r"(c0), "r"(c1), "r"(c2), "r"(c3), "r"(c4) : "memory");
}
__device__ __forceinline__ void e_bulk_load(uint32_t dst, const void* src, uint32_t bytes, uint32_t bar) {
    asm volatile(ELECT "cp.async.bulk.shared::cluster.global.mbarrier::complete_tx::bytes [%0], [%1], %2, [%3];\n}"
                 ::"r"(dst), "l"(src), "r"(bytes), "r"(bar) : "memory");
}
__device__ __forceinline__ void l2_prefetch(const void* p, uint32_t bytes) {
    asm volatile("cp.async.bulk.prefetch.L2.global [%0], %1;" ::"l"(p), "r"(bytes) : "memory");
}
__device__ __forceinline__ void l2_prefetch_4d(const CUtensorMap* map, int c0, int c1, int c2, int c3) {
    asm volatile("cp.async.bulk.prefetch.tensor.4d.L2.global [%0, {%1, %2, %3, %4}];" ::"l"((uint64_t)map), "r"(c0), "r"(c1), "r"(c2), "r"(c3) : "memory");
}
__device__ __forceinline__ void l2_prefetch_5d(const CUtensorMap* map, int c0, int c1, int c2, int c3, int c4) {
    asm volatile("cp.async.bulk.prefetch.tensor.5d.L2.global [%0, {%1, %2, %3, %4, %5}];" ::"l"((uint64_t)map), "r"(c0), "r"(c1), "r"(c2), "r"(c3), "r"(c4) : "memory");
}
__device__ __forceinline__ unsigned int ld_relaxed(const unsigned int* p) {
    unsigned int v;
    asm volatile("ld.relaxed.gpu.global.u32 %0, [%1];" : "=r"(v) : "l"(p) : "memory");
    return v;
}
__device__ __forceinline__ void fence_async_global() { asm volatile("fence.proxy.async.global;" ::: "memory"); }
__device__ __forceinline__ void wait_counter(const unsigned int* p, unsigned int target) {
    unsigned int v;
    int it = 0;
    do { asm volatile("ld.acquire.gpu.global.u32 %0, [%1];" : "=r"(v) : "l"(p) : "memory"); } while (v != target && ++it < (1 << 22));
    fence_async_global();
}
__device__ __forceinline__ void red_release(unsigned int* p, unsigned int n) {
    asm volatile("red.release.gpu.global.add.u32 [%0], %1;" ::"l"(p), "r"(n) : "memory");
}
__device__ __forceinline__ uint4 ldg128(const void* p) {
    uint4 v;
    asm volatile("ld.global.nc.v4.u32 {%0,%1,%2,%3}, [%4];" : "=r"(v.x), "=r"(v.y), "=r"(v.z), "=r"(v.w) : "l"(p));
    return v;
}
__device__ __forceinline__ void stg128(void* p, uint32_t a, uint32_t b, uint32_t c, uint32_t d) {
    asm volatile("st.global.v4.b32 [%0], {%1, %2, %3, %4};" ::"l"(p), "r"(a), "r"(b), "r"(c), "r"(d) : "memory");
}

template <int TA>
__device__ __forceinline__ void wgmma_n128(float (&d)[64], uint32_t alo, uint32_t blo, int acc) {
    asm volatile(
        "{\n.reg .pred p;\n.reg .b64 da, db;\nsetp.ne.b32 p, %67, 0;\nmov.b64 da, {%64, %69};\nmov.b64 db, {%65, %66};\n"
        "wgmma.mma_async.sync.aligned.m64n128k16.f32.bf16.bf16 "
        "{%0, %1, %2, %3, %4, %5, %6, %7, %8, %9, %10, %11, %12, %13, %14, %15, "
        "%16, %17, %18, %19, %20, %21, %22, %23, %24, %25, %26, %27, %28, %29, %30, %31, "
        "%32, %33, %34, %35, %36, %37, %38, %39, %40, %41, %42, %43, %44, %45, %46, %47, "
        "%48, %49, %50, %51, %52, %53, %54, %55, %56, %57, %58, %59, %60, %61, %62, %63}, "
        "da, db, p, 1, 1, %68, 0;\n"
        "}\n"
        : R8(d, 0), R8(d, 8), R8(d, 16), R8(d, 24), R8(d, 32), R8(d, 40), R8(d, 48), R8(d, 56)
        : "r"(alo), "r"(blo), "n"(HI128), "r"(acc), "n"(TA), "n"(TA ? HI64 : HI128));
}

constexpr int NST = 6;
constexpr int XTRA = SKEW1 - 4;
static_assert(SKEW1 >= 4 && SKEW1 <= 12, "skew");
constexpr int OFF_BB = 4 * 32768;
constexpr int OFF_CT = 5 * 32768;
constexpr int OFF_CU = OFF_CT + 32768;
__host__ __device__ constexpr uint32_t conv_buf(int p) { return OFF_CT + 16384 + (p == 3 ? 0 : p) * 16384; }
constexpr int OFF_PAR = OFF_CU + 32768;
constexpr int OFF_BAR = OFF_PAR + 2048;
constexpr int SMEM_BYTES = OFF_BAR + 896;
static_assert(SMEM_BYTES <= 232448, "smem layout");

struct Ring { unsigned long long w[2]; };
constexpr Ring make_ring() {
    Ring r{};
    int st = 0, uses[NST] = {};
    for (int kb = 0; kb < 32; ++kb) {
        r.w[kb >> 4] |= (unsigned long long)(st | (uses[st]++ & 1) << 3) << (4 * (kb & 15));
        if (++st >= (kb + 1 < SLOT4 ? 4 : kb + 1 < SLOT5 ? 5 : 6)) st = 0;
    }
    return r;
}
constexpr unsigned long long RING0 = make_ring().w[0], RING1 = make_ring().w[1];
__host__ __device__ constexpr uint32_t ring_code(int kb) { return (uint32_t)((kb < 16 ? RING0 : RING1) >> (4 * (kb & 15))) & 15u; }
__host__ __device__ constexpr int ring_slot(int kb) { return ring_code(kb) & 7; }
__host__ __device__ constexpr uint32_t ring_par(int kb) { return ring_code(kb) >> 3; }
constexpr int OFF_O1 = SLOT5 < 32 ? ring_slot(SKEW2 == 6 ? 26 : 31 - SKEW2) * 32768 : OFF_CT;

struct Maps {
    CUtensorMap x5, b4, cre, cim, sk, yt, yt3, out, kvst, bre, bim;
};

__device__ __forceinline__ void cmul(float& r, float& i, float ar, float ai, float br, float bi) {
    const float a = ar * br - ai * bi, b = ar * bi + ai * br;
    r = a; i = b;
}
__device__ __forceinline__ void csqr(float& r, float& i) { const float a = r * r - i * i, b = 2.f * r * i; r = a; i = b; }
__device__ __forceinline__ float after(float v, float dep) { return __float_as_uint(dep) == 0x7fedcba9u ? dep : v; }

template <int BMODE>
__global__ void __launch_bounds__(512, 1)
fused_kernel(const __nv_bfloat16* __restrict__ x, const __nv_bfloat16* __restrict__ b_re, const __nv_bfloat16* __restrict__ b_im,
             const __nv_bfloat16* __restrict__ kin, const __nv_bfloat16* __restrict__ vin, const __nv_bfloat16* __restrict__ ssm_k,
             const __nv_bfloat16* __restrict__ shift_k, const __nv_bfloat16* __restrict__ ssm_D,
             const __nv_bfloat16* __restrict__ lam_re, const __nv_bfloat16* __restrict__ lam_im,
             const __nv_bfloat16* __restrict__ log_dt, const __nv_bfloat16* __restrict__ gate_w,
             const __nv_bfloat16* __restrict__ dskip,
             const __nv_bfloat16* __restrict__ c_re, const __nv_bfloat16* __restrict__ c_im,
             const __grid_constant__ Maps maps) {
    constexpr bool MERGED = BMODE != 0, SW = BMODE == 2;
    extern __shared__ __align__(1024) unsigned char smem_raw[];
    const uint32_t sbase = smem_u32(smem_raw);
    const uint32_t bar_full = sbase + OFF_BAR;
    const uint32_t bar_empty = bar_full + 32;
    const uint32_t bar_full2 = bar_empty + 32;
    const uint32_t bar_empty2 = bar_full2 + 48;
    const uint32_t bar_k = bar_empty2 + 48;
    const uint32_t bar_tab = bar_k + 32;
    const uint32_t bar_ab = bar_tab + 8;
    const uint32_t bar_adone = bar_ab + 8;
    const uint32_t bar_par = bar_adone + 8;
    const uint32_t bar_y = bar_par + 8;
    const uint32_t bar_rel = bar_y + 8;
    const uint32_t bar_kvrel = bar_rel + 8;
    const uint32_t bar_yrel = bar_kvrel + 8;
    const uint32_t bar_y1 = bar_yrel + 8;
    const uint32_t bar_fh = bar_y1 + 8;
    const uint32_t bar_o1 = bar_fh + 8;
    const uint32_t bar_tick = bar_o1 + 8;
    const uint32_t bar_stg = bar_tick + 104;
    const uint32_t bar_bias = bar_stg + 112;
    const uint32_t bar_hw = bar_bias + 16;
    const uint32_t bar_gate = bar_hw + 8;
    const uint32_t bar_g2 = bar_gate + 8;
    const uint32_t w_bid = bar_full + 600, w_dsk = bar_full + 608, w_ones = bar_full + 640;
    const int tid = threadIdx.x ^ (((threadIdx.x + 128) & 256) ? 0 : 384);
    if (tid == 384) { prefetch_map(&maps.x5); prefetch_map(&maps.b4); }
    if (EPF && (threadIdx.x >> 5) - 1u < EPF && blockIdx.x < 128) {
        const int ln = threadIdx.x & 31;
        const __nv_bfloat16* p = ln < 16 ? x + (size_t)(blockIdx.x * 16 + ln) * D_DIM : ((ln & 8) ? b_im : b_re) + (size_t)(blockIdx.x * 8 + (ln & 7)) * D_DIM;
        asm volatile("prefetch.global.L2 [%0];" ::"l"(p + ((threadIdx.x >> 5) - 1) * 64) : "memory");
    }
    int bid;
    {
        unsigned int sm, nsm;
        asm volatile("mov.u32 %0, %smid;" : "=r"(sm));
        asm volatile("mov.u32 %0, %nsmid;" : "=r"(nsm));
        const int tpc = sm >> 1, q7 = ((tpc - 32) * 37) >> 8;
        const int gp = tpc < 32 ? tpc & 7 : tpc < 60 ? tpc - 31 - 7 * q7 : 0;
        const int ix = tpc < 32 ? tpc >> 3 : tpc < 60 ? q7 + 4 : ALTMAP ? (tpc - 56) ^ 2 : tpc - 58;
        bid = (ALTMAP ? tpc >= 64 : (tpc | 1) == 61) ? 128 : (4 * (gp >> 1) + (ix >> 1)) * 8 + 4 * (gp & 1) + 2 * (ix & 1) + (sm & 1);
        if (gridDim.x != 132 || nsm != 132) bid = blockIdx.x;
    }
    const int tt = bid >> 3, dt = bid & 7;
    const int ti = tt >> 1;
    const int cg = (dt >> 2) * 8 + (tt & 1) * 4 + (dt & 3);
    if (MERGED && threadIdx.x == 0 && bid < 128) {
        mbar_init(bar_full, 1);
        asm volatile("fence.mbarrier_init.release.cluster;" ::: "memory");
        mbar_expect_tx(bar_full, 49152);
        tma_load_4d(sbase + OFF_CU, &maps.b4, bar_full, 0, 0, 0, cg * 4);
        tma_load_5d(sbase + ((0 - XTRA) & 3) * 32768, &maps.x5, bar_full, 0, 0, 0, 0, ti);
        tma_load_4d(sbase + OFF_BB, &maps.b4, bar_full, 0, 0, 0, 64 + cg * 4);
    }
    __syncwarp();
    const int warp = __shfl_sync(0xffffffffu, tid >> 5, 0), wg = warp >> 2, lane = tid & 31;
    if (warp == 12 && bid < 128) {
        if (lane == 0) {
#pragma unroll
            for (int s = MERGED; s < 4; ++s) mbar_init(bar_full + 8 * s, 1);
            asm volatile("fence.mbarrier_init.release.cluster;" ::: "memory");
        }
        __syncwarp();
        asm volatile("bar.arrive 4, 512;" ::: "memory");
        if (MERGED) {
#pragma unroll 1
            for (int it = 1; it < 4; ++it) {
                e_expect_tx(bar_full + 8 * it, 49152);
                e_load_4d(sbase + OFF_CU + it * 8192, &maps.b4, bar_full + 8 * it, it * 64, 0, 0, cg * 4);
                e_load_5d(sbase + ((it - XTRA) & 3) * 32768, &maps.x5, bar_full + 8 * it, it * 64, 0, 0, 0, ti);
                e_load_4d(sbase + OFF_BB + it * 8192, &maps.b4, bar_full + 8 * it, it * 64, 0, 0, 64 + cg * 4);
            }
        }
    }
    if (bid >= 128) {
        if (tid == 0) {
            __nanosleep(2000);
            const unsigned int target = (ld_relaxed(&g_cnt[32 * 32]) & ~63u) + 64u;
            for (int i = 0; i < 8; ++i)
                for (int it = 0; ld_relaxed(&g_cnt[(40 + i) * 32]) != target && it < (1 << 12); ++it) __nanosleep(500);
        }
        return;
    }
    if (wg == 0) {
        asm volatile("setmaxnreg.dec.sync.aligned.u32 %0;" ::"n"(REG_P));
        if (tid == 32) {
            if (sbase & 1023) __trap();
#pragma unroll
            for (int s = 0; s < 4; ++s) mbar_init(bar_empty + 8 * s, 2);
#pragma unroll
            for (int s = 0; s < NST; ++s) { mbar_init(bar_full2 + 8 * s, 1); mbar_init(bar_empty2 + 8 * s, 1); }
            mbar_init(bar_k, 1); mbar_init(bar_k + 8, 1); mbar_init(bar_k + 16, 1); mbar_init(bar_k + 24, 1);
            mbar_init(bar_tab, 1);
            mbar_init(bar_ab, 1);
            mbar_init(bar_adone, 4);
            mbar_init(bar_par, 2);
            asm volatile("fence.mbarrier_init.release.cluster;" ::: "memory");
        } else if (tid == 64) {
#pragma unroll
            for (int s = 0; s < 20; ++s) mbar_init(bar_y + 8 * s, 1);
        } else if (tid == 96) {
#pragma unroll
            for (int s = 0; s < 11; ++s) mbar_init(bar_stg + 8 * s, 4);
        } else if (tid == 0) {
#pragma unroll
            for (int s = 11; s < 19; ++s) mbar_init(bar_stg + 8 * s, 4);
            asm volatile("st.shared.b32 [%0], %1;" ::"r"(w_bid), "r"(bid) : "memory");
        }
        __syncwarp();
        asm volatile("bar.sync 4, 512;" ::: "memory");
        if (warp == 0) {
#pragma unroll 1
            for (int it = MERGED ? 4 : 0; it < 16 + XTRA; ++it) {
                const int st = it & 3, kb = it < 16 ? it : it - SKEW1;
                const bool fa = it < 16, fb = it < 16 - SKEW1 || it >= 12;
                const uint32_t bf = bar_full + 8 * st;
                mbar_wait(bar_empty + 8 * st, ((it >> 2) & 1) ^ 1);
                e_expect_tx(bf, fa && fb ? 49152 : 40960);
                e_load_5d(sbase + ((it - XTRA) & 3) * 32768, &maps.x5, bf, kb * 64, 0, 0, 0, ti);
                if (MERGED) {
                    if (fa) e_load_4d(sbase + OFF_CU + st * 8192, &maps.b4, bf, kb * 64, 0, 0, cg * 4);
                    if (fb) e_load_4d(sbase + OFF_BB + st * 8192, &maps.b4, bf, kb * 64, 0, 0, 64 + cg * 4);
                } else {
                    if (lane < 16 && ((lane & 8) ? fb : fa))
                        tma_load_2d(sbase + ((lane & 8) ? OFF_BB : OFF_CU) + st * 8192 + (lane & 7) * 1024, (lane & 1) ? &maps.bim : &maps.bre, bf,
                                    kb * 64, (lane >> 3) * 512 + cg * 32 + ((lane & 7) >> 1) * 8);
                    __syncwarp();
                }
                if (it >= 4 && it < 16) e_arrive(bar_tick + 8 * (it - 3));
                if (lane == 0) STAMP(1, 16 + it);
                if (lane == 0 && it < 16) SAMPLE(it - 3);
            }
#pragma unroll 1
            for (int kb = 0; kb < 32; ++kb) {
                const int st = ring_slot(kb);
                const uint32_t bf = bar_full2 + 8 * st;
                mbar_wait(bar_empty2 + 8 * st, ring_par(kb));
                e_expect_tx(bf, 32768);
                e_load_5d(sbase + st * 32768 + 16384, &maps.cre + ((kb >> 3) & 1), bf, ((kb >> 4) * 8 + (kb & 7)) * 64, 0, 0, 0, dt * 4);
                if (lane == 0) STAMP(2, 16 + kb);
                if (lane == 0 && (kb & 3) == 0) SAMPLE(13 + (kb >> 2));
            }
        } else if (warp == 1) {
            if (MERGED && PFD && lane == 0) {
#pragma unroll 1
                for (int n = -1; n + PFD < 16; ++n) {
                    if (n >= 0) mbar_wait(bar_tick + 8 * n, 0);
                    if (cg >= 4 && (cg < 6 ? -1 : max(cg - PFD, 0)) == n) l2_prefetch_5d(&maps.x5, cg * 64, 0, 0, 0, ti);
                    if (ti >= 2 && (ti < 3 ? -1 : max(2 * ti - PFD, 0)) == n) {
#pragma unroll 1
                        for (int i = 0; i < 4; ++i) l2_prefetch_4d(&maps.b4, (2 * ti + (i >> 1)) * 64, 0, 0, (i & 1) * 64 + cg * 4);
                    }
                }
            }
            __syncwarp();
            const char* hp = reinterpret_cast<const char*>(g_H) + (size_t)tt * 262144;
            mbar_wait(bar_adone, 0);
            e_expect_tx(bar_k + 8, 16384);
            e_expect_tx(bar_k + 16, 16384);
#pragma unroll 1
            for (int c = 2; c < 6; ++c) {
                e_load_4d(sbase + conv_buf(0) + (c >> 1) * 16384 + (c & 1) * 4096 + 8192, &maps.sk, bar_k + 8 * (c >> 1), 0, 0, 0, bid * 8 + c);
                if (GAP_CV) __nanosleep(GAP_CV);
            }
            mbar_wait(bar_kvrel, 0);
            const unsigned int target = lds32(w_bid + 4);
            mbar_wait(bar_rel, 0);
#pragma unroll 1
            for (int q = 0; q < 2; ++q) {
                if (lane == 0) STAMP(0, 8 + 4 * q);
                if (q == 0) wait_counter(&g_cnt[(2 * ti) * 32], target);
                else { mbar_wait(bar_fh, 0); fence_async_global(); }
                if (lane == 0) STAMP(0, 9 + 4 * q);
#pragma unroll 1
                for (int kb = 0; kb < 16; ++kb) {
                    const int st = ring_slot(16 * q + kb);
                    mbar_wait(bar_empty2 + 8 * st, ring_par(16 * q + kb));
                    e_bulk_load(sbase + st * 32768, hp + kb * 16384, 16384, bar_full2 + 8 * st);
                }
                hp += 4194304;
            }
        } else if (warp == 2) {
            if (lane == 0) {
                mbar_wait(bar_tick + 8, 0);
                const unsigned int target = (ld_relaxed(&g_cnt[(40 + dt) * 32]) & ~63u) + 64u;
                asm volatile("st.shared.b32 [%0], %1;" ::"r"(w_bid + 4), "r"(target) : "memory");
                prefetch_map(&maps.kvst); prefetch_map(&maps.sk);
#pragma unroll 1
                for (int bt = 0; bt < 2; ++bt) {
                    mbar_wait(bar_stg + 8 * bt, 0);
#pragma unroll 1
                    for (int i = 0; i < 4; ++i) {
                        if (i) __nanosleep(GAP_ST);
                        tma_store_3d(&maps.kvst, sbase + OFF_CT + bt * 16384 + i * 4096, (tt & 1) * 1024 + ti * 128 + 64 * bt, dt * 16, 2 * i);
                    }
                    bulk_commit();
                }
                bulk_wait0();
                fence_async_global();
                red_release(&g_cnt[(40 + dt) * 32], 4);
                mbar_arrive(bar_kvrel);
                STAMP(0, 23);
                mbar_expect_tx(bar_tab, 12288);
                bulk_load(sbase + OFF_CT, &g_conv_tab, 12288, bar_tab);
                mbar_expect_tx(bar_k, 16384);
                tma_load_4d(sbase + conv_buf(0) + 8192, &maps.sk, bar_k, 0, 0, 0, bid * 8);
                tma_load_4d(sbase + conv_buf(0) + 12288, &maps.sk, bar_k, 0, 0, 0, bid * 8 + 1);
                wait_counter(&g_cnt[(40 + (bid >> 4)) * 32], target);
                STAMP(0, 19);
#pragma unroll 1
                for (int p = 0; p < 3; ++p) {
                    if (p == 1) mbar_wait(bar_adone, 0);
                    bulk_load(sbase + conv_buf(p), g_kvT + (size_t)(bid * 8 + 2 * p) * 2048, 8192, bar_k + 8 * p);
                    if (GAP_CV) __nanosleep(GAP_CV);
                }
                prefetch_map(&maps.out); prefetch_map(&maps.yt); prefetch_map(&maps.yt3);
#pragma unroll 1
                for (int p = 0; p < 4; ++p) {
                    mbar_wait(bar_stg + 16 + 8 * p, 0);
                    if (p == 0) {
                        mbar_expect_tx(bar_k + 24, 16384);
                        tma_load_4d(sbase + conv_buf(3) + 8192, &maps.sk, bar_k + 24, 0, 0, 0, bid * 8 + 6);
                        mbar_wait(bar_g2, 0);
                        tma_load_4d(sbase + conv_buf(3) + 12288, &maps.sk, bar_k + 24, 0, 0, 0, bid * 8 + 7);
                    }
#pragma unroll 1
                    for (int i = 0; i < 2; ++i) {
                        if (i) __nanosleep(GAP_Y);
                        asm volatile("cp.async.bulk.global.shared::cta.bulk_group [%0], [%1], 4096;"
                                     ::"l"(g_y2 + (size_t)(bid * 8 + 2 * p + i) * 2048), "r"(sbase + conv_buf(p) + i * 4096) : "memory");
                    }
                    bulk_commit();
                    STAMP(0, 24 + p);
                    if (p == 0) {
                        bulk_wait_read0();
                        bulk_load(sbase + conv_buf(3), g_kvT + (size_t)(bid * 8 + 6) * 2048, 8192, bar_k + 24);
                    }
                    if (p == 2) {
                        bulk_wait0();
                        fence_async_global();
                        red_release(&g_cnt[(48 + (bid >> 4)) * 32], 4);
                        mbar_arrive(bar_yrel);
                        STAMP(0, 3);
                    }
                }
                bulk_wait0();
                mbar_arrive(bar_empty2 + 40);
                fence_async_global();
                red_release(&g_cnt[(32 + (bid >> 4)) * 32], 4);
                STAMP(0, 2);
                wait_counter(&g_cnt[(32 + dt) * 32], target);
                STAMP(0, 5);
                mbar_expect_tx(bar_y, 8192);
#pragma unroll 1
                for (int i = 6; i < 8; ++i)
                    tma_load_5d(sbase + OFF_CU + i * 4096, &maps.yt, bar_y, (tt & 1) * 1024 + ti * 128 + (i & 1) * 64, 0, 0, i >> 1, dt * 4);
#pragma unroll 1
                for (int i = 0; i < 8; ++i) {
                    mbar_wait(bar_stg + 48 + 8 * i, 0);
                    tma_store_5d(&maps.out, sbase + ((i & 4) ? OFF_O1 : OFF_CU) + (i & 3) * 8192, dt * 128 + (i & 3) * 32, 0, 0, (tt & 1) * 4 + ((i & 4) >> 1), ti);
                    bulk_commit();
                }
                bulk_wait_read0();
                STAMP(2, 3);
                SAMPLE(21);
            }
        } else if (lane == 0) {
            mbar_wait(bar_tick + 8 * TK_PF0, 0);
#pragma unroll 1
            for (int i = 0; i < 8; ++i) {
                l2_prefetch(((i & 1) ? vin : kin) + (size_t)(ti * 256 + 32 * (i & 4) + (bid & 15) * 8 + 2 * (i & 2)) * D_DIM, 8192);
                __nanosleep(GAP_PF);
            }
            if (bid < 3) l2_prefetch(reinterpret_cast<const char*>(&g_conv_tab) + bid * 4096, 4096);
            prefetch_map(&maps.cre); prefetch_map(&maps.cim);
            mbar_wait(bar_tick + 8 * TK_C, 0);
#pragma unroll 1
            for (int i = 0; i < 8; ++i) {
                l2_prefetch((i & 1) ? ((i & 4) ? c_im : c_re) + (size_t)bid * 8192 + (i & 2) * 2048 : ssm_k + (size_t)bid * 16384 + (i >> 1) * 4096, 8192);
                __nanosleep(GAP_PF);
            }
            const unsigned int target = (ld_relaxed(&g_cnt[(2 * ti + 1) * 32]) & ~63u) + 64u;
            mbar_wait(bar_gate, 0);
            mbar_wait(bar_hw, 0);
            mbar_wait(bar_g2, 0);
            char* hp = reinterpret_cast<char*>(g_H) + (size_t)((16 + 2 * ti) * 16 + (cg >> 1)) * 16384 + (cg & 1) * 2048;
#pragma unroll 1
            for (int i = 0; i < 16; ++i) {
                asm volatile("cp.async.bulk.global.shared::cta.bulk_group [%0], [%1], 2048;"
                             ::"l"(hp + (i & 3) * 4096 + ((i >> 2) & 1) * 262144 + (i >> 3) * 131072), "r"(sbase + OFF_BB + i * 2048) : "memory");
                __nanosleep(GAP_HB);
            }
            bulk_commit();
            bulk_wait0();
            mbar_arrive(bar_empty2 + 32);
            fence_async_global();
            red_release(&g_cnt[(2 * ti + 1) * 32], 4);
            STAMP(0, 38);
            wait_counter(&g_cnt[(2 * ti + 1) * 32], target);
            mbar_arrive(bar_fh);
        }
    } else {
    if (wg == 3) {
        if (warp != 12) asm volatile("bar.sync 4, 512;" ::: "memory");
        named_bar(3, 128);
        asm volatile("setmaxnreg.inc.sync.aligned.u32 %0;" ::"n"(REG_C));
        const int t = tid & 127, w4 = t >> 5;
        if (t == 0) SAMPLE(0);
        mbar_wait(bar_tick, 0);
        if (t < 64) {
            const int ch = (t >> 5) * 512 + cg * 32 + (t & 31);
            unsigned long long oldagg;
            asm volatile("ld.relaxed.gpu.global.u64 %0, [%1];" : "=l"(oldagg) : "l"(&g_agg[ti * D_DIM + ch]) : "memory");
            const float Lr = __bfloat162float(lam_re[ch]), Li = __bfloat162float(lam_im[ch]);
            const float dtv = bf16r(expf(__bfloat162float(log_dt[ch])));
            const unsigned int tag = ((((unsigned int)oldagg & 1u) | ((unsigned int)(oldagg >> 31) & 2u)) + 1u) & 3u;
            const float er = expf(dtv * Lr);
            float s, c;
            sincospif(dtv * Li * 0.318309886183790672f, &s, &c);
            const float lr = er * c, li = er * s;
            const float nr = lr - 1.f, ni = li;
            const float den = Lr * Lr + Li * Li;
            const float cr = 2.f * (nr * Lr + ni * Li) / den, ci = 2.f * (ni * Lr - nr * Li) / den;
            float pr = lr, pi = -li;
#pragma unroll
            for (int i = 0; i < 5; ++i) csqr(pr, pi);
            sts128(sbase + OFF_PAR + t * 32, __float_as_uint(lr), __float_as_uint(-li), __float_as_uint(cr), __float_as_uint(ci));
            sts128(sbase + OFF_PAR + t * 32 + 16, __float_as_uint(pr), __float_as_uint(pi), tag, 0);
            __syncwarp();
            if (lane == 0) mbar_arrive(bar_par);
        }
        if (t >= 120) asm volatile("st.shared.b32 [%0], %1;" ::"r"(w_dsk - 480 + 4 * t),
                                   "r"(t < 124 ? __ldg(reinterpret_cast<const uint32_t*>(ssm_D + bid * 8) + (t & 3)) : 0u) : "memory");
        if (t < 64) asm volatile("st.shared.b32 [%0], %1;" ::"r"(w_ones + 4 * t), "r"(0x3F803F80u) : "memory");
        {
            const int cq = lane & 15, rg = (lane >> 4) + 2 * w4;
            uint32_t sk[4][4];
#pragma unroll
            for (int c = 0; c < 4; ++c) {
                const uint4 w = ldg128(shift_k + (size_t)(dt * 128 + 8 * cq + 2 * c) * 4);
                sk[0][c] = __byte_perm(w.x, w.z, 0x5410); sk[1][c] = __byte_perm(w.x, w.z, 0x7632);
                sk[2][c] = __byte_perm(w.y, w.w, 0x5410); sk[3][c] = __byte_perm(w.y, w.w, 0x7632);
            }
#pragma unroll 1
            for (int bt = 0; bt < 2; ++bt) {
                const int t0 = ti * 256 + 128 * bt + 16 * (rg & 4) + 32 * (tt & 1) + 8 * (rg & 3);
                mbar_wait(bar_tick + 8 * (bt ? TK_KV1 : TK_KV0), 0);
                if (t == 0) STAMP(0, 30 + 3 * bt);
                uint4 kk[11], vv[8];
                const __nv_bfloat16* kp = kin + (size_t)t0 * D_DIM + dt * 128 + 8 * cq;
                const __nv_bfloat16* vp = vin + (size_t)t0 * D_DIM + dt * 128 + 8 * cq;
#pragma unroll
                for (int i = 0; i < 11; ++i) {
                    if (i < 3 && t0 == 0) kk[i] = make_uint4(0, 0, 0, 0);
                    else kk[i] = ldg128(kp + (i - 3) * D_DIM);
                    if (i == 6 || i == 10) __nanosleep(GAP_KV);
                }
#pragma unroll
                for (int i = 0; i < 8; ++i) { vv[i] = ldg128(vp + i * D_DIM); if (i == 3) __nanosleep(GAP_KV); }
                const uint32_t ua = sbase + OFF_CT + bt * 16384 + cq * 128 + ((rg ^ ((2 * ti + bt) & 3) ^ (cq & 7)) << 4);
#pragma unroll
                for (int c = 0; c < 4; ++c) {
                    uint32_t res[8];
#pragma unroll
                    for (int i = 0; i < 8; ++i) {
                        uint32_t ks = hmul((&kk[i].x)[c], sk[3][c]);
                        ks = hadd(ks, hmul((&kk[i + 1].x)[c], sk[2][c]));
                        ks = hadd(ks, hmul((&kk[i + 2].x)[c], sk[1][c]));
                        ks = hadd(ks, hmul((&kk[i + 3].x)[c], sk[0][c]));
                        res[i] = hmul(ks, (&vv[i].x)[c]);
                    }
                    sts128(ua + (2 * c) * 2048, __byte_perm(res[0], res[1], 0x5410), __byte_perm(res[2], res[3], 0x5410),
                           __byte_perm(res[4], res[5], 0x5410), __byte_perm(res[6], res[7], 0x5410));
                    sts128(ua + (2 * c + 1) * 2048, __byte_perm(res[0], res[1], 0x7632), __byte_perm(res[2], res[3], 0x7632),
                           __byte_perm(res[4], res[5], 0x7632), __byte_perm(res[6], res[7], 0x7632));
                }
                fence_async_smem();
                __syncwarp();
                if (lane == 0) mbar_arrive(bar_stg + 8 * bt);
                if (t == 0) STAMP(0, 21 + bt);
            }
        }
        {
            const int row = bid * 16 + (t >> 3);
            uint4 xv[16];
#pragma unroll
            for (int n = 0; n < 16; ++n) {
                xv[n] = ldg128(x + (size_t)row * D_DIM + ((t & 7) + 8 * n) * 8);
                if ((n & 3) == 3) __nanosleep(GAP_KV);
            }
#pragma unroll
            for (int n8 = 0; n8 < 16; n8 += 8) {
                uint4 wv[8];
#pragma unroll
                for (int n = 0; n < 8; ++n) wv[n] = ldg128(gate_w + ((t & 7) + 8 * (n8 + n)) * 8);
#pragma unroll
                for (int n = 0; n < 8; ++n) {
                    uint4& p = xv[n8 + n];
                    p.x = hmul(p.x, wv[n].x); p.y = hmul(p.y, wv[n].y); p.z = hmul(p.z, wv[n].z); p.w = hmul(p.w, wv[n].w);
                }
            }
            float d[4] = {0.f, 0.f, 0.f, 0.f};
            fence_regs(d);
            named_bar(3, 128);
            wgmma_fence();
#pragma unroll
            for (int n = 0; n < 16; ++n)
                asm volatile("{\n.reg .b64 db;\nmov.b64 db, {%8, 8};\n"
                             "wgmma.mma_async.sync.aligned.m64n8k16.f32.bf16.bf16 {%0, %1, %2, %3}, {%4, %5, %6, %7}, db, 1, 1, 1, 0;\n}\n"
                             : "+f"(d[0]), "+f"(d[1]), "+f"(d[2]), "+f"(d[3]) : "r"(xv[n].x), "r"(xv[n].y), "r"(xv[n].z), "r"(xv[n].w), "r"(desc_lo(w_ones, 128)));
            wgmma_commit();
            wgmma_wait<0>();
            fence_regs(d);
#pragma unroll
            for (int n = 0; n < 16; ++n) asm volatile("" ::"r"(xv[n].x), "r"(xv[n].y), "r"(xv[n].z), "r"(xv[n].w) : "memory");
            float sum = d[0] + d[2];
            sum += __shfl_xor_sync(0xffffffffu, sum, 4);
            if ((t & 7) == 0) g_gate[row] = bf16r(1.f / (1.f + expf(-bf16r(sum))));
            if (t == 0) STAMP(0, 4);
            __syncwarp();
            if (lane == 0) mbar_arrive(bar_gate);
        }
    } else {
        asm volatile("setmaxnreg.inc.sync.aligned.u32 %0;" ::"n"(REG_AB));
        if (tid == 128) STAMP(1, 54);
        asm volatile("bar.sync 4, 512;" ::: "memory");
        if (tid == 128) STAMP(1, 55);
        const int cw = wg - 1;
        const int t = tid & 127, w4 = t >> 5, g = lane >> 2, t4 = lane & 3;
        {
            float a0[64], a1[64];
            auto release = [&](int it) {
                if (it < 12 + XTRA && t <= ((it >= 16 - SKEW1 && it < 12) || it >= 16)) mbar_arrive(bar_empty + 8 * (it & 3));
            };
#pragma unroll 1
            for (int kb = 0; kb < 16; ++kb) {
                const int it = cw == 1 && kb >= 16 - SKEW1 ? kb + XTRA : kb, st = it & 3;
                if (cw == 1 && kb == 16 - SKEW1) mbar_wait(bar_ab, 0);
                mbar_wait(bar_full + 8 * st, (it >> 2) & 1);
                if (kb == 0 && tid == 288) mbar_arrive(bar_tick);
                if (kb == 0 && t == 0) STAMP(1, 14 + cw);
                const uint32_t alo = desc_lo(sbase + (cw ? OFF_BB : OFF_CU) + st * 8192, 16), blo = desc_lo(sbase + ((it - XTRA) & 3) * 32768, 16);
                wgmma_fence();
#pragma unroll
                for (int k = 0; k < 4; ++k) {
                    wgmma_n128<0>(a0, alo + 2 * k, blo + 2 * k, k ? 1 : kb);
                    wgmma_n128<0>(a1, alo + 2 * k, blo + 1024 + 2 * k, k ? 1 : kb);
                }
                wgmma_commit();
                wgmma_wait<1>();
                if (kb > 0 && !(cw == 1 && kb == 16 - SKEW1)) release(it - 1);
                if (cw == 1 && kb == 15 - SKEW1) {
                    wgmma_wait<0>();
                    release(it);
                }
                if (cw == 1 && kb > 12) {
                    if (kb == 13) mbar_wait(bar_adone, 0);
                    if (t == 0) mbar_arrive(bar_empty2 + 8 * (kb - 13));
                }
            }
            if (tid == 192) mbar_arrive(bar_ab);
            float mr, mi, cr, ci, p32r, p32i;
            uint32_t tag;
            mbar_wait(bar_par, 0);
            {
                const uint32_t par = sbase + OFF_PAR + (cw * 32 + w4 * 8 + g) * 32;
                uint32_t dummy;
                asm volatile("ld.shared.v4.f32 {%0,%1,%2,%3}, [%4];" : "=f"(mr), "=f"(mi), "=f"(cr), "=f"(ci) : "r"(par));
                asm volatile("ld.shared.v4.b32 {%0,%1,%2,%3}, [%4];" : "=f"(p32r), "=f"(p32i), "=r"(tag), "=r"(dummy) : "r"(par + 16));
            }
            const float l1i = SW ? mi : -mi;
            auto map = [&](float p, float q, float& r, float& i) {
                if (SW) { r = fmaf(cr, q, -ci * p); i = fmaf(-cr, p, -ci * q); }
                else { r = fmaf(cr, p, -ci * q); i = fmaf(-cr, q, -ci * p); }
            };
            float p64r = p32r, p64i = p32i;
            csqr(p64r, p64i);
            float p128r = p64r, p128i = p64i;
            csqr(p128r, p128i);
            wgmma_wait<0>();
            fence_regs(a0); fence_regs(a1);
            if (cw == 0) { release(15); if (lane == 0) mbar_arrive(bar_adone); }
            else if (t == 0) mbar_arrive(bar_empty2 + 24);
            if (t == 0) STAMP(1, 2 + 6 * cw);
            float hr = 0.f, hi = 0.f, ar = 0.f, ai = 0.f;
#pragma unroll
            for (int j = 0; j < 16; ++j)
#pragma unroll
                for (int e = 0; e < 2; ++e) {
                    const float nr = fmaf(mr, ar, fmaf(-l1i, ai, a0[4 * j + e])), ni = fmaf(mr, ai, fmaf(l1i, ar, a0[4 * j + 2 + e]));
                    const float or_ = fmaf(mr, hr, fmaf(-l1i, hi, a1[4 * j + e])), oi = fmaf(mr, hi, fmaf(l1i, hr, a1[2 + 4 * j + e]));
                    ar = nr; ai = ni; hr = or_; hi = oi;
                }
            map(ar, ai, ar, ai);
            map(hr, hi, hr, hi);
            hr += p32r * ar - p32i * ai; hi += p32r * ai + p32i * ar;
            {
                float vr = __shfl_up_sync(0xffffffffu, hr, 1, 4), vi = __shfl_up_sync(0xffffffffu, hi, 1, 4);
                if (t4 >= 1) { hr += p64r * vr - p64i * vi; hi += p64r * vi + p64i * vr; }
                vr = __shfl_up_sync(0xffffffffu, hr, 2, 4); vi = __shfl_up_sync(0xffffffffu, hi, 2, 4);
                if (t4 >= 2) { hr += p128r * vr - p128i * vi; hi += p128r * vi + p128i * vr; }
            }
            unsigned long long* ap = &g_agg[ti * D_DIM + cw * 512 + cg * 32 + w4 * 8 + g];
            if (t4 == 3) asm volatile("{\n.reg .b64 a;\nmov.b64 a, {%1, %2};\nst.relaxed.gpu.global.u64 [%0], a;\n}\n" ::"l"(ap),
                                      "r"((__float_as_uint(hr) & ~1u) | (tag & 1u)), "r"((__float_as_uint(hi) & ~1u) | (tag >> 1)) : "memory");
            float exr = __shfl_up_sync(0xffffffffu, hr, 1, 4), exi = __shfl_up_sync(0xffffffffu, hi, 1, 4);
            if (t4 == 0) { exr = 0.f; exi = 0.f; }
            if (t == 0) STAMP(1, 3 + 6 * cw);
            ci = after(ci, exr);
#pragma unroll
            for (int j = 0; j < 16; ++j)
#pragma unroll
                for (int e = 0; e < 2; ++e) {
                    map(a0[4 * j + e], a0[4 * j + 2 + e], a0[4 * j + e], a0[4 * j + 2 + e]);
                    map(a1[4 * j + e], a1[4 * j + 2 + e], a1[4 * j + e], a1[4 * j + 2 + e]);
                }
            float qr = 1.f, qi = 0.f, ur = 1.f, ui = 0.f;
            if (t4 & 1) { qr = p64r; qi = p64i; }
            if (t4 & 2) cmul(qr, qi, qr, qi, p128r, p128i);
            csqr(p128r, p128i);
            if (t4 & 1) { ur = p128r; ui = p128i; }
            csqr(p128r, p128i);
            if (t4 & 2) cmul(ur, ui, ur, ui, p128r, p128i);
            csqr(p128r, p128i);
            fence_regs(a0); fence_regs(a1);
            if (t == 0) STAMP(1, 7 + 6 * cw);
            if (ti > 0) {
                const unsigned long long tmask = 0x0000000100000001ull, tval = ((unsigned long long)(tag >> 1) << 32) | (tag & 1u);
                unsigned long long u0 = tval, u1 = tval;
                ap -= D_DIM * (1 + t4);
                int it = 0;
                do {
                    asm volatile("{\n.reg .pred p, q;\nsetp.gt.s32 p, %3, 0;\nsetp.gt.s32 q, %3, 4;\n@p ld.relaxed.gpu.global.u64 %0, [%2];\n"
                                 "@q ld.relaxed.gpu.global.u64 %1, [%2+-32768];\n}\n" : "+l"(u0), "+l"(u1) : "l"(ap), "r"(ti - t4) : "memory");
                } while (__any_sync(0xffffffffu, (((u0 ^ tval) | (u1 ^ tval)) & tmask) != 0) && ++it < (1 << 22));
                float Pr = __uint_as_float((unsigned)u1 & ~1u), Pi = __uint_as_float((unsigned)(u1 >> 32) & ~1u);
                cmul(Pr, Pi, Pr, Pi, p128r, p128i);
                Pr += __uint_as_float((unsigned)u0 & ~1u); Pi += __uint_as_float((unsigned)(u0 >> 32) & ~1u);
                cmul(Pr, Pi, Pr, Pi, ur, ui);
                Pr += __shfl_xor_sync(0xffffffffu, Pr, 1); Pi += __shfl_xor_sync(0xffffffffu, Pi, 1);
                Pr += __shfl_xor_sync(0xffffffffu, Pr, 2); Pi += __shfl_xor_sync(0xffffffffu, Pi, 2);
                exr += qr * Pr - qi * Pi;
                exi += qr * Pi + qi * Pr;
            }
            if (t == 0) STAMP(1, 4 + 6 * cw);
            char* hp = reinterpret_cast<char*>(g_H) + (size_t)((2 * ti) * 16 + (cg >> 1)) * 16384 + ((cg & 1) * 32 + w4 * 8 + g) * 64 + ((t4 ^ (g >> 1)) << 4);
            float fxr = ar + p32r * exr - p32i * exi, fxi = ai + p32r * exi + p32i * exr;
            const uint32_t hs = sbase + OFF_BB + (w4 * 8 + g) * 64 + ((t4 ^ (g >> 1)) << 4);
            if (cw == 1) named_bar(2, 128);
#pragma unroll
            for (int jj = 0; jj < 4; ++jj) {
                uint32_t pr[4], qq[4], pi[4], qi[4];
#pragma unroll
                for (int j4 = 0; j4 < 4; ++j4) {
                    const int j = jj * 4 + j4;
                    const float r0 = fmaf(mr, exr, fmaf(-mi, exi, a0[4 * j])), i0 = fmaf(mr, exi, fmaf(mi, exr, a0[4 * j + 2]));
                    const float r1 = fmaf(mr, fxr, fmaf(-mi, fxi, a1[4 * j])), i1 = fmaf(mr, fxi, fmaf(mi, fxr, a1[2 + 4 * j]));
                    exr = fmaf(mr, r0, fmaf(-mi, i0, a0[4 * j + 1]));
                    exi = fmaf(mr, i0, fmaf(mi, r0, a0[4 * j + 3]));
                    fxr = fmaf(mr, r1, fmaf(-mi, i1, a1[1 + 4 * j]));
                    fxi = fmaf(mr, i1, fmaf(mi, r1, a1[3 + 4 * j]));
                    pr[j4] = pack_bf16(r0, exr); pi[j4] = pack_bf16(i0, exi);
                    qq[j4] = pack_bf16(r1, fxr); qi[j4] = pack_bf16(i1, fxi);
                }
                if (cw == 0) {
                    stg128(hp + jj * 4096, pr[0], pr[1], pr[2], pr[3]);
                    stg128(hp + jj * 4096 + 262144, qq[0], qq[1], qq[2], qq[3]);
                    stg128(hp + jj * 4096 + 131072, pi[0], pi[1], pi[2], pi[3]);
                    stg128(hp + jj * 4096 + 393216, qi[0], qi[1], qi[2], qi[3]);
                } else {
                    sts128(hs + jj * 2048, pr[0], pr[1], pr[2], pr[3]);
                    sts128(hs + jj * 2048 + 8192, qq[0], qq[1], qq[2], qq[3]);
                    sts128(hs + jj * 2048 + 16384, pi[0], pi[1], pi[2], pi[3]);
                    sts128(hs + jj * 2048 + 24576, qi[0], qi[1], qi[2], qi[3]);
                }
            }
            if (t == 0) STAMP(1, 5 + 6 * cw);
            if (cw == 0) {
                named_bar(1, 128);
                if (t == 0) { red_release(&g_cnt[(2 * ti) * 32], 4); mbar_arrive(bar_rel); }
                if (t == 0) STAMP(1, 6);
                __syncwarp();
            } else {
                fence_async_smem();
                __syncwarp();
                if (lane == 0) mbar_arrive(bar_hw);
            }
            if (t == 0) STAMP(1, 50 + cw);
        }
        if (cw == 0) {
            float c0[64], c1[64];
            int pst = 0;
            auto kblock = [&](int kb, auto shallow) {
                const int t = fresh_tid() & 127, lane = t & 31;
                const int st = ring_slot(kb);
                mbar_wait(bar_full2 + 8 * st, ring_par(kb));
                if (kb == 0 && t == 0) STAMP(2, 6);
                if (kb == 0 && lane == 0) mbar_arrive(bar_g2);
                const uint32_t alo = desc_lo(sbase + st * 32768, 4096), blo = desc_lo(sbase + st * 32768 + 16384, 16);
                constexpr int Q = decltype(shallow)::value;
#pragma unroll
                for (int j = 0; j < 8; ++j) {
                    wgmma_fence();
                    if (j & 1) wgmma_n128<1>(c1, alo + 512 + 64 * (j >> 1), blo + 2 * (j >> 1), j >> 1 ? 1 : kb);
                    else wgmma_n128<1>(c0, alo + 64 * (j >> 1), blo + 2 * (j >> 1), j >> 1 ? 1 : kb);
                    wgmma_commit();
                    wgmma_wait<Q>();
                    if (j == Q - 1 && kb > 0 && t == 0) mbar_arrive(bar_empty2 + 8 * pst);
                }
                pst = st;
            };
#pragma unroll 1
            for (int kb = 0; kb < QKB; ++kb) kblock(kb, std::integral_constant<int, QD>());
#pragma unroll 1
            for (int kb = QKB; kb < 32 - SKEW2; ++kb) kblock(kb, std::integral_constant<int, QD2>());
            static_assert(SKEW2 <= (SLOT5 < 32 ? 6 : 4), "slot release");
            const uint32_t alo = desc_lo(sbase, 4096), blo = desc_lo(sbase + 16384, 16);
#pragma unroll
            for (int kb = 32 - SKEW2; kb < 32; ++kb) {
                mbar_wait(bar_full2 + 8 * ring_slot(kb), ring_par(kb));
                wgmma_fence();
#pragma unroll
                for (int k = 0; k < 4; ++k) wgmma_n128<1>(c0, alo + ring_slot(kb) * 2048 + 64 * k, blo + ring_slot(kb) * 2048 + 2 * k, 1);
                wgmma_commit();
                if (SLOT5 < 32 && SKEW2 < 6 && kb == 33 - SKEW2) {
                    wgmma_wait<2>();
                    if ((fresh_tid() & 127) == 0) mbar_arrive(bar_o1);
                }
                if (SKEW2 == 6 && kb == 26) {
                    wgmma_wait<1>();
                    if ((fresh_tid() & 127) == 0) mbar_arrive(bar_empty2 + 8 * ring_slot(25));
                }
            }
            auto late = [&](int kb) {
                wgmma_fence();
#pragma unroll
                for (int k = 0; k < 4; ++k) wgmma_n128<1>(c1, alo + 512 + ring_slot(kb) * 2048 + 64 * k, blo + ring_slot(kb) * 2048 + 2 * k, 1);
                wgmma_commit();
            };
            late(32 - SKEW2);
            const int t = fresh_tid() & 127, lane = t & 31, w4 = t >> 5, g = lane >> 2, t4 = lane & 3;
            auto epilogue = [&](const float (&a)[64], int b) {
                const uint32_t ad0 = sbase + (b ? OFF_O1 : OFF_CU) + (w4 * 16 + g) * 128 + (((2 * t4) ^ g) << 4);
                float gt[2];
                uint32_t bv[4][4];
#pragma unroll
                for (int h = 0; h < 2; ++h) gt[h] = __uint_as_float(lds32(sbase + OFF_PAR + (64 * b + 16 * w4 + 8 * h + g) * 4));
#pragma unroll
                for (int i = 0; i < 4; ++i)
                    asm volatile("ld.shared.v4.b32 {%0,%1,%2,%3}, [%4];" : "=r"(bv[i][0]), "=r"(bv[i][1]), "=r"(bv[i][2]), "=r"(bv[i][3])
                                 : "r"(ad0 + (i & 1) * 1024 + (i >> 1) * 8192) : "memory");
                if (b == 0) wgmma_wait<1>(); else wgmma_wait<0>();
                if (b == 0) fence_regs(c0); else fence_regs(c1);
                if (t == 0) STAMP(2, b ? 2 : 5);
#pragma unroll
                for (int jq = 0; jq < 4; ++jq) {
#pragma unroll
                    for (int h = 0; h < 2; ++h) {
                        const uint32_t ad = ad0 + h * 1024 + jq * 8192;
                        uint32_t (&w)[4] = bv[2 * (jq & 1) + h];
                        const int r = 16 * jq + 2 * h;
                        sts128(ad, __float_as_uint(fmaf(gt[h], a[r], bf_lo(w[0]))), __float_as_uint(fmaf(gt[h], a[r + 1], bf_hi(w[0]))),
                               __float_as_uint(fmaf(gt[h], a[r + 4], bf_lo(w[1]))), __float_as_uint(fmaf(gt[h], a[r + 5], bf_hi(w[1]))));
                        sts128(ad ^ 16, __float_as_uint(fmaf(gt[h], a[r + 8], bf_lo(w[2]))), __float_as_uint(fmaf(gt[h], a[r + 9], bf_hi(w[2]))),
                               __float_as_uint(fmaf(gt[h], a[r + 12], bf_lo(w[3]))), __float_as_uint(fmaf(gt[h], a[r + 13], bf_hi(w[3]))));
                        if (jq < 2) asm volatile("ld.shared.v4.b32 {%0,%1,%2,%3}, [%4];" : "=r"(w[0]), "=r"(w[1]), "=r"(w[2]), "=r"(w[3]) : "r"(ad + 16384) : "memory");
                    }
                    fence_async_smem();
                    __syncwarp();
                    if (lane == 0) mbar_arrive(bar_stg + 48 + 32 * b + 8 * jq);
                    if (b == 0 && jq < SKEW2 - 1) late(33 - SKEW2 + jq);
                    if (SKEW2 == 6 && b == 0 && jq == 0) {
                        wgmma_wait<1>();
                        if (t == 0) mbar_arrive(bar_o1);
                    }
                    if (SKEW2 == 6 && b == 0 && jq == 3) late(31);
                }
            };
            mbar_wait(bar_bias, 0);
            if (t == 0) STAMP(2, 4);
            epilogue(c0, 0);
            mbar_wait(bar_bias + 8, 0);
            epilogue(c1, 1);
            if (t == 0) STAMP(2, 7);
            return;
        }
        asm volatile("setmaxnreg.dec.sync.aligned.u32 %0;" ::"n"(REG_C));
    }
    {
        {
            const int t = fresh_tid() & 127, lane = t & 31, w4 = t >> 5;
            Twiddle tw;
            load_twiddle(tw, reinterpret_cast<const uint4*>(g_tw_tab.w) + t);
            const uint32_t lo = (uint32_t)((16 * w4 + (lane & 7)) * 64 + (((lane >> 3) ^ ((lane >> 1) & 3)) << 4));
            const uint32_t tlo = desc_lo(sbase + OFF_CT, 16);
            float dE[32], dO[32];
            int p = wg == 2 ? 2 : 0;
            mbar_wait(bar_stg, 0);
            mbar_wait(bar_tab, 0);
            mbar_wait(bar_k + 8 * p, 0);
            if (t == 0) STAMP(0, wg == 2 ? 50 : 1);
            wgmma_fence();
            conv_s1(dE, dO, tlo, desc_lo(sbase + conv_buf(0) + p * 16384, 8192));
            wgmma_commit();
            wgmma_wait<0>();
            fence_regs(dE); fence_regs(dO);
            named_bar(wg, 128);
#pragma unroll 1
            for (; p < 4; p = 2 * p + 1) {
                const int pn = p < 2 ? 2 * p + 1 : p;
                if (t == 0) STAMP(0, 40 + 2 * p);
                conv_pair(dE, dO, tw, lds32(w_dsk + ((lane & 3) ? 16 : 4 * p)), tlo, sbase + conv_buf(p), sbase + conv_buf(pn), lo, wg,
                                [&]() { mbar_wait(bar_k + 8 * pn, 0); });
                if (lane == 0) mbar_arrive(bar_stg + 16 + 8 * p);
            }
            if (t == 0) STAMP(0, 57 + wg);
            __syncwarp();
        }
        if (wg == 2) {
            {
            const int t = fresh_tid() & 127, lane = t & 31, w4 = t >> 5, g = lane >> 2, t4 = lane & 3;
            const int bid = lds32(w_bid), dt = bid & 7;
            const int trow = (bid >> 4) * 256 + 4 * (bid & 8) + 128 * (w4 & 1) + 8 * (w4 >> 1) + g;
            uint4 xv[16], dk[4];
            const __nv_bfloat16* xp = x + (size_t)trow * D_DIM + dt * 128 + 8 * t4;
#pragma unroll
            for (int i = 0; i < 16; ++i) {
                xv[i] = ldg128(xp + (size_t)(16 * (i >> 3) + 64 * ((i >> 2) & 1)) * D_DIM + 32 * (i & 3));
                if (i & 1) __nanosleep(GAP_X);
            }
#pragma unroll
            for (int jq = 0; jq < 4; ++jq) dk[jq] = ldg128(dskip + dt * 128 + 32 * jq + 8 * t4);
            mbar_wait(bar_fh, 0);
            uint32_t omg[4], g2[4];
#pragma unroll
            for (int i = 0; i < 4; ++i) {
                const float gt = __ldcg(g_gate + trow + 16 * (i >> 1) + 64 * (i & 1));
                if (t4 == 0) asm volatile("st.shared.f32 [%0], %1;" ::"r"(sbase + OFF_PAR + (64 * (i >> 1) + 16 * w4 + 8 * (i & 1) + g) * 4), "f"(gt) : "memory");
                omg[i] = pack_bf16(2.f - 2.f * gt, 2.f - 2.f * gt); g2[i] = pack_bf16(gt, gt);
            }
            if (t == 0) {
                mbar_wait(bar_yrel, 0);
                wait_counter(&g_cnt[(48 + dt) * 32], lds32(w_bid + 4));
                STAMP(0, 16);
                mbar_expect_tx(bar_y1, 24576);
                tma_load_5d(sbase + OFF_CU, &maps.yt3, bar_y1, (bid & 8) * 128 + (bid >> 4) * 128, 0, 0, 0, dt * 4);
                tma_load_5d(sbase + OFF_CU + 12288, &maps.yt3, bar_y1, (bid & 8) * 128 + (bid >> 4) * 128 + 64, 0, 0, 0, dt * 4);
            }
            __syncwarp();
            uint32_t ya = sbase + OFF_CU + (w4 & 1) * 12288 + (lane >> 3) * 3072 + (lane & 7) * 128 + ((((w4 >> 1) ^ ((bid >> 3 & 2) + (w4 & 1))) ^ (lane & 7)) << 4);
            mbar_wait(bar_y1, 0);
            if (t == 0) STAMP(0, 18);
#pragma unroll
            for (int p = 0; p < 3; ++p)
#pragma unroll
                for (int i = 0; i < 4; ++i) {
                    uint32_t yw[4];
                    ldsm_x4_t(yw[0], yw[1], yw[2], yw[3], (ya ^ ((i & 1) << 6) ^ ((i & 2) << 4)) + p * 1024);
#pragma unroll
                    for (int jq = 0; jq < 4; ++jq) {
                        uint32_t& w = (&xv[4 * i + jq].x)[p];
                        w = hfma(g2[i], hmul(w, (&dk[jq].x)[p]), hmul(omg[i], hmul(w, yw[jq])));
                    }
                }
            uint32_t xd[16], yw[16];
#pragma unroll
            for (int i = 0; i < 16; ++i) { xd[i] = hmul(xv[i].w, dk[i & 3].w); asm volatile("" : "+r"(xd[i]), "+r"(xv[i].x), "+r"(xv[i].y), "+r"(xv[i].z)); }
            if (t == 0) STAMP(0, 17);
            ya += 24576 - (w4 & 1) * 8192 - (lane >> 3) * 2048;
            mbar_wait(bar_y, 0);
            if (t == 0) STAMP(0, 6);
#pragma unroll
            for (int i = 0; i < 4; ++i) ldsm_x4_t(yw[4 * i], yw[4 * i + 1], yw[4 * i + 2], yw[4 * i + 3], ya ^ ((i & 1) << 6) ^ ((i & 2) << 4));
            named_bar(2, 128);
#pragma unroll
            for (int i = 0; i < 16; ++i) {
                if (SLOT5 < 32 && i == 8) mbar_wait(bar_o1, 0);
                sts128(sbase + (i & 8 ? OFF_O1 : OFF_CU) + (i & 3) * 8192 + (w4 * 16 + g + (i & 4) * 2) * 128 + (((2 * t4) ^ g) << 4), xv[i].x, xv[i].y, xv[i].z,
                       hfma(g2[i >> 2], xd[i], hmul(omg[i >> 2], hmul(xv[i].w, yw[i]))));
                if ((i & 7) == 7) {
                    __syncwarp();
                    if (lane == 0) mbar_arrive(bar_bias + (i & 8));
                }
            }
            if (t == 0) STAMP(0, 7);
            }
        }
    }
    }
}

void make_map(CUtensorMap* m, const void* ptr, int rank, const cuuint64_t* dims, const cuuint64_t* strides, const cuuint32_t* box,
              CUtensorMapSwizzle swz, bool f32 = false) {
    cuuint32_t es[5] = {1, 1, 1, 1, 1};
    get_encode()(m, f32 ? CU_TENSOR_MAP_DATA_TYPE_FLOAT32 : CU_TENSOR_MAP_DATA_TYPE_BFLOAT16, rank, const_cast<void*>(ptr), dims, strides, box, es,
                 CU_TENSOR_MAP_INTERLEAVE_NONE, swz, CU_TENSOR_MAP_L2_PROMOTION_L2_256B, CU_TENSOR_MAP_FLOAT_OOB_FILL_NONE);
}
void make_map_2d(CUtensorMap* m, const void* ptr, uint64_t inner, uint64_t outer, uint32_t box_in, uint32_t box_out) {
    cuuint64_t dims[2] = {inner, outer};
    cuuint64_t strides[1] = {inner * 2};
    cuuint32_t box[2] = {box_in, box_out};
    make_map(m, ptr, 2, dims, strides, box, CU_TENSOR_MAP_SWIZZLE_128B);
}
void make_map_conv(CUtensorMap* m, const void* p, uint32_t nch = 2) {
    cuuint64_t dims[4] = {32, 32, 2, 1024};
    cuuint64_t strides[3] = {128, 64, 4096};
    cuuint32_t box[4] = {32, 32, 2, nch};
    make_map(m, p, 4, dims, strides, box, CU_TENSOR_MAP_SWIZZLE_64B);
}

}

extern "C" void kernel_launch(void* const* d_in, const int* in_sizes, int n_in, void* d_out, int out_size) {
    const __nv_bfloat16* x = (const __nv_bfloat16*)d_in[0];
    const __nv_bfloat16* lam_re = (const __nv_bfloat16*)d_in[1];
    const __nv_bfloat16* lam_im = (const __nv_bfloat16*)d_in[2];
    const __nv_bfloat16* b_re = (const __nv_bfloat16*)d_in[3];
    const __nv_bfloat16* b_im = (const __nv_bfloat16*)d_in[4];
    const __nv_bfloat16* c_re = (const __nv_bfloat16*)d_in[5];
    const __nv_bfloat16* c_im = (const __nv_bfloat16*)d_in[6];
    const __nv_bfloat16* log_dt = (const __nv_bfloat16*)d_in[7];
    const __nv_bfloat16* dskip = (const __nv_bfloat16*)d_in[8];
    const __nv_bfloat16* kin = (const __nv_bfloat16*)d_in[10];
    const __nv_bfloat16* vin = (const __nv_bfloat16*)d_in[11];
    const __nv_bfloat16* shift_k = (const __nv_bfloat16*)d_in[12];
    const __nv_bfloat16* ssm_k = (const __nv_bfloat16*)d_in[13];
    const __nv_bfloat16* ssm_D = (const __nv_bfloat16*)d_in[14];
    const __nv_bfloat16* gate_w = (const __nv_bfloat16*)d_in[15];
    float* out = (float*)d_out;

    void *yptr = nullptr, *kvtptr = nullptr;
    cudaGetSymbolAddress(&yptr, g_y2);
    cudaGetSymbolAddress(&kvtptr, g_kvT);

    Maps maps;
    {
        cuuint64_t dims[5] = {1024, 2, 4, 32, 8};
        cuuint64_t strides[4] = {2048, 64 * 2048, 2 * 2048, 256 * 2048};
        cuuint32_t box[5] = {64, 2, 4, 32, 1};
        make_map(&maps.x5, x, 5, dims, strides, box, CU_TENSOR_MAP_SWIZZLE_128B);
    }
    int bmode = 0;
    {
        const uint64_t a = (uint64_t)b_re, b = (uint64_t)b_im;
        const uint64_t delta = a < b ? b - a : a - b;
        if (delta != 0 && (delta & 15) == 0 && delta < (1ull << 40)) bmode = a < b ? 1 : 2;
        cuuint64_t dims[4] = {1024, 8, 2, 128};
        cuuint64_t strides[3] = {2048, bmode ? delta : 16, 16384};
        cuuint32_t box[4] = {64, 8, 2, 4};
        make_map(&maps.b4, a < b ? b_re : b_im, 4, dims, strides, box, CU_TENSOR_MAP_SWIZZLE_128B);
    }
    make_map_2d(&maps.bre, b_re, 1024, 1024, 64, 8);
    make_map_2d(&maps.bim, b_im, 1024, 1024, 64, 8);
    {
        cuuint64_t dims[3] = {S_LEN, 128, 8};
        cuuint64_t strides[2] = {8 * 4096, 4096};
        cuuint32_t box[3] = {64, 16, 2};
        make_map(&maps.kvst, kvtptr, 3, dims, strides, box, CU_TENSOR_MAP_SWIZZLE_128B);
    }
    make_map_conv(&maps.sk, ssm_k, 1);
    for (int i = 0; i < 2; ++i) {
        cuuint64_t dims[5] = {1024, 2, 4, 4, 32};
        cuuint64_t strides[4] = {2048, 8 * 2048, 2 * 2048, 32 * 2048};
        cuuint32_t box[5] = {64, 2, 4, 4, 4};
        make_map(i ? &maps.cim : &maps.cre, i ? c_im : c_re, 5, dims, strides, box, CU_TENSOR_MAP_SWIZZLE_128B);
    }
    {
        cuuint64_t dims[5] = {S_LEN, 2, 4, 4, 32};
        cuuint64_t strides[4] = {4096, 8 * 4096, 2 * 4096, 32 * 4096};
        cuuint32_t box[5] = {64, 2, 4, 1, 4};
        make_map(&maps.yt, yptr, 5, dims, strides, box, CU_TENSOR_MAP_SWIZZLE_128B);
        box[3] = 3;
        make_map(&maps.yt3, yptr, 5, dims, strides, box, CU_TENSOR_MAP_SWIZZLE_128B);
    }
    {
        cuuint64_t dims[5] = {D_DIM, 8, 4, 8, 8};
        cuuint64_t strides[4] = {4096, 64 * 4096, 8 * 4096, 256 * 4096};
        cuuint32_t box[5] = {32, 8, 4, 2, 1};
        make_map(&maps.out, out, 5, dims, strides, box, CU_TENSOR_MAP_SWIZZLE_128B, true);
    }

    auto kern = bmode == 1 ? fused_kernel<1> : bmode == 2 ? fused_kernel<2> : fused_kernel<0>;
    cudaFuncSetAttribute(kern, cudaFuncAttributeMaxDynamicSharedMemorySize, SMEM_BYTES);
    static int grid = 0;
    if (!grid) {
        int dev = 0, sms = 0;
        cudaGetDevice(&dev);
        cudaDeviceGetAttribute(&sms, cudaDevAttrMultiProcessorCount, dev);
        grid = sms == 132 ? 132 : 128;
    }
    kern<<<grid, 512, SMEM_BYTES>>>(x, b_re, b_im, kin, vin, ssm_k, shift_k, ssm_D, lam_re, lam_im, log_dt, gate_w, dskip, c_re, c_im, maps);
}
```

```cpp
#include <cuda_runtime.h>
#include <cuda_bf16.h>
#include <cuda.h>
#include <stdint.h>
#include <type_traits>

namespace {
__device__ __forceinline__ uint32_t smem_u32(const void* p) { return (uint32_t)__cvta_generic_to_shared(p); }
__device__ __forceinline__ void mbar_init(uint32_t bar, uint32_t count) {
    asm volatile("mbarrier.init.shared::cta.b64 [%0], %1;" ::"r"(bar), "r"(count) : "memory");
}
__device__ __forceinline__ void mbar_expect_tx(uint32_t bar, uint32_t bytes) {
    asm volatile("mbarrier.arrive.expect_tx.shared::cta.b64 _, [%0], %1;" ::"r"(bar), "r"(bytes) : "memory");
}
__device__ __forceinline__ void mbar_arrive(uint32_t bar) {
    asm volatile("mbarrier.arrive.shared::cta.b64 _, [%0];" ::"r"(bar) : "memory");
}
__device__ __forceinline__ void mbar_wait(uint32_t bar, uint32_t parity) {
    asm volatile(
        "{\n"
        ".reg .pred p;\n"
        ".reg .u32 n;\n"
        "mov.u32 n, 0;\n"
        "LAB_WAIT:\n"
        "mbarrier.try_wait.parity.shared::cta.b64 p, [%0], %1;\n"
        "@p bra LAB_DONE;\n"
        "add.u32 n, n, 1;\n"
        "setp.lt.u32 p, n, 0x400000;\n"
        "@p bra LAB_WAIT;\n"
        "trap;\n"
        "LAB_DONE:\n"
        "}\n" ::"r"(bar), "r"(parity) : "memory");
}
__device__ __forceinline__ void tma_load_2d(uint32_t dst, const CUtensorMap* map, uint32_t bar, int c0, int c1) {
    asm volatile(
        "cp.async.bulk.tensor.2d.shared::cluster.global.mbarrier::complete_tx::bytes [%0], [%1, {%3, %4}], [%2];"
        ::"r"(dst), "l"((uint64_t)map), "r"(bar), "r"(c0), "r"(c1) : "memory");
}
__device__ __forceinline__ void tma_load_4d(uint32_t dst, const CUtensorMap* map, uint32_t bar, int c0, int c1, int c2, int c3) {
    asm volatile(
        "cp.async.bulk.tensor.4d.shared::cluster.global.mbarrier::complete_tx::bytes [%0], [%1, {%3, %4, %5, %6}], [%2];"
        ::"r"(dst), "l"((uint64_t)map), "r"(bar), "r"(c0), "r"(c1), "r"(c2), "r"(c3) : "memory");
}
__device__ __forceinline__ void tma_load_5d(uint32_t dst, const CUtensorMap* map, uint32_t bar, int c0, int c1, int c2, int c3, int c4) {
    asm volatile(
        "cp.async.bulk.tensor.5d.shared::cluster.global.mbarrier::complete_tx::bytes [%0], [%1, {%3, %4, %5, %6, %7}], [%2];"
        ::"r"(dst), "l"((uint64_t)map), "r"(bar), "r"(c0), "r"(c1), "r"(c2), "r"(c3), "r"(c4) : "memory");
}
__device__ __forceinline__ void bulk_load(uint32_t dst, const void* src, uint32_t bytes, uint32_t bar) {
    asm volatile("cp.async.bulk.shared::cluster.global.mbarrier::complete_tx::bytes [%0], [%1], %2, [%3];"
                 ::"r"(dst), "l"(src), "r"(bytes), "r"(bar) : "memory");
}
__device__ __forceinline__ void tma_store_3d(const CUtensorMap* map, uint32_t src, int c0, int c1, int c2) {
    asm volatile("cp.async.bulk.tensor.3d.global.shared::cta.bulk_group [%0, {%2, %3, %4}], [%1];"
                 ::"l"((uint64_t)map), "r"(src), "r"(c0), "r"(c1), "r"(c2) : "memory");
}
__device__ __forceinline__ void bulk_commit() { asm volatile("cp.async.bulk.commit_group;" ::: "memory"); }
__device__ __forceinline__ void bulk_wait0() { asm volatile("cp.async.bulk.wait_group 0;" ::: "memory"); }
__device__ __forceinline__ void bulk_wait_read0() { asm volatile("cp.async.bulk.wait_group.read 0;" ::: "memory"); }
__device__ __forceinline__ void fence_async_smem() { asm volatile("fence.proxy.async.shared::cta;" ::: "memory"); }
__device__ __forceinline__ void named_bar(int id, int n) { asm volatile("bar.sync %0, %1;" ::"r"(id), "r"(n) : "memory"); }
__device__ __forceinline__ void sts128(uint32_t addr, uint32_t a, uint32_t b, uint32_t c, uint32_t d) {
    asm volatile("st.shared.v4.b32 [%0], {%1, %2, %3, %4};" ::"r"(addr), "r"(a), "r"(b), "r"(c), "r"(d) : "memory");
}
__device__ __forceinline__ void prefetch_map(const CUtensorMap* m) {
    asm volatile("prefetch.tensormap [%0];" ::"l"((uint64_t)m) : "memory");
}
__device__ __forceinline__ void wgmma_fence() { asm volatile("wgmma.fence.sync.aligned;" ::: "memory"); }
__device__ __forceinline__ void wgmma_commit() { asm volatile("wgmma.commit_group.sync.aligned;" ::: "memory"); }
template <int N>
__device__ __forceinline__ void wgmma_wait() { asm volatile("wgmma.wait_group.sync.aligned %0;" ::"n"(N) : "memory"); }
template <int N>
__device__ __forceinline__ void fence_regs(float (&a)[N]) {
#pragma unroll
    for (int i = 0; i < N; ++i) asm volatile("" : "+f"(a[i])::"memory");
}
template <int N>
__device__ __forceinline__ void fence_regs(uint32_t (&a)[N]) {
#pragma unroll
    for (int i = 0; i < N; ++i) asm volatile("" : "+r"(a[i])::"memory");
}
#define R8(a, i) "+f"(a[i + 0]), "+f"(a[i + 1]), "+f"(a[i + 2]), "+f"(a[i + 3]), "+f"(a[i + 4]), "+f"(a[i + 5]), "+f"(a[i + 6]), "+f"(a[i + 7])
#define REGS32 "{%0, %1, %2, %3, %4, %5, %6, %7, %8, %9, %10, %11, %12, %13, %14, %15, %16, %17, %18, %19, %20, %21, %22, %23, %24, %25, %26, %27, %28, %29, %30, %31}"
#define REGS16 "{%0, %1, %2, %3, %4, %5, %6, %7, %8, %9, %10, %11, %12, %13, %14, %15}"

__host__ __device__ constexpr uint32_t desc_hi(uint32_t sbo, uint32_t mode) { return (sbo >> 4) | (mode << 30); }
__device__ __forceinline__ uint32_t desc_lo(uint32_t saddr, uint32_t lbo) { return ((saddr & 0x3FFFF) >> 4) | ((lbo >> 4) << 16); }
constexpr uint32_t HI128 = desc_hi(1024, 1), HI64 = desc_hi(512, 2);
#define W8(a, i) "=f"(a[i + 0]), "=f"(a[i + 1]), "=f"(a[i + 2]), "=f"(a[i + 3]), "=f"(a[i + 4]), "=f"(a[i + 5]), "=f"(a[i + 6]), "=f"(a[i + 7])
template <int TA, int TB, int ACC, uint32_t AHI, uint32_t BHI>
__device__ __forceinline__ void wgmma_n64_ss(float (&d)[32], uint32_t alo, uint32_t blo) {
#define N64_TEXT "{\n.reg .pred p;\n.reg .b64 da, db;\nsetp.ne.b32 p, %36, 0;\nmov.b64 da, {%32, %37};\nmov.b64 db, {%33, %38};\n" \
        "wgmma.mma_async.sync.aligned.m64n64k16.f32.bf16.bf16 " REGS32 ", da, db, p, 1, 1, %34, %35;\n}\n"
    if (ACC) asm volatile(N64_TEXT : R8(d, 0), R8(d, 8), R8(d, 16), R8(d, 24) : "r"(alo), "r"(blo), "n"(TA), "n"(TB), "n"(ACC), "n"(AHI), "n"(BHI));
    else asm volatile(N64_TEXT : W8(d, 0), W8(d, 8), W8(d, 16), W8(d, 24) : "r"(alo), "r"(blo), "n"(TA), "n"(TB), "n"(ACC), "n"(AHI), "n"(BHI));
}
template <int ACC, int SA>
__device__ __forceinline__ void wgmma_n32_tt(float (&d)[16], uint32_t alo, uint32_t blo) {
#define N32T_TEXT "{\n.reg .pred p;\n.reg .b64 da, db;\nsetp.ne.b32 p, %18, 0;\nmov.b64 da, {%16, %19};\nmov.b64 db, {%17, %20};\n" \
        "wgmma.mma_async.sync.aligned.m64n32k16.f32.bf16.bf16 " REGS16 ", da, db, p, %21, 1, 1, 1;\n}\n"
    if (ACC) asm volatile(N32T_TEXT : R8(d, 0), R8(d, 8) : "r"(alo), "r"(blo), "n"(ACC), "n"(HI64), "n"(HI128), "n"(SA));
    else asm volatile(N32T_TEXT : W8(d, 0), W8(d, 8) : "r"(alo), "r"(blo), "n"(ACC), "n"(HI64), "n"(HI128), "n"(SA));
}
__device__ __forceinline__ void wgmma_n16_rs(float (&d)[8], const uint32_t (&a)[4], uint32_t blo) {
    asm volatile("{\n.reg .pred p;\n.reg .b64 db;\nsetp.ne.b32 p, 0, 0;\nmov.b64 db, {%12, %13};\n"
        "wgmma.mma_async.sync.aligned.m64n16k16.f32.bf16.bf16 {%0, %1, %2, %3, %4, %5, %6, %7}, {%8, %9, %10, %11}, db, p, 1, 1, 0;\n}\n"
        : W8(d, 0) : "r"(a[0]), "r"(a[1]), "r"(a[2]), "r"(a[3]), "r"(blo), "n"(HI128));
}

__device__ __forceinline__ float bf16r(float x) { return __bfloat162float(__float2bfloat16_rn(x)); }
__device__ __forceinline__ uint32_t pack_bf16(float lo, float hi) {
    __nv_bfloat162 v = __floats2bfloat162_rn(lo, hi);
    return *reinterpret_cast<uint32_t*>(&v);
}
__device__ __forceinline__ __nv_bfloat162 as_bf2(uint32_t w) { return *reinterpret_cast<__nv_bfloat162*>(&w); }
__device__ __forceinline__ uint32_t as_u32(__nv_bfloat162 v) { return *reinterpret_cast<uint32_t*>(&v); }
__device__ __forceinline__ float bf_lo(uint32_t w) { return __uint_as_float(w << 16); }
__device__ __forceinline__ float bf_hi(uint32_t w) { return __uint_as_float(w & 0xFFFF0000u); }
__device__ __forceinline__ void ldsm_x4_t(uint32_t& r0, uint32_t& r1, uint32_t& r2, uint32_t& r3, uint32_t addr) {
    asm volatile("ldmatrix.sync.aligned.m8n8.x4.trans.shared.b16 {%0,%1,%2,%3}, [%4];"
                 : "=r"(r0), "=r"(r1), "=r"(r2), "=r"(r3) : "r"(addr) : "memory");
}
__device__ __forceinline__ void stsm_x4(uint32_t addr, uint32_t r0, uint32_t r1, uint32_t r2, uint32_t r3) {
    asm volatile("stmatrix.sync.aligned.m8n8.x4.shared.b16 [%0], {%1,%2,%3,%4};"
                 ::"r"(addr), "r"(r0), "r"(r1), "r"(r2), "r"(r3) : "memory");
}
__device__ __forceinline__ void stsm_x4_t(uint32_t addr, uint32_t r0, uint32_t r1, uint32_t r2, uint32_t r3) {
    asm volatile("stmatrix.sync.aligned.m8n8.x4.trans.shared.b16 [%0], {%1,%2,%3,%4};"
                 ::"r"(addr), "r"(r0), "r"(r1), "r"(r2), "r"(r3) : "memory");
}
__device__ __forceinline__ uint32_t lds32(uint32_t addr) {
    uint32_t v;
    asm volatile("ld.shared.b32 %0, [%1];" : "=r"(v) : "r"(addr));
    return v;
}

typedef CUresult (*EncodeFn)(CUtensorMap*, CUtensorMapDataType, cuuint32_t, void*, const cuuint64_t*, const cuuint64_t*,
                             const cuuint32_t*, const cuuint32_t*, CUtensorMapInterleave, CUtensorMapSwizzle,
                             CUtensorMapL2promotion, CUtensorMapFloatOOBfill);
EncodeFn get_encode() {
    static EncodeFn fn = nullptr;
    if (!fn) {
        void* p = nullptr;
        cudaDriverEntryPointQueryResult qres;
        cudaGetDriverEntryPoint("cuTensorMapEncodeTiled", &p, cudaEnableDefault, &qres);
        fn = (EncodeFn)p;
    }
    return fn;
}
}
namespace {
constexpr double c_pi = 3.14159265358979323846;
constexpr double c_cos256(int i) {
    i &= 255;
    if (i > 128) i = 256 - i;
    double sgn = 1.0;
    if (i > 64) { i = 128 - i; sgn = -1.0; }
    if (i == 64) return 0.0;
    double x = 2.0 * c_pi * i / 256.0, x2 = x * x, term = 1.0, sum = 1.0;
    for (int k = 1; k < 20; ++k) { term *= -x2 / ((2 * k - 1) * (2 * k)); sum += term; }
    return sgn * sum;
}
constexpr uint32_t c_bf16(double v) {
    if (v == 0.0) return 0u;
    uint32_t s = v < 0 ? 0x8000u : 0u;
    double a = v < 0 ? -v : v;
    int e = 0;
    while (a >= 2.0) { a *= 0.5; ++e; }
    while (a < 1.0) { a *= 2.0; --e; }
    int r = (int)(a * 128.0 + 0.5);
    if (r == 256) { r = 128; ++e; }
    return s | (uint32_t)((e + 127) << 7) | (uint32_t)(r - 128);
}
__host__ __device__ constexpr int conv_k1(int r) { return (r & 8) ? 63 - (((r >> 4) << 3) | (r & 7)) : (((r >> 4) << 3) | (r & 7)); }
struct ConvTab { uint32_t w[96 * 32]; };
constexpr ConvTab make_conv_tab() {
    ConvTab t{};
    uint32_t cs[256] = {};
    for (int i = 0; i < 256; ++i) cs[i] = c_bf16(c_cos256(i));
    for (int n = 0; n < 96; ++n)
        for (int c = 0; c < 64; ++c) {
            int a = 0;
            if (n < 32) {
                const int ro = (n >> 3) & 1, ri = n & 7, co = (c >> 3) & 1, ci = c & 7;
                a = n < 16 ? 8 * ci * (4 * ri + (c >> 4)) : 8 * ri * (4 * ci + (c >> 4));
                a += (ro == co) ? 0 : (ro == 0) ? 192 : 64;
            } else {
                const int r = n - 32, n1 = 2 * (c & 31) + (c >> 5);
                a = n1 * (2 * (((r >> 4) << 3) | (r & 7)) + 1) + ((r & 8) ? 64 : 0);
            }
            const int off = n * 128 + (((c >> 3) ^ (n & 7)) << 4) + (c & 7) * 2;
            t.w[off >> 2] |= cs[a & 255] << ((off & 2) * 8);
        }
    return t;
}
__device__ __align__(128) constexpr ConvTab g_conv_tab = make_conv_tab();

struct Twiddle { uint32_t r[8], i[8], n[8]; };
constexpr double c_cospi(double x) {
    double sgn = 1.0;
    if (x > 0.5) { x = 1.0 - x; sgn = -1.0; }
    const double y = c_pi * x, y2 = y * y;
    double term = 1.0, sum = 1.0;
    for (int k = 1; k < 12; ++k) { term *= -y2 / ((2 * k - 1) * (2 * k)); sum += term; }
    return sgn * sum;
}
struct TwTab { uint32_t w[3072]; };
constexpr TwTab make_tw_tab() {
    TwTab t{};
    for (int th = 0; th < 128; ++th)
        for (int q = 0; q < 8; ++q)
            for (int e = 0; e < 2; ++e) {
                const int k1 = conv_k1(16 * (th >> 5) + 8 * (q & 1) + ((th & 31) >> 2)), n2 = 8 * (q >> 1) + 2 * (th & 3) + e;
                const double x = (double)(n2 * (2 * k1 + 1)) / 4096.0;
                const double cs = c_cospi(x), sn = n2 == 0 ? 0.0 : c_cospi(x > 0.5 ? x - 0.5 : 0.5 - x);
                t.w[((q >> 2) * 128 + th) * 4 + (q & 3)] |= c_bf16(cs * 0.0625) << (16 * e);
                t.w[((2 + (q >> 2)) * 128 + th) * 4 + (q & 3)] |= c_bf16(-sn * 0.0625) << (16 * e);
                t.w[((4 + (q >> 2)) * 128 + th) * 4 + (q & 3)] |= c_bf16(sn * 0.0625) << (16 * e);
            }
    return t;
}
__device__ __align__(128) constexpr TwTab g_tw_tab = make_tw_tab();
__device__ __forceinline__ void load_twiddle(Twiddle& tw, const uint4* p) {
#pragma unroll
    for (int q = 0; q < 2; ++q) {
        const uint4 a = __ldg(p + q * 128);
        const uint4 b = __ldg(p + (2 + q) * 128);
        tw.r[4 * q] = a.x; tw.r[4 * q + 1] = a.y; tw.r[4 * q + 2] = a.z; tw.r[4 * q + 3] = a.w;
        const uint4 n = __ldg(p + (4 + q) * 128);
        tw.n[4 * q] = n.x; tw.n[4 * q + 1] = n.y; tw.n[4 * q + 2] = n.z; tw.n[4 * q + 3] = n.w;
        tw.i[4 * q] = b.x; tw.i[4 * q + 1] = b.y; tw.i[4 * q + 2] = b.z; tw.i[4 * q + 3] = b.w;
    }
}

__device__ __forceinline__ int fresh_tid() { int v; asm volatile("mov.u32 %0, %tid.x;" : "=r"(v)); return v; }
__device__ __forceinline__ uint32_t hmul(uint32_t a, uint32_t b) { return as_u32(__hmul2_rn(as_bf2(a), as_bf2(b))); }
__device__ __forceinline__ uint32_t hadd(uint32_t a, uint32_t b) { return as_u32(__hadd2_rn(as_bf2(a), as_bf2(b))); }
__device__ __forceinline__ uint32_t hsub(uint32_t a, uint32_t b) { return as_u32(__hsub2_rn(as_bf2(a), as_bf2(b))); }
__device__ __forceinline__ uint32_t hfma(uint32_t a, uint32_t b, uint32_t c) { return as_u32(__hfma2(as_bf2(a), as_bf2(b), as_bf2(c))); }

__device__ __forceinline__ void conv_dft8(float (&x)[4][8], const uint32_t (&f)[4][4], uint32_t blo) {
#pragma unroll
    for (int r = 0; r < 4; ++r) wgmma_n16_rs(x[r], f[r], blo + 2 * r);
}
template <class T, int N>
__device__ __forceinline__ void fence_regs4(T (&a)[4][N]) { fence_regs(a[0]); fence_regs(a[1]); fence_regs(a[2]); fence_regs(a[3]); }
__device__ __forceinline__ void conv_s1(float (&dE)[32], float (&dO)[32], uint32_t tlo, uint32_t ulo) {
    wgmma_n64_ss<0, 1, 0, HI128, HI64>(dE, tlo + 256, ulo);
    wgmma_n64_ss<0, 1, 0, HI128, HI64>(dO, tlo + 256 + 4, ulo + 128);
    wgmma_n64_ss<0, 1, 1, HI128, HI64>(dE, tlo + 256 + 2, ulo + 64);
    wgmma_n64_ss<0, 1, 1, HI128, HI64>(dO, tlo + 256 + 6, ulo + 192);
}
template <int S>
__device__ __forceinline__ void conv_t1(const float (&dE)[32], const float (&dO)[32], const Twiddle& tw, float dsk, uint32_t (&f)[4][4]) {
    uint32_t ar[8], ai[8], fs[8], fd[8];
#pragma unroll
    for (int j = 0; j < 4; ++j) {
        const int i = 16 * S + 4 * j;
        const uint32_t e0 = pack_bf16(i == 16 ? dE[i] + dsk : dE[i], dE[i + 1]), e1 = pack_bf16(dE[i + 2], dE[i + 3]);
        const uint32_t o0 = pack_bf16(dO[i], dO[i + 1]), o1 = pack_bf16(dO[i + 2], dO[i + 3]);
        ar[2 * j] = hadd(e0, o0); ai[2 * j] = hadd(e1, o1);
        ar[2 * j + 1] = hsub(e0, o0); ai[2 * j + 1] = hsub(o1, e1);
    }
#pragma unroll
    for (int q = 0; q < 4; ++q) {
        const uint32_t pr = hfma(ar[q], tw.r[q], hmul(ai[q], tw.n[q])), pi = hfma(ar[q], tw.i[q], hmul(ai[q], tw.r[q]));
        fs[q] = hfma(ar[4 + q], tw.r[4 + q], hfma(ai[4 + q], tw.n[4 + q], pr));
        fs[4 + q] = hfma(ar[4 + q], tw.i[4 + q], hfma(ai[4 + q], tw.r[4 + q], pi));
        fd[q] = hfma(pr, 0xC000C000u, fs[q]);
        fd[4 + q] = hfma(pi, 0xC000C000u, fs[4 + q]);
    }
#pragma unroll
    for (int h = 0; h < 2; ++h) {
        f[0][h] = hadd(fs[h], fs[2 + h]); f[0][2 + h] = hadd(fs[4 + h], fs[6 + h]);
        f[2][h] = hsub(fs[h], fs[2 + h]); f[2][2 + h] = hsub(fs[4 + h], fs[6 + h]);
        f[1][h] = hadd(fd[h], fd[6 + h]); f[1][2 + h] = hsub(fd[4 + h], fd[2 + h]);
        f[3][h] = hsub(fd[h], fd[6 + h]); f[3][2 + h] = hadd(fd[4 + h], fd[2 + h]);
    }
}
__device__ __forceinline__ void conv_prod(const float (&xu)[8], const float (&xk)[8], uint32_t (&f)[4]) {
#pragma unroll
    for (int h = 0; h < 2; ++h) {
        float pr[2], pi[2];
#pragma unroll
        for (int e = 0; e < 2; ++e) {
            const float ur = xu[2 * h + e], ui = xu[4 + 2 * h + e], kr = xk[2 * h + e], ki = xk[4 + 2 * h + e];
            pr[e] = fmaf(ur, kr, -ui * ki);
            pi[e] = fmaf(-ur, ki, -ui * kr);
        }
        f[h] = pack_bf16(pr[0], pr[1]);
        f[2 + h] = pack_bf16(pi[0], pi[1]);
    }
}
template <bool SECOND, class G>
__device__ __forceinline__ void conv_channel(float (&dE)[32], float (&dO)[32], const Twiddle& tw, float dsk, uint32_t tlo, uint32_t nxt,
                                             uint32_t wre, uint32_t wim, int bar, G before_next) {
    float xu[4][8], xk[4][8];
    {
        uint32_t fu[4][4], fk[4][4];
        conv_t1<0>(dE, dO, tw, 0.f, fu);
        wgmma_fence();
        conv_dft8(xu, fu, tlo);
        wgmma_commit();
        conv_t1<1>(dE, dO, tw, dsk, fk);
        wgmma_fence();
        conv_dft8(xk, fk, tlo);
        wgmma_commit();
        before_next();
        wgmma_wait<0>();
        fence_regs4(xu); fence_regs4(xk);
        fence_regs4(fu); fence_regs4(fk);
    }
    uint32_t fp[4][4];
#pragma unroll
    for (int r = 0; r < 4; ++r) conv_prod(xu[r], xk[r], fp[r]);
    wgmma_fence();
    conv_dft8(xu, fp, tlo + 128);
    wgmma_commit();
    if (!SECOND || nxt) {
        if (SECOND) wgmma_fence();
        conv_s1(dE, dO, tlo, nxt);
        wgmma_commit();
        wgmma_wait<1>();
    } else {
        wgmma_wait<0>();
#pragma unroll
        for (int i = 0; i < 32; ++i) { dE[i] = 0.f; dO[i] = 0.f; }
        fence_regs(dE); fence_regs(dO);
    }
    fence_regs4(xu);
    fence_regs4(fp);
    uint32_t zr[8], zi[8], wr[8], wi[8];
#pragma unroll
    for (int h = 0; h < 2; ++h) {
        uint32_t yr[4], yi[4];
#pragma unroll
        for (int r = 0; r < 4; ++r) { yr[r] = pack_bf16(xu[r][2 * h], xu[r][2 * h + 1]); yi[r] = pack_bf16(xu[r][4 + 2 * h], xu[r][5 + 2 * h]); }
        const uint32_t u0r = hadd(yr[0], yr[2]), u0i = hadd(yi[0], yi[2]), u1r = hsub(yr[0], yr[2]), u1i = hsub(yi[0], yi[2]);
        const uint32_t v0r = hadd(yr[1], yr[3]), v0i = hadd(yi[1], yi[3]), v1r = hsub(yr[1], yr[3]), v1i = hsub(yi[1], yi[3]);
        zr[h] = hadd(u0r, v0r); zi[h] = hadd(u0i, v0i); zr[4 + h] = hsub(u0r, v0r); zi[4 + h] = hsub(u0i, v0i);
        zr[2 + h] = hadd(u1r, v1i); zi[2 + h] = hsub(u1i, v1r); zr[6 + h] = hsub(u1r, v1i); zi[6 + h] = hadd(u1i, v1r);
    }
#pragma unroll
    for (int q = 0; q < 8; ++q) {
        wr[q] = hfma(zr[q], tw.r[q], hmul(zi[q], tw.n[q]));
        wi[q] = hfma(zr[q], tw.i[q], hmul(zi[q], tw.r[q]));
    }
    if (SECOND) named_bar(bar, 128);
    stsm_x4(wre, hadd(wr[0], wr[1]), hadd(wr[2], wr[3]), hadd(wr[4], wr[5]), hadd(wr[6], wr[7]));
    stsm_x4(wre + 512, hsub(wi[1], wi[0]), hsub(wi[3], wi[2]), hsub(wi[5], wi[4]), hsub(wi[7], wi[6]));
    stsm_x4(wim, hsub(wr[1], wr[0]), hsub(wr[3], wr[2]), hsub(wr[5], wr[4]), hsub(wr[7], wr[6]));
    stsm_x4(wim + 512, hadd(wi[0], wi[1]), hadd(wi[2], wi[3]), hadd(wi[4], wi[5]), hadd(wi[6], wi[7]));
}
template <class G>
__device__ __forceinline__ void conv_pair(float (&dE)[32], float (&dO)[32], const Twiddle& tw, uint32_t dd, uint32_t tlo, uint32_t u0, uint32_t un,
                                          uint32_t lo, int BAR, G before_next) {
    conv_channel<false>(dE, dO, tw, bf_lo(dd), tlo, desc_lo(u0 + 4096, 8192), u0 + lo, u0 + 8192 + lo, BAR, []() {});
    wgmma_wait<0>();
    fence_regs(dE); fence_regs(dO);
    conv_channel<true>(dE, dO, tw, bf_hi(dd), tlo, un == u0 ? 0 : desc_lo(un, 8192), u0 + 4096 + lo, u0 + 12288 + lo, BAR, before_next);
    fence_async_smem();
    named_bar(BAR, 128);
    float ye[16], yo[16];
    wgmma_fence();
    const uint32_t wlo = desc_lo(u0, 4096);
    wgmma_n32_tt<0, 1>(ye, wlo, tlo + 256);
    wgmma_n32_tt<0, -1>(yo, wlo + 512, tlo + 256 + 4);
#pragma unroll
    for (int k = 1; k < 4; ++k) {
        wgmma_n32_tt<1, 1>(ye, wlo + 64 * k, tlo + 256 + 128 * k);
        wgmma_n32_tt<1, -1>(yo, wlo + 512 + 64 * k, tlo + 256 + 4 + 128 * k);
    }
    wgmma_commit();
    wgmma_wait<0>();
    fence_regs(ye); fence_regs(yo);
    fence_regs(dE); fence_regs(dO);
    named_bar(BAR, 128);
    const int t = fresh_tid();
    const uint32_t ya = u0 + (t & 64) * 64 + (t & 31) * 64 + (((((t >> 4) & 2) ^ (t >> 1)) & 3) << 4);
#pragma unroll
    for (int h = 0; h < 2; ++h) {
        stsm_x4_t(ya ^ (16 * h), pack_bf16(ye[2 * h], ye[2 * h + 1]), pack_bf16(ye[4 + 2 * h], ye[5 + 2 * h]),
                  pack_bf16(ye[8 + 2 * h], ye[9 + 2 * h]), pack_bf16(ye[12 + 2 * h], ye[13 + 2 * h]));
        stsm_x4_t((ya ^ (16 * h)) + 2048, pack_bf16(yo[2 * h], yo[2 * h + 1]), pack_bf16(yo[4 + 2 * h], yo[5 + 2 * h]),
                  pack_bf16(yo[8 + 2 * h], yo[9 + 2 * h]), pack_bf16(yo[12 + 2 * h], yo[13 + 2 * h]));
    }
    fence_async_smem();
    __syncwarp();
}
}

namespace {

constexpr int S_LEN = 2048;
constexpr int D_DIM = 1024;

#define REG_P 24
#define REG_AB 168
#define REG_C 152
#define BA 0
#define G1Q 4
#define SKEW1 4
#define SKEW2 6
#define QD 4
#define QKB 18
#define QD2 6
#define SLOT4 16
#define SLOT5 27
#define EPF 2
#define PFD 7
#define TK_PF0 0
#define TK_KV0 2
#define TK_KV1 4
#define TK_C 8
#define GAP_PF 300
#define GAP_KV 50
#define GAP_ST 50
#define GAP_CV 100
#define GAP_HB 100
#define GAP_Y 100
#define GAP_X 150
#define ALTMAP 0

__device__ __align__(1024) __nv_bfloat16 g_H[2 * D_DIM * S_LEN];
__device__ __align__(1024) __nv_bfloat16 g_y2[D_DIM * S_LEN];
__device__ __align__(1024) __nv_bfloat16 g_kvT[D_DIM * S_LEN];
__device__ __align__(128) float g_gate[S_LEN];
__device__ __align__(128) unsigned long long g_agg[8 * D_DIM];
__device__ __align__(128) unsigned int g_cnt[56 * 32];

#define STAMP(k, s) do { } while (0)
#define SAMPLE(i) do { } while (0)

__device__ __forceinline__ void tma_store_5d(const CUtensorMap* map, uint32_t src, int c0, int c1, int c2, int c3, int c4) {
    asm volatile("cp.async.bulk.tensor.5d.global.shared::cta.bulk_group [%0, {%2, %3, %4, %5, %6}], [%1];"
                 ::"l"((uint64_t)map), "r"(src), "r"(c0), "r"(c1), "r"(c2), "r"(c3), "r"(c4) : "memory");
}
#define ELECT "{\n.reg .pred p;\nelect.sync _|p, 0xffffffff;\n@p "
__device__ __forceinline__ void e_expect_tx(uint32_t bar, uint32_t bytes) {
    asm volatile(ELECT "mbarrier.arrive.expect_tx.shared::cta.b64 _, [%0], %1;\n}" ::"r"(bar), "r"(bytes) : "memory");
}
__device__ __forceinline__ void e_arrive(uint32_t bar) {
    asm volatile(ELECT "mbarrier.arrive.shared::cta.b64 _, [%0];\n}" ::"r"(bar) : "memory");
}
__device__ __forceinline__ void e_load_4d(uint32_t dst, const CUtensorMap* map, uint32_t bar, int c0, int c1, int c2, int c3) {
    asm volatile(ELECT "cp.async.bulk.tensor.4d.shared::cluster.global.mbarrier::complete_tx::bytes [%0], [%1, {%3, %4, %5, %6}], [%2];\n}"
        ::"r"(dst), "l"((uint64_t)map), "r"(bar), "r"(c0), "r"(c1), "r"(c2), "r"(c3) : "memory");
}
__device__ __forceinline__ void e_load_5d(uint32_t dst, const CUtensorMap* map, uint32_t bar, int c0, int c1, int c2, int c3, int c4) {
    asm volatile(ELECT "cp.async.bulk.tensor.5d.shared::cluster.global.mbarrier::complete_tx::bytes [%0], [%1, {%3, %4, %5, %6, %7}], [%2];\n}"
        ::"r"(dst), "l"((uint64_t)map), "r"(bar), "r"(c0), "r"(c1), "r"(c2), "r"(c3), "r"(c4) : "memory");
}
__device__ __forceinline__ void e_bulk_load(uint32_t dst, const void* src, uint32_t bytes, uint32_t bar) {
    asm volatile(ELECT "cp.async.bulk.shared::cluster.global.mbarrier::complete_tx::bytes [%0], [%1], %2, [%3];\n}"
                 ::"r"(dst), "l"(src), "r"(bytes), "r"(bar) : "memory");
}
__device__ __forceinline__ void l2_prefetch(const void* p, uint32_t bytes) {
    asm volatile("cp.async.bulk.prefetch.L2.global [%0], %1;" ::"l"(p), "r"(bytes) : "memory");
}
__device__ __forceinline__ void l2_prefetch_4d(const CUtensorMap* map, int c0, int c1, int c2, int c3) {
    asm volatile("cp.async.bulk.prefetch.tensor.4d.L2.global [%0, {%1, %2, %3, %4}];" ::"l"((uint64_t)map), "r"(c0), "r"(c1), "r"(c2), "r"(c3) : "memory");
}
__device__ __forceinline__ void l2_prefetch_5d(const CUtensorMap* map, int c0, int c1, int c2, int c3, int c4) {
    asm volatile("cp.async.bulk.prefetch.tensor.5d.L2.global [%0, {%1, %2, %3, %4, %5}];" ::"l"((uint64_t)map), "r"(c0), "r"(c1), "r"(c2), "r"(c3), "r"(c4) : "memory");
}
__device__ __forceinline__ unsigned int ld_relaxed(const unsigned int* p) {
    unsigned int v;
    asm volatile("ld.relaxed.gpu.global.u32 %0, [%1];" : "=r"(v) : "l"(p) : "memory");
    return v;
}
__device__ __forceinline__ void fence_async_global() { asm volatile("fence.proxy.async.global;" ::: "memory"); }
__device__ __forceinline__ void wait_counter(const unsigned int* p, unsigned int target) {
    unsigned int v;
    int it = 0;
    do { asm volatile("ld.acquire.gpu.global.u32 %0, [%1];" : "=r"(v) : "l"(p) : "memory"); } while (v != target && ++it < (1 << 22));
    fence_async_global();
}
__device__ __forceinline__ void red_release(unsigned int* p, unsigned int n) {
    asm volatile("red.release.gpu.global.add.u32 [%0], %1;" ::"l"(p), "r"(n) : "memory");
}
__device__ __forceinline__ uint4 ldg128(const void* p) {
    uint4 v;
    asm volatile("ld.global.nc.v4.u32 {%0,%1,%2,%3}, [%4];" : "=r"(v.x), "=r"(v.y), "=r"(v.z), "=r"(v.w) : "l"(p));
    return v;
}
__device__ __forceinline__ void stg128(void* p, uint32_t a, uint32_t b, uint32_t c, uint32_t d) {
    asm volatile("st.global.v4.b32 [%0], {%1, %2, %3, %4};" ::"l"(p), "r"(a), "r"(b), "r"(c), "r"(d) : "memory");
}

template <int TA>
__device__ __forceinline__ void wgmma_n128(float (&d)[64], uint32_t alo, uint32_t blo, int acc) {
    asm volatile(
        "{\n.reg .pred p;\n.reg .b64 da, db;\nsetp.ne.b32 p, %67, 0;\nmov.b64 da, {%64, %69};\nmov.b64 db, {%65, %66};\n"
        "wgmma.mma_async.sync.aligned.m64n128k16.f32.bf16.bf16 "
        "{%0, %1, %2, %3, %4, %5, %6, %7, %8, %9, %10, %11, %12, %13, %14, %15, "
        "%16, %17, %18, %19, %20, %21, %22, %23, %24, %25, %26, %27, %28, %29, %30, %31, "
        "%32, %33, %34, %35, %36, %37, %38, %39, %40, %41, %42, %43, %44, %45, %46, %47, "
        "%48, %49, %50, %51, %52, %53, %54, %55, %56, %57, %58, %59, %60, %61, %62, %63}, "
        "da, db, p, 1, 1, %68, 0;\n"
        "}\n"
        : R8(d, 0), R8(d, 8), R8(d, 16), R8(d, 24), R8(d, 32), R8(d, 40), R8(d, 48), R8(d, 56)
        : "r"(alo), "r"(blo), "n"(HI128), "r"(acc), "n"(TA), "n"(TA ? HI64 : HI128));
}

constexpr int NST = 6;
constexpr int XTRA = SKEW1 - 4;
static_assert(SKEW1 >= 4 && SKEW1 <= 12, "skew");
constexpr int OFF_BB = 4 * 32768;
constexpr int OFF_CT = 5 * 32768;
constexpr int OFF_CU = OFF_CT + 32768;
__host__ __device__ constexpr uint32_t conv_buf(int p) { return OFF_CT + 16384 + (p == 3 ? 0 : p) * 16384; }
constexpr int OFF_PAR = OFF_CU + 32768;
constexpr int OFF_BAR = OFF_PAR + 2048;
constexpr int SMEM_BYTES = OFF_BAR + 896;
static_assert(SMEM_BYTES <= 232448, "smem layout");

struct Ring { unsigned long long w[2]; };
constexpr Ring make_ring() {
    Ring r{};
    int st = 0, uses[NST] = {};
    for (int kb = 0; kb < 32; ++kb) {
        r.w[kb >> 4] |= (unsigned long long)(st | (uses[st]++ & 1) << 3) << (4 * (kb & 15));
        if (++st >= (kb + 1 < SLOT4 ? 4 : kb + 1 < SLOT5 ? 5 : 6)) st = 0;
    }
    return r;
}
constexpr unsigned long long RING0 = make_ring().w[0], RING1 = make_ring().w[1];
__host__ __device__ constexpr uint32_t ring_code(int kb) { return (uint32_t)((kb < 16 ? RING0 : RING1) >> (4 * (kb & 15))) & 15u; }
__host__ __device__ constexpr int ring_slot(int kb) { return ring_code(kb) & 7; }
__host__ __device__ constexpr uint32_t ring_par(int kb) { return ring_code(kb) >> 3; }
constexpr int OFF_O1 = SLOT5 < 32 ? ring_slot(SKEW2 == 6 ? 26 : 31 - SKEW2) * 32768 : OFF_CT;

struct Maps {
    CUtensorMap x5, b4, cre, cim, sk, yt, yt3, out, kvst, bre, bim;
};

__device__ __forceinline__ void cmul(float& r, float& i, float ar, float ai, float br, float bi) {
    const float a = ar * br - ai * bi, b = ar * bi + ai * br;
    r = a; i = b;
}
__device__ __forceinline__ void csqr(float& r, float& i) { const float a = r * r - i * i, b = 2.f * r * i; r = a; i = b; }
__device__ __forceinline__ float after(float v, float dep) { return __float_as_uint(dep) == 0x7fedcba9u ? dep : v; }

template <int BMODE>
__global__ void __launch_bounds__(512, 1)
fused_kernel(const __nv_bfloat16* __restrict__ x, const __nv_bfloat16* __restrict__ b_re, const __nv_bfloat16* __restrict__ b_im,
             const __nv_bfloat16* __restrict__ kin, const __nv_bfloat16* __restrict__ vin, const __nv_bfloat16* __restrict__ ssm_k,
             const __nv_bfloat16* __restrict__ shift_k, const __nv_bfloat16* __restrict__ ssm_D,
             const __nv_bfloat16* __restrict__ lam_re, const __nv_bfloat16* __restrict__ lam_im,
             const __nv_bfloat16* __restrict__ log_dt, const __nv_bfloat16* __restrict__ gate_w,
             const __nv_bfloat16* __restrict__ dskip,
             const __nv_bfloat16* __restrict__ c_re, const __nv_bfloat16* __restrict__ c_im,
             const __grid_constant__ Maps maps) {
    constexpr bool MERGED = BMODE != 0, SW = BMODE == 2;
    extern __shared__ __align__(1024) unsigned char smem_raw[];
    const uint32_t sbase = smem_u32(smem_raw);
    const uint32_t bar_full = sbase + OFF_BAR;
    const uint32_t bar_empty = bar_full + 32;
    const uint32_t bar_full2 = bar_empty + 32;
    const uint32_t bar_empty2 = bar_full2 + 48;
    const uint32_t bar_k = bar_empty2 + 48;
    const uint32_t bar_tab = bar_k + 32;
    const uint32_t bar_ab = bar_tab + 8;
    const uint32_t bar_adone = bar_ab + 8;
    const uint32_t bar_par = bar_adone + 8;
    const uint32_t bar_y = bar_par + 8;
    const uint32_t bar_rel = bar_y + 8;
    const uint32_t bar_kvrel = bar_rel + 8;
    const uint32_t bar_yrel = bar_kvrel + 8;
    const uint32_t bar_y1 = bar_yrel + 8;
    const uint32_t bar_fh = bar_y1 + 8;
    const uint32_t bar_o1 = bar_fh + 8;
    const uint32_t bar_tick = bar_o1 + 8;
    const uint32_t bar_stg = bar_tick + 104;
    const uint32_t bar_bias = bar_stg + 112;
    const uint32_t bar_hw = bar_bias + 16;
    const uint32_t bar_gate = bar_hw + 8;
    const uint32_t bar_g2 = bar_gate + 8;
    const uint32_t bar_ba = bar_g2 + 8;
    const uint32_t w_bid = bar_full + 600, w_dsk = bar_full + 608, w_ones = bar_full + 640;
    const int tid = threadIdx.x ^ (((threadIdx.x + 128) & 256) ? 0 : 384);
    if (tid == 384) { prefetch_map(&maps.x5); prefetch_map(&maps.b4); }
    if (EPF && (threadIdx.x >> 5) - 1u < EPF && blockIdx.x < 128) {
        const int ln = threadIdx.x & 31;
        const __nv_bfloat16* p = ln < 16 ? x + (size_t)(blockIdx.x * 16 + ln) * D_DIM : ((ln & 8) ? b_im : b_re) + (size_t)(blockIdx.x * 8 + (ln & 7)) * D_DIM;
        asm volatile("prefetch.global.L2 [%0];" ::"l"(p + ((threadIdx.x >> 5) - 1) * 64) : "memory");
    }
    int bid;
    {
        unsigned int sm, nsm;
        asm volatile("mov.u32 %0, %smid;" : "=r"(sm));
        asm volatile("mov.u32 %0, %nsmid;" : "=r"(nsm));
        const int tpc = sm >> 1, q7 = ((tpc - 32) * 37) >> 8;
        const int gp = tpc < 32 ? tpc & 7 : tpc < 60 ? tpc - 31 - 7 * q7 : 0;
        const int ix = tpc < 32 ? tpc >> 3 : tpc < 60 ? q7 + 4 : ALTMAP ? (tpc - 56) ^ 2 : tpc - 58;
        bid = (ALTMAP ? tpc >= 64 : (tpc | 1) == 61) ? 128 : (4 * (gp >> 1) + (ix >> 1)) * 8 + 4 * (gp & 1) + 2 * (ix & 1) + (sm & 1);
        if (gridDim.x != 132 || nsm != 132) bid = blockIdx.x;
    }
    const int tt = bid >> 3, dt = bid & 7;
    const int ti = tt >> 1;
    const int cg = (dt >> 2) * 8 + (tt & 1) * 4 + (dt & 3);
    if (MERGED && threadIdx.x == 0 && bid < 128) {
        mbar_init(bar_full, 1);
        asm volatile("fence.mbarrier_init.release.cluster;" ::: "memory");
        mbar_expect_tx(bar_full, 49152);
        tma_load_4d(sbase + OFF_CU, &maps.b4, bar_full, 0, 0, 0, cg * 4);
        tma_load_5d(sbase + ((0 - XTRA) & 3) * 32768, &maps.x5, bar_full, 0, 0, 0, 0, ti);
        tma_load_4d(sbase + OFF_BB, &maps.b4, bar_full, 0, 0, 0, 64 + cg * 4);
    }
    __syncwarp();
    const int warp = __shfl_sync(0xffffffffu, tid >> 5, 0), wg = warp >> 2, lane = tid & 31;
    if (warp == 12 && bid < 128) {
        if (lane == 0) {
#pragma unroll
            for (int s = MERGED; s < 4; ++s) mbar_init(bar_full + 8 * s, 1);
            asm volatile("fence.mbarrier_init.release.cluster;" ::: "memory");
        }
        __syncwarp();
        asm volatile("bar.arrive 4, 512;" ::: "memory");
        if (MERGED) {
#pragma unroll 1
            for (int it = 1; it < 4; ++it) {
                e_expect_tx(bar_full + 8 * it, 49152);
                e_load_4d(sbase + OFF_CU + it * 8192, &maps.b4, bar_full + 8 * it, it * 64, 0, 0, cg * 4);
                e_load_5d(sbase + ((it - XTRA) & 3) * 32768, &maps.x5, bar_full + 8 * it, it * 64, 0, 0, 0, ti);
                e_load_4d(sbase + OFF_BB + it * 8192, &maps.b4, bar_full + 8 * it, it * 64, 0, 0, 64 + cg * 4);
            }
        }
    }
    if (bid >= 128) {
        if (tid == 0) {
            __nanosleep(2000);
            const unsigned int target = (ld_relaxed(&g_cnt[32 * 32]) & ~63u) + 64u;
            for (int i = 0; i < 8; ++i)
                for (int it = 0; ld_relaxed(&g_cnt[(40 + i) * 32]) != target && it < (1 << 12); ++it) __nanosleep(500);
        }
        return;
    }
    if (wg == 0) {
        asm volatile("setmaxnreg.dec.sync.aligned.u32 %0;" ::"n"(REG_P));
        if (tid == 32) {
            if (sbase & 1023) __trap();
#pragma unroll
            for (int s = 0; s < 4; ++s) mbar_init(bar_empty + 8 * s, 2);
#pragma unroll
            for (int s = 0; s < NST; ++s) { mbar_init(bar_full2 + 8 * s, 1); mbar_init(bar_empty2 + 8 * s, 1); }
            mbar_init(bar_k, 1); mbar_init(bar_k + 8, 1); mbar_init(bar_k + 16, 1); mbar_init(bar_k + 24, 1);
            mbar_init(bar_tab, 1);
            mbar_init(bar_ab, 1);
            mbar_init(bar_adone, 4);
            mbar_init(bar_par, 2);
            mbar_init(bar_ba, 1);
            asm volatile("fence.mbarrier_init.release.cluster;" ::: "memory");
        } else if (tid == 64) {
#pragma unroll
            for (int s = 0; s < 20; ++s) mbar_init(bar_y + 8 * s, 1);
        } else if (tid == 96) {
#pragma unroll
            for (int s = 0; s < 11; ++s) mbar_init(bar_stg + 8 * s, 4);
        } else if (tid == 0) {
#pragma unroll
            for (int s = 11; s < 19; ++s) mbar_init(bar_stg + 8 * s, 4);
            asm volatile("st.shared.b32 [%0], %1;" ::"r"(w_bid), "r"(bid) : "memory");
        }
        __syncwarp();
        asm volatile("bar.sync 4, 512;" ::: "memory");
        if (warp == 0) {
#pragma unroll 1
            for (int it = MERGED ? 4 : 0; it < 16 + XTRA; ++it) {
                const int st = it & 3, kb = it < 16 ? it : it - SKEW1;
                const bool fa = it < 16, fb = it < 16 - SKEW1 || it >= 12;
                const uint32_t bf = bar_full + 8 * st;
                mbar_wait(bar_empty + 8 * st, ((it >> 2) & 1) ^ 1);
                e_expect_tx(bf, fa && fb ? 49152 : 40960);
                e_load_5d(sbase + ((it - XTRA) & 3) * 32768, &maps.x5, bf, kb * 64, 0, 0, 0, ti);
                if (MERGED) {
                    if (fa) e_load_4d(sbase + OFF_CU + st * 8192, &maps.b4, bf, kb * 64, 0, 0, cg * 4);
                    if (fb) e_load_4d(sbase + OFF_BB + st * 8192, &maps.b4, bf, kb * 64, 0, 0, 64 + cg * 4);
                } else {
                    if (lane < 16 && ((lane & 8) ? fb : fa))
                        tma_load_2d(sbase + ((lane & 8) ? OFF_BB : OFF_CU) + st * 8192 + (lane & 7) * 1024, (lane & 1) ? &maps.bim : &maps.bre, bf,
                                    kb * 64, (lane >> 3) * 512 + cg * 32 + ((lane & 7) >> 1) * 8);
                    __syncwarp();
                }
                if (it >= 4 && it < 16) e_arrive(bar_tick + 8 * (it - 3));
                if (lane == 0) STAMP(1, 16 + it);
                if (lane == 0 && it < 16) SAMPLE(it - 3);
            }
#pragma unroll 1
            for (int kb = 0; kb < 32; ++kb) {
                const int st = ring_slot(kb);
                const uint32_t bf = bar_full2 + 8 * st;
                mbar_wait(bar_empty2 + 8 * st, ring_par(kb));
                e_expect_tx(bf, 32768);
                e_load_5d(sbase + st * 32768 + 16384, &maps.cre + ((kb >> 3) & 1), bf, ((kb >> 4) * 8 + (kb & 7)) * 64, 0, 0, 0, dt * 4);
                if (lane == 0) STAMP(2, 16 + kb);
                if (lane == 0 && (kb & 3) == 0) SAMPLE(13 + (kb >> 2));
            }
        } else if (warp == 1) {
            if (MERGED && PFD && lane == 0) {
#pragma unroll 1
                for (int n = -1; n + PFD < 16; ++n) {
                    if (n >= 0) mbar_wait(bar_tick + 8 * n, 0);
                    if (cg >= 4 && (cg < 6 ? -1 : max(cg - PFD, 0)) == n) l2_prefetch_5d(&maps.x5, cg * 64, 0, 0, 0, ti);
                    if (ti >= 2 && (ti < 3 ? -1 : max(2 * ti - PFD, 0)) == n) {
#pragma unroll 1
                        for (int i = 0; i < 4; ++i) l2_prefetch_4d(&maps.b4, (2 * ti + (i >> 1)) * 64, 0, 0, (i & 1) * 64 + cg * 4);
                    }
                }
            }
            __syncwarp();
            const char* hp = reinterpret_cast<const char*>(g_H) + (size_t)tt * 262144;
            mbar_wait(bar_adone, 0);
            e_expect_tx(bar_k + 8, 16384);
            e_expect_tx(bar_k + 16, 16384);
#pragma unroll 1
            for (int c = 2; c < 6; ++c) {
                e_load_4d(sbase + conv_buf(0) + (c >> 1) * 16384 + (c & 1) * 4096 + 8192, &maps.sk, bar_k + 8 * (c >> 1), 0, 0, 0, bid * 8 + c);
                if (GAP_CV) __nanosleep(GAP_CV);
            }
            mbar_wait(bar_kvrel, 0);
            const unsigned int target = lds32(w_bid + 4);
            mbar_wait(bar_rel, 0);
#pragma unroll 1
            for (int q = 0; q < 2; ++q) {
                if (lane == 0) STAMP(0, 8 + 4 * q);
                if (q == 0) wait_counter(&g_cnt[(2 * ti) * 32], target);
                else { mbar_wait(bar_fh, 0); fence_async_global(); }
                if (lane == 0) STAMP(0, 9 + 4 * q);
#pragma unroll 1
                for (int kb = 0; kb < 16; ++kb) {
                    const int st = ring_slot(16 * q + kb);
                    mbar_wait(bar_empty2 + 8 * st, ring_par(16 * q + kb));
                    e_bulk_load(sbase + st * 32768, hp + kb * 16384, 16384, bar_full2 + 8 * st);
                }
                hp += 4194304;
            }
        } else if (warp == 2) {
            if (lane == 0) {
                mbar_wait(bar_tick + 8, 0);
                const unsigned int target = (ld_relaxed(&g_cnt[(40 + dt) * 32]) & ~63u) + 64u;
                asm volatile("st.shared.b32 [%0], %1;" ::"r"(w_bid + 4), "r"(target) : "memory");
                prefetch_map(&maps.kvst); prefetch_map(&maps.sk);
#pragma unroll 1
                for (int bt = 0; bt < 2; ++bt) {
                    mbar_wait(bar_stg + 8 * bt, 0);
#pragma unroll 1
                    for (int i = 0; i < 4; ++i) {
                        if (i) __nanosleep(GAP_ST);
                        tma_store_3d(&maps.kvst, sbase + OFF_CT + bt * 16384 + i * 4096, (tt & 1) * 1024 + ti * 128 + 64 * bt, dt * 16, 2 * i);
                    }
                    bulk_commit();
                }
                bulk_wait0();
                fence_async_global();
                red_release(&g_cnt[(40 + dt) * 32], 4);
                mbar_arrive(bar_kvrel);
                STAMP(0, 23);
                mbar_expect_tx(bar_tab, 12288);
                bulk_load(sbase + OFF_CT, &g_conv_tab, 12288, bar_tab);
                mbar_expect_tx(bar_k, 16384);
                tma_load_4d(sbase + conv_buf(0) + 8192, &maps.sk, bar_k, 0, 0, 0, bid * 8);
                tma_load_4d(sbase + conv_buf(0) + 12288, &maps.sk, bar_k, 0, 0, 0, bid * 8 + 1);
                wait_counter(&g_cnt[(40 + (bid >> 4)) * 32], target);
                STAMP(0, 19);
#pragma unroll 1
                for (int p = 0; p < 3; ++p) {
                    if (p == 1) mbar_wait(bar_adone, 0);
                    bulk_load(sbase + conv_buf(p), g_kvT + (size_t)(bid * 8 + 2 * p) * 2048, 8192, bar_k + 8 * p);
                    if (GAP_CV) __nanosleep(GAP_CV);
                }
                prefetch_map(&maps.out); prefetch_map(&maps.yt); prefetch_map(&maps.yt3);
#pragma unroll 1
                for (int p = 0; p < 4; ++p) {
                    mbar_wait(bar_stg + 16 + 8 * p, 0);
                    if (p == 0) {
                        mbar_expect_tx(bar_k + 24, 16384);
                        tma_load_4d(sbase + conv_buf(3) + 8192, &maps.sk, bar_k + 24, 0, 0, 0, bid * 8 + 6);
                        mbar_wait(bar_g2, 0);
                        tma_load_4d(sbase + conv_buf(3) + 12288, &maps.sk, bar_k + 24, 0, 0, 0, bid * 8 + 7);
                    }
#pragma unroll 1
                    for (int i = 0; i < 2; ++i) {
                        if (i) __nanosleep(GAP_Y);
                        asm volatile("cp.async.bulk.global.shared::cta.bulk_group [%0], [%1], 4096;"
                                     ::"l"(g_y2 + (size_t)(bid * 8 + 2 * p + i) * 2048), "r"(sbase + conv_buf(p) + i * 4096) : "memory");
                    }
                    bulk_commit();
                    STAMP(0, 24 + p);
                    if (p == 0) {
                        bulk_wait_read0();
                        bulk_load(sbase + conv_buf(3), g_kvT + (size_t)(bid * 8 + 6) * 2048, 8192, bar_k + 24);
                    }
                    if (p == 2) {
                        bulk_wait0();
                        fence_async_global();
                        red_release(&g_cnt[(48 + (bid >> 4)) * 32], 4);
                        mbar_arrive(bar_yrel);
                        STAMP(0, 3);
                    }
                }
                bulk_wait0();
                mbar_arrive(bar_empty2 + 40);
                fence_async_global();
                red_release(&g_cnt[(32 + (bid >> 4)) * 32], 4);
                STAMP(0, 2);
                wait_counter(&g_cnt[(32 + dt) * 32], target);
                STAMP(0, 5);
                mbar_expect_tx(bar_y, 8192);
#pragma unroll 1
                for (int i = 6; i < 8; ++i)
                    tma_load_5d(sbase + OFF_CU + i * 4096, &maps.yt, bar_y, (tt & 1) * 1024 + ti * 128 + (i & 1) * 64, 0, 0, i >> 1, dt * 4);
#pragma unroll 1
                for (int i = 0; i < 8; ++i) {
                    mbar_wait(bar_stg + 48 + 8 * i, 0);
                    tma_store_5d(&maps.out, sbase + ((i & 4) ? OFF_O1 : OFF_CU) + (i & 3) * 8192, dt * 128 + (i & 3) * 32, 0, 0, (tt & 1) * 4 + ((i & 4) >> 1), ti);
                    bulk_commit();
                }
                bulk_wait_read0();
                STAMP(2, 3);
                SAMPLE(21);
            }
        } else if (lane == 0) {
            mbar_wait(bar_tick + 8 * TK_PF0, 0);
#pragma unroll 1
            for (int i = 0; i < 8; ++i) {
                l2_prefetch(((i & 1) ? vin : kin) + (size_t)(ti * 256 + 32 * (i & 4) + (bid & 15) * 8 + 2 * (i & 2)) * D_DIM, 8192);
                __nanosleep(GAP_PF);
            }
            if (bid < 3) l2_prefetch(reinterpret_cast<const char*>(&g_conv_tab) + bid * 4096, 4096);
            prefetch_map(&maps.cre); prefetch_map(&maps.cim);
            mbar_wait(bar_tick + 8 * TK_C, 0);
#pragma unroll 1
            for (int i = 0; i < 8; ++i) {
                l2_prefetch((i & 1) ? ((i & 4) ? c_im : c_re) + (size_t)bid * 8192 + (i & 2) * 2048 : ssm_k + (size_t)bid * 16384 + (i >> 1) * 4096, 8192);
                __nanosleep(GAP_PF);
            }
            const unsigned int target = (ld_relaxed(&g_cnt[(2 * ti + 1) * 32]) & ~63u) + 64u;
            mbar_wait(bar_gate, 0);
            mbar_wait(bar_hw, 0);
            mbar_wait(bar_g2, 0);
            char* hp = reinterpret_cast<char*>(g_H) + (size_t)((16 + 2 * ti) * 16 + (cg >> 1)) * 16384 + (cg & 1) * 2048;
#pragma unroll 1
            for (int i = 0; i < 16; ++i) {
                asm volatile("cp.async.bulk.global.shared::cta.bulk_group [%0], [%1], 2048;"
                             ::"l"(hp + (i & 3) * 4096 + ((i >> 2) & 1) * 262144 + (i >> 3) * 131072), "r"(sbase + OFF_BB + i * 2048) : "memory");
                __nanosleep(GAP_HB);
            }
            bulk_commit();
            bulk_wait0();
            mbar_arrive(bar_empty2 + 32);
            fence_async_global();
            red_release(&g_cnt[(2 * ti + 1) * 32], 4);
            STAMP(0, 38);
            wait_counter(&g_cnt[(2 * ti + 1) * 32], target);
            mbar_arrive(bar_fh);
        }
    } else {
    if (wg == 3) {
        if (warp != 12) asm volatile("bar.sync 4, 512;" ::: "memory");
        named_bar(3, 128);
        asm volatile("setmaxnreg.inc.sync.aligned.u32 %0;" ::"n"(REG_C));
        const int t = tid & 127, w4 = t >> 5;
        if (t == 0) SAMPLE(0);
        mbar_wait(bar_tick, 0);
        if (t < 64) {
            const int ch = (t >> 5) * 512 + cg * 32 + (t & 31);
            unsigned long long oldagg;
            asm volatile("ld.relaxed.gpu.global.u64 %0, [%1];" : "=l"(oldagg) : "l"(&g_agg[ti * D_DIM + ch]) : "memory");
            const float Lr = __bfloat162float(lam_re[ch]), Li = __bfloat162float(lam_im[ch]);
            const float dtv = bf16r(expf(__bfloat162float(log_dt[ch])));
            const unsigned int tag = ((((unsigned int)oldagg & 1u) | ((unsigned int)(oldagg >> 31) & 2u)) + 1u) & 3u;
            const float er = expf(dtv * Lr);
            float s, c;
            sincospif(dtv * Li * 0.318309886183790672f, &s, &c);
            const float lr = er * c, li = er * s;
            const float nr = lr - 1.f, ni = li;
            const float den = Lr * Lr + Li * Li;
            const float cr = 2.f * (nr * Lr + ni * Li) / den, ci = 2.f * (ni * Lr - nr * Li) / den;
            float pr = lr, pi = -li;
#pragma unroll
            for (int i = 0; i < 5; ++i) csqr(pr, pi);
            sts128(sbase + OFF_PAR + t * 32, __float_as_uint(lr), __float_as_uint(-li), __float_as_uint(cr), __float_as_uint(ci));
            sts128(sbase + OFF_PAR + t * 32 + 16, __float_as_uint(pr), __float_as_uint(pi), tag, 0);
            __syncwarp();
            if (lane == 0) mbar_arrive(bar_par);
        }
        if (t >= 120) asm volatile("st.shared.b32 [%0], %1;" ::"r"(w_dsk - 480 + 4 * t),
                                   "r"(t < 124 ? __ldg(reinterpret_cast<const uint32_t*>(ssm_D + bid * 8) + (t & 3)) : 0u) : "memory");
        if (t < 64) asm volatile("st.shared.b32 [%0], %1;" ::"r"(w_ones + 4 * t), "r"(0x3F803F80u) : "memory");
        {
            const int cq = lane & 15, rg = (lane >> 4) + 2 * w4;
            uint32_t sk[4][4];
#pragma unroll
            for (int c = 0; c < 4; ++c) {
                const uint4 w = ldg128(shift_k + (size_t)(dt * 128 + 8 * cq + 2 * c) * 4);
                sk[0][c] = __byte_perm(w.x, w.z, 0x5410); sk[1][c] = __byte_perm(w.x, w.z, 0x7632);
                sk[2][c] = __byte_perm(w.y, w.w, 0x5410); sk[3][c] = __byte_perm(w.y, w.w, 0x7632);
            }
#pragma unroll 1
            for (int bt = 0; bt < 2; ++bt) {
                const int t0 = ti * 256 + 128 * bt + 16 * (rg & 4) + 32 * (tt & 1) + 8 * (rg & 3);
                mbar_wait(bar_tick + 8 * (bt ? TK_KV1 : TK_KV0), 0);
                if (t == 0) STAMP(0, 30 + 3 * bt);
                uint4 kk[11], vv[8];
                const __nv_bfloat16* kp = kin + (size_t)t0 * D_DIM + dt * 128 + 8 * cq;
                const __nv_bfloat16* vp = vin + (size_t)t0 * D_DIM + dt * 128 + 8 * cq;
#pragma unroll
                for (int i = 0; i < 11; ++i) {
                    if (i < 3 && t0 == 0) kk[i] = make_uint4(0, 0, 0, 0);
                    else kk[i] = ldg128(kp + (i - 3) * D_DIM);
                    if (i == 6 || i == 10) __nanosleep(GAP_KV);
                }
#pragma unroll
                for (int i = 0; i < 8; ++i) { vv[i] = ldg128(vp + i * D_DIM); if (i == 3) __nanosleep(GAP_KV); }
                const uint32_t ua = sbase + OFF_CT + bt * 16384 + cq * 128 + ((rg ^ ((2 * ti + bt) & 3) ^ (cq & 7)) << 4);
#pragma unroll
                for (int c = 0; c < 4; ++c) {
                    uint32_t res[8];
#pragma unroll
                    for (int i = 0; i < 8; ++i) {
                        uint32_t ks = hmul((&kk[i].x)[c], sk[3][c]);
                        ks = hadd(ks, hmul((&kk[i + 1].x)[c], sk[2][c]));
                        ks = hadd(ks, hmul((&kk[i + 2].x)[c], sk[1][c]));
                        ks = hadd(ks, hmul((&kk[i + 3].x)[c], sk[0][c]));
                        res[i] = hmul(ks, (&vv[i].x)[c]);
                    }
                    sts128(ua + (2 * c) * 2048, __byte_perm(res[0], res[1], 0x5410), __byte_perm(res[2], res[3], 0x5410),
                           __byte_perm(res[4], res[5], 0x5410), __byte_perm(res[6], res[7], 0x5410));
                    sts128(ua + (2 * c + 1) * 2048, __byte_perm(res[0], res[1], 0x7632), __byte_perm(res[2], res[3], 0x7632),
                           __byte_perm(res[4], res[5], 0x7632), __byte_perm(res[6], res[7], 0x7632));
                }
                fence_async_smem();
                __syncwarp();
                if (lane == 0) mbar_arrive(bar_stg + 8 * bt);
                if (t == 0) STAMP(0, 21 + bt);
            }
        }
        {
            const int row = bid * 16 + (t >> 3);
            uint4 xv[16];
#pragma unroll
            for (int n = 0; n < 16; ++n) {
                xv[n] = ldg128(x + (size_t)row * D_DIM + ((t & 7) + 8 * n) * 8);
                if ((n & 3) == 3) __nanosleep(GAP_KV);
            }
#pragma unroll
            for (int n8 = 0; n8 < 16; n8 += 8) {
                uint4 wv[8];
#pragma unroll
                for (int n = 0; n < 8; ++n) wv[n] = ldg128(gate_w + ((t & 7) + 8 * (n8 + n)) * 8);
#pragma unroll
                for (int n = 0; n < 8; ++n) {
                    uint4& p = xv[n8 + n];
                    p.x = hmul(p.x, wv[n].x); p.y = hmul(p.y, wv[n].y); p.z = hmul(p.z, wv[n].z); p.w = hmul(p.w, wv[n].w);
                }
            }
            float d[4] = {0.f, 0.f, 0.f, 0.f};
            fence_regs(d);
            named_bar(3, 128);
            wgmma_fence();
#pragma unroll
            for (int n = 0; n < 16; ++n)
                asm volatile("{\n.reg .b64 db;\nmov.b64 db, {%8, 8};\n"
                             "wgmma.mma_async.sync.aligned.m64n8k16.f32.bf16.bf16 {%0, %1, %2, %3}, {%4, %5, %6, %7}, db, 1, 1, 1, 0;\n}\n"
                             : "+f"(d[0]), "+f"(d[1]), "+f"(d[2]), "+f"(d[3]) : "r"(xv[n].x), "r"(xv[n].y), "r"(xv[n].z), "r"(xv[n].w), "r"(desc_lo(w_ones, 128)));
            wgmma_commit();
            wgmma_wait<0>();
            fence_regs(d);
#pragma unroll
            for (int n = 0; n < 16; ++n) asm volatile("" ::"r"(xv[n].x), "r"(xv[n].y), "r"(xv[n].z), "r"(xv[n].w) : "memory");
            float sum = d[0] + d[2];
            sum += __shfl_xor_sync(0xffffffffu, sum, 4);
            if ((t & 7) == 0) g_gate[row] = bf16r(1.f / (1.f + expf(-bf16r(sum))));
            if (t == 0) STAMP(0, 4);
            __syncwarp();
            if (lane == 0) mbar_arrive(bar_gate);
        }
    } else {
        asm volatile("setmaxnreg.inc.sync.aligned.u32 %0;" ::"n"(REG_AB));
        if (tid == 128) STAMP(1, 54);
        asm volatile("bar.sync 4, 512;" ::: "memory");
        if (tid == 128) STAMP(1, 55);
        const int cw = wg - 1;
        const int t = tid & 127, w4 = t >> 5, g = lane >> 2, t4 = lane & 3;
        {
            float a0[64], a1[64];
            auto release = [&](int it) {
                if (it < 12 + XTRA && t <= ((it >= 16 - SKEW1 && it < 12) || it >= 16)) mbar_arrive(bar_empty + 8 * (it & 3));
            };
#pragma unroll 1
            for (int kb = 0; kb < 16; ++kb) {
                const int it = cw == 1 && kb >= 16 - SKEW1 ? kb + XTRA : kb, st = it & 3;
                if (cw == 1 && kb == 16 - SKEW1) mbar_wait(bar_ab, 0);
                if (BA && cw == 0 && kb == 16 - SKEW1 - (BA & 1)) mbar_wait(bar_ba, 0);
                mbar_wait(bar_full + 8 * st, (it >> 2) & 1);
                if (kb == 0 && tid == 288) mbar_arrive(bar_tick);
                if (kb == 0 && t == 0) STAMP(1, 14 + cw);
                const uint32_t alo = desc_lo(sbase + (cw ? OFF_BB : OFF_CU) + st * 8192, 16), blo = desc_lo(sbase + ((it - XTRA) & 3) * 32768, 16);
                wgmma_fence();
#pragma unroll
                for (int j = 0; j < 8; ++j) {
                    if (j & 1) wgmma_n128<0>(a1, alo + (j & 6), blo + 1024 + (j & 6), j >> 1 ? 1 : kb);
                    else wgmma_n128<0>(a0, alo + (j & 6), blo + (j & 6), j >> 1 ? 1 : kb);
                    if (j == G1Q - 1) {
                        wgmma_commit();
                        wgmma_wait<1>();
                        if (kb > 0 && !(cw == 1 && kb == 16 - SKEW1)) release(it - 1);
                        if (cw == 1 && kb > 12) {
                            if (kb == 13) mbar_wait(bar_adone, 0);
                            if (t == 0) mbar_arrive(bar_empty2 + 8 * (kb - 13));
                        }
                        if (j < 7) wgmma_fence();
                    }
                }
                if (G1Q < 8) wgmma_commit();
                if ((BA & 2) && kb == 15 - SKEW1 && tid == 320) mbar_arrive(bar_ba);
                if (cw == 1 && kb == 15 - SKEW1) {
                    wgmma_wait<0>();
                    release(it);
                }
            }
            if (tid == 192) mbar_arrive(bar_ab);
            float mr, mi, cr, ci, p32r, p32i;
            uint32_t tag;
            mbar_wait(bar_par, 0);
            {
                const uint32_t par = sbase + OFF_PAR + (cw * 32 + w4 * 8 + g) * 32;
                uint32_t dummy;
                asm volatile("ld.shared.v4.f32 {%0,%1,%2,%3}, [%4];" : "=f"(mr), "=f"(mi), "=f"(cr), "=f"(ci) : "r"(par));
                asm volatile("ld.shared.v4.b32 {%0,%1,%2,%3}, [%4];" : "=f"(p32r), "=f"(p32i), "=r"(tag), "=r"(dummy) : "r"(par + 16));
            }
            const float l1i = SW ? mi : -mi;
            auto map = [&](float p, float q, float& r, float& i) {
                if (SW) { r = fmaf(cr, q, -ci * p); i = fmaf(-cr, p, -ci * q); }
                else { r = fmaf(cr, p, -ci * q); i = fmaf(-cr, q, -ci * p); }
            };
            float p64r = p32r, p64i = p32i;
            csqr(p64r, p64i);
            float p128r = p64r, p128i = p64i;
            csqr(p128r, p128i);
            wgmma_wait<0>();
            fence_regs(a0); fence_regs(a1);
            if (cw == 0) { release(15); if (lane == 0) mbar_arrive(bar_adone); }
            else if (t == 0) mbar_arrive(bar_empty2 + 24);
            if (t == 0) STAMP(1, 2 + 6 * cw);
            float hr = 0.f, hi = 0.f, ar = 0.f, ai = 0.f;
#pragma unroll
            for (int j = 0; j < 16; ++j)
#pragma unroll
                for (int e = 0; e < 2; ++e) {
                    const float nr = fmaf(mr, ar, fmaf(-l1i, ai, a0[4 * j + e])), ni = fmaf(mr, ai, fmaf(l1i, ar, a0[4 * j + 2 + e]));
                    const float or_ = fmaf(mr, hr, fmaf(-l1i, hi, a1[4 * j + e])), oi = fmaf(mr, hi, fmaf(l1i, hr, a1[2 + 4 * j + e]));
                    ar = nr; ai = ni; hr = or_; hi = oi;
                }
            map(ar, ai, ar, ai);
            map(hr, hi, hr, hi);
            hr += p32r * ar - p32i * ai; hi += p32r * ai + p32i * ar;
            {
                float vr = __shfl_up_sync(0xffffffffu, hr, 1, 4), vi = __shfl_up_sync(0xffffffffu, hi, 1, 4);
                if (t4 >= 1) { hr += p64r * vr - p64i * vi; hi += p64r * vi + p64i * vr; }
                vr = __shfl_up_sync(0xffffffffu, hr, 2, 4); vi = __shfl_up_sync(0xffffffffu, hi, 2, 4);
                if (t4 >= 2) { hr += p128r * vr - p128i * vi; hi += p128r * vi + p128i * vr; }
            }
            unsigned long long* ap = &g_agg[ti * D_DIM + cw * 512 + cg * 32 + w4 * 8 + g];
            if (t4 == 3) asm volatile("{\n.reg .b64 a;\nmov.b64 a, {%1, %2};\nst.relaxed.gpu.global.u64 [%0], a;\n}\n" ::"l"(ap),
                                      "r"((__float_as_uint(hr) & ~1u) | (tag & 1u)), "r"((__float_as_uint(hi) & ~1u) | (tag >> 1)) : "memory");
            float exr = __shfl_up_sync(0xffffffffu, hr, 1, 4), exi = __shfl_up_sync(0xffffffffu, hi, 1, 4);
            if (t4 == 0) { exr = 0.f; exi = 0.f; }
            if (t == 0) STAMP(1, 3 + 6 * cw);
            ci = after(ci, exr);
#pragma unroll
            for (int j = 0; j < 16; ++j)
#pragma unroll
                for (int e = 0; e < 2; ++e) {
                    map(a0[4 * j + e], a0[4 * j + 2 + e], a0[4 * j + e], a0[4 * j + 2 + e]);
                    map(a1[4 * j + e], a1[4 * j + 2 + e], a1[4 * j + e], a1[4 * j + 2 + e]);
                }
            float qr = 1.f, qi = 0.f, ur = 1.f, ui = 0.f;
            if (t4 & 1) { qr = p64r; qi = p64i; }
            if (t4 & 2) cmul(qr, qi, qr, qi, p128r, p128i);
            csqr(p128r, p128i);
            if (t4 & 1) { ur = p128r; ui = p128i; }
            csqr(p128r, p128i);
            if (t4 & 2) cmul(ur, ui, ur, ui, p128r, p128i);
            csqr(p128r, p128i);
            fence_regs(a0); fence_regs(a1);
            if (t == 0) STAMP(1, 7 + 6 * cw);
            if (ti > 0) {
                const unsigned long long tmask = 0x0000000100000001ull, tval = ((unsigned long long)(tag >> 1) << 32) | (tag & 1u);
                unsigned long long u0 = tval, u1 = tval;
                ap -= D_DIM * (1 + t4);
                int it = 0;
                do {
                    asm volatile("{\n.reg .pred p, q;\nsetp.gt.s32 p, %3, 0;\nsetp.gt.s32 q, %3, 4;\n@p ld.relaxed.gpu.global.u64 %0, [%2];\n"
                                 "@q ld.relaxed.gpu.global.u64 %1, [%2+-32768];\n}\n" : "+l"(u0), "+l"(u1) : "l"(ap), "r"(ti - t4) : "memory");
                } while (__any_sync(0xffffffffu, (((u0 ^ tval) | (u1 ^ tval)) & tmask) != 0) && ++it < (1 << 22));
                float Pr = __uint_as_float((unsigned)u1 & ~1u), Pi = __uint_as_float((unsigned)(u1 >> 32) & ~1u);
                cmul(Pr, Pi, Pr, Pi, p128r, p128i);
                Pr += __uint_as_float((unsigned)u0 & ~1u); Pi += __uint_as_float((unsigned)(u0 >> 32) & ~1u);
                cmul(Pr, Pi, Pr, Pi, ur, ui);
                Pr += __shfl_xor_sync(0xffffffffu, Pr, 1); Pi += __shfl_xor_sync(0xffffffffu, Pi, 1);
                Pr += __shfl_xor_sync(0xffffffffu, Pr, 2); Pi += __shfl_xor_sync(0xffffffffu, Pi, 2);
                exr += qr * Pr - qi * Pi;
                exi += qr * Pi + qi * Pr;
            }
            if (t == 0) STAMP(1, 4 + 6 * cw);
            char* hp = reinterpret_cast<char*>(g_H) + (size_t)((2 * ti) * 16 + (cg >> 1)) * 16384 + ((cg & 1) * 32 + w4 * 8 + g) * 64 + ((t4 ^ (g >> 1)) << 4);
            float fxr = ar + p32r * exr - p32i * exi, fxi = ai + p32r * exi + p32i * exr;
            const uint32_t hs = sbase + OFF_BB + (w4 * 8 + g) * 64 + ((t4 ^ (g >> 1)) << 4);
            if (cw == 1) named_bar(2, 128);
#pragma unroll
            for (int jj = 0; jj < 4; ++jj) {
                uint32_t pr[4], qq[4], pi[4], qi[4];
#pragma unroll
                for (int j4 = 0; j4 < 4; ++j4) {
                    const int j = jj * 4 + j4;
                    const float r0 = fmaf(mr, exr, fmaf(-mi, exi, a0[4 * j])), i0 = fmaf(mr, exi, fmaf(mi, exr, a0[4 * j + 2]));
                    const float r1 = fmaf(mr, fxr, fmaf(-mi, fxi, a1[4 * j])), i1 = fmaf(mr, fxi, fmaf(mi, fxr, a1[2 + 4 * j]));
                    exr = fmaf(mr, r0, fmaf(-mi, i0, a0[4 * j + 1]));
                    exi = fmaf(mr, i0, fmaf(mi, r0, a0[4 * j + 3]));
                    fxr = fmaf(mr, r1, fmaf(-mi, i1, a1[1 + 4 * j]));
                    fxi = fmaf(mr, i1, fmaf(mi, r1, a1[3 + 4 * j]));
                    pr[j4] = pack_bf16(r0, exr); pi[j4] = pack_bf16(i0, exi);
                    qq[j4] = pack_bf16(r1, fxr); qi[j4] = pack_bf16(i1, fxi);
                }
                if (cw == 0) {
                    stg128(hp + jj * 4096, pr[0], pr[1], pr[2], pr[3]);
                    stg128(hp + jj * 4096 + 262144, qq[0], qq[1], qq[2], qq[3]);
                    stg128(hp + jj * 4096 + 131072, pi[0], pi[1], pi[2], pi[3]);
                    stg128(hp + jj * 4096 + 393216, qi[0], qi[1], qi[2], qi[3]);
                } else {
                    sts128(hs + jj * 2048, pr[0], pr[1], pr[2], pr[3]);
                    sts128(hs + jj * 2048 + 8192, qq[0], qq[1], qq[2], qq[3]);
                    sts128(hs + jj * 2048 + 16384, pi[0], pi[1], pi[2], pi[3]);
                    sts128(hs + jj * 2048 + 24576, qi[0], qi[1], qi[2], qi[3]);
                }
            }
            if (t == 0) STAMP(1, 5 + 6 * cw);
            if (cw == 0) {
                named_bar(1, 128);
                if (t == 0) { red_release(&g_cnt[(2 * ti) * 32], 4); mbar_arrive(bar_rel); }
                if (t == 0) STAMP(1, 6);
                __syncwarp();
            } else {
                fence_async_smem();
                __syncwarp();
                if (lane == 0) mbar_arrive(bar_hw);
            }
            if (t == 0) STAMP(1, 50 + cw);
        }
        if (cw == 0) {
            float c0[64], c1[64];
            wgmma_fence();
#pragma unroll
            for (int i = 0; i < QD2; ++i) wgmma_commit();
            int pst = 0;
            auto kblock = [&](int kb, auto shallow) {
                const int t = fresh_tid() & 127, lane = t & 31;
                const int st = ring_slot(kb);
                mbar_wait(bar_full2 + 8 * st, ring_par(kb));
                if (kb == 0 && t == 0) STAMP(2, 6);
                if (kb == 0 && lane == 0) mbar_arrive(bar_g2);
                const uint32_t alo = desc_lo(sbase + st * 32768, 4096), blo = desc_lo(sbase + st * 32768 + 16384, 16);
                constexpr int Q = decltype(shallow)::value;
#pragma unroll
                for (int j = 0; j < 8; ++j) {
                    wgmma_fence();
                    if (j & 1) wgmma_n128<1>(c1, alo + 512 + 64 * (j >> 1), blo + 2 * (j >> 1), j >> 1 ? 1 : kb);
                    else wgmma_n128<1>(c0, alo + 64 * (j >> 1), blo + 2 * (j >> 1), j >> 1 ? 1 : kb);
                    wgmma_commit();
                    wgmma_wait<Q>();
                    if (j == Q - 1 && kb > 0 && t == 0) mbar_arrive(bar_empty2 + 8 * pst);
                }
                pst = st;
            };
#pragma unroll 1
            for (int kb = 0; kb < QKB; ++kb) kblock(kb, std::integral_constant<int, QD>());
#pragma unroll 1
            for (int kb = QKB; kb < 32 - SKEW2; ++kb) kblock(kb, std::integral_constant<int, QD2>());
            static_assert(SKEW2 <= (SLOT5 < 32 ? 6 : 4), "slot release");
            const uint32_t alo = desc_lo(sbase, 4096), blo = desc_lo(sbase + 16384, 16);
#pragma unroll
            for (int kb = 32 - SKEW2; kb < 32; ++kb) {
                mbar_wait(bar_full2 + 8 * ring_slot(kb), ring_par(kb));
                wgmma_fence();
#pragma unroll
                for (int k = 0; k < 4; ++k) wgmma_n128<1>(c0, alo + ring_slot(kb) * 2048 + 64 * k, blo + ring_slot(kb) * 2048 + 2 * k, 1);
                wgmma_commit();
                if (SLOT5 < 32 && SKEW2 < 6 && kb == 33 - SKEW2) {
                    wgmma_wait<2>();
                    if ((fresh_tid() & 127) == 0) mbar_arrive(bar_o1);
                }
                if (SKEW2 == 6 && kb == 26) {
                    wgmma_wait<1>();
                    if ((fresh_tid() & 127) == 0) mbar_arrive(bar_empty2 + 8 * ring_slot(25));
                }
            }
            auto late = [&](int kb) {
                wgmma_fence();
#pragma unroll
                for (int k = 0; k < 4; ++k) wgmma_n128<1>(c1, alo + 512 + ring_slot(kb) * 2048 + 64 * k, blo + ring_slot(kb) * 2048 + 2 * k, 1);
                wgmma_commit();
            };
            late(32 - SKEW2);
            const int t = fresh_tid() & 127, lane = t & 31, w4 = t >> 5, g = lane >> 2, t4 = lane & 3;
            auto epilogue = [&](const float (&a)[64], int b) {
                const uint32_t ad0 = sbase + (b ? OFF_O1 : OFF_CU) + (w4 * 16 + g) * 128 + (((2 * t4) ^ g) << 4);
                float gt[2];
                uint32_t bv[4][4];
#pragma unroll
                for (int h = 0; h < 2; ++h) gt[h] = __uint_as_float(lds32(sbase + OFF_PAR + (64 * b + 16 * w4 + 8 * h + g) * 4));
#pragma unroll
                for (int i = 0; i < 4; ++i)
                    asm volatile("ld.shared.v4.b32 {%0,%1,%2,%3}, [%4];" : "=r"(bv[i][0]), "=r"(bv[i][1]), "=r"(bv[i][2]), "=r"(bv[i][3])
                                 : "r"(ad0 + (i & 1) * 1024 + (i >> 1) * 8192) : "memory");
                if (b == 0) wgmma_wait<1>(); else wgmma_wait<0>();
                if (b == 0) fence_regs(c0); else fence_regs(c1);
                if (t == 0) STAMP(2, b ? 2 : 5);
#pragma unroll
                for (int jq = 0; jq < 4; ++jq) {
#pragma unroll
                    for (int h = 0; h < 2; ++h) {
                        const uint32_t ad = ad0 + h * 1024 + jq * 8192;
                        uint32_t (&w)[4] = bv[2 * (jq & 1) + h];
                        const int r = 16 * jq + 2 * h;
                        sts128(ad, __float_as_uint(fmaf(gt[h], a[r], bf_lo(w[0]))), __float_as_uint(fmaf(gt[h], a[r + 1], bf_hi(w[0]))),
                               __float_as_uint(fmaf(gt[h], a[r + 4], bf_lo(w[1]))), __float_as_uint(fmaf(gt[h], a[r + 5], bf_hi(w[1]))));
                        sts128(ad ^ 16, __float_as_uint(fmaf(gt[h], a[r + 8], bf_lo(w[2]))), __float_as_uint(fmaf(gt[h], a[r + 9], bf_hi(w[2]))),
                               __float_as_uint(fmaf(gt[h], a[r + 12], bf_lo(w[3]))), __float_as_uint(fmaf(gt[h], a[r + 13], bf_hi(w[3]))));
                        if (jq < 2) asm volatile("ld.shared.v4.b32 {%0,%1,%2,%3}, [%4];" : "=r"(w[0]), "=r"(w[1]), "=r"(w[2]), "=r"(w[3]) : "r"(ad + 16384) : "memory");
                    }
                    fence_async_smem();
                    __syncwarp();
                    if (lane == 0) mbar_arrive(bar_stg + 48 + 32 * b + 8 * jq);
                    if (b == 0 && jq < SKEW2 - 1) late(33 - SKEW2 + jq);
                    if (SKEW2 == 6 && b == 0 && jq == 0) {
                        wgmma_wait<1>();
                        if (t == 0) mbar_arrive(bar_o1);
                    }
                    if (SKEW2 == 6 && b == 0 && jq == 3) late(31);
                }
            };
            mbar_wait(bar_bias, 0);
            if (t == 0) STAMP(2, 4);
            epilogue(c0, 0);
            mbar_wait(bar_bias + 8, 0);
            epilogue(c1, 1);
            if (t == 0) STAMP(2, 7);
            return;
        }
        asm volatile("setmaxnreg.dec.sync.aligned.u32 %0;" ::"n"(REG_C));
    }
    {
        {
            const int t = fresh_tid() & 127, lane = t & 31, w4 = t >> 5;
            Twiddle tw;
            load_twiddle(tw, reinterpret_cast<const uint4*>(g_tw_tab.w) + t);
            const uint32_t lo = (uint32_t)((16 * w4 + (lane & 7)) * 64 + (((lane >> 3) ^ ((lane >> 1) & 3)) << 4));
            const uint32_t tlo = desc_lo(sbase + OFF_CT, 16);
            float dE[32], dO[32];
            int p = wg == 2 ? 2 : 0;
            mbar_wait(bar_stg, 0);
            mbar_wait(bar_tab, 0);
            mbar_wait(bar_k + 8 * p, 0);
            if (t == 0) STAMP(0, wg == 2 ? 50 : 1);
            wgmma_fence();
            conv_s1(dE, dO, tlo, desc_lo(sbase + conv_buf(0) + p * 16384, 8192));
            wgmma_commit();
            wgmma_wait<0>();
            fence_regs(dE); fence_regs(dO);
            named_bar(wg, 128);
#pragma unroll 1
            for (; p < 4; p = 2 * p + 1) {
                const int pn = p < 2 ? 2 * p + 1 : p;
                if (t == 0) STAMP(0, 40 + 2 * p);
                conv_pair(dE, dO, tw, lds32(w_dsk + ((lane & 3) ? 16 : 4 * p)), tlo, sbase + conv_buf(p), sbase + conv_buf(pn), lo, wg,
                                [&]() { mbar_wait(bar_k + 8 * pn, 0); });
                if (lane == 0) mbar_arrive(bar_stg + 16 + 8 * p);
            }
            if (t == 0) STAMP(0, 57 + wg);
            __syncwarp();
        }
        if (wg == 2) {
            {
            const int t = fresh_tid() & 127, lane = t & 31, w4 = t >> 5, g = lane >> 2, t4 = lane & 3;
            const int bid = lds32(w_bid), dt = bid & 7;
            const int trow = (bid >> 4) * 256 + 4 * (bid & 8) + 128 * (w4 & 1) + 8 * (w4 >> 1) + g;
            uint4 xv[16], dk[4];
            const __nv_bfloat16* xp = x + (size_t)trow * D_DIM + dt * 128 + 8 * t4;
#pragma unroll
            for (int i = 0; i < 16; ++i) {
                xv[i] = ldg128(xp + (size_t)(16 * (i >> 3) + 64 * ((i >> 2) & 1)) * D_DIM + 32 * (i & 3));
                if (i & 1) __nanosleep(GAP_X);
            }
#pragma unroll
            for (int jq = 0; jq < 4; ++jq) dk[jq] = ldg128(dskip + dt * 128 + 32 * jq + 8 * t4);
            mbar_wait(bar_fh, 0);
            uint32_t omg[4], g2[4];
#pragma unroll
            for (int i = 0; i < 4; ++i) {
                const float gt = __ldcg(g_gate + trow + 16 * (i >> 1) + 64 * (i & 1));
                if (t4 == 0) asm volatile("st.shared.f32 [%0], %1;" ::"r"(sbase + OFF_PAR + (64 * (i >> 1) + 16 * w4 + 8 * (i & 1) + g) * 4), "f"(gt) : "memory");
                omg[i] = pack_bf16(2.f - 2.f * gt, 2.f - 2.f * gt); g2[i] = pack_bf16(gt, gt);
            }
            if (t == 0) {
                mbar_wait(bar_yrel, 0);
                wait_counter(&g_cnt[(48 + dt) * 32], lds32(w_bid + 4));
                STAMP(0, 16);
                mbar_expect_tx(bar_y1, 24576);
                tma_load_5d(sbase + OFF_CU, &maps.yt3, bar_y1, (bid & 8) * 128 + (bid >> 4) * 128, 0, 0, 0, dt * 4);
                tma_load_5d(sbase + OFF_CU + 12288, &maps.yt3, bar_y1, (bid & 8) * 128 + (bid >> 4) * 128 + 64, 0, 0, 0, dt * 4);
            }
            __syncwarp();
            uint32_t ya = sbase + OFF_CU + (w4 & 1) * 12288 + (lane >> 3) * 3072 + (lane & 7) * 128 + ((((w4 >> 1) ^ ((bid >> 3 & 2) + (w4 & 1))) ^ (lane & 7)) << 4);
            mbar_wait(bar_y1, 0);
            if (t == 0) STAMP(0, 18);
#pragma unroll
            for (int p = 0; p < 3; ++p)
#pragma unroll
                for (int i = 0; i < 4; ++i) {
                    uint32_t yw[4];
                    ldsm_x4_t(yw[0], yw[1], yw[2], yw[3], (ya ^ ((i & 1) << 6) ^ ((i & 2) << 4)) + p * 1024);
#pragma unroll
                    for (int jq = 0; jq < 4; ++jq) {
                        uint32_t& w = (&xv[4 * i + jq].x)[p];
                        w = hfma(g2[i], hmul(w, (&dk[jq].x)[p]), hmul(omg[i], hmul(w, yw[jq])));
                    }
                }
            uint32_t xd[16], yw[16];
#pragma unroll
            for (int i = 0; i < 16; ++i) { xd[i] = hmul(xv[i].w, dk[i & 3].w); asm volatile("" : "+r"(xd[i]), "+r"(xv[i].x), "+r"(xv[i].y), "+r"(xv[i].z)); }
            if (t == 0) STAMP(0, 17);
            ya += 24576 - (w4 & 1) * 8192 - (lane >> 3) * 2048;
            mbar_wait(bar_y, 0);
            if (t == 0) STAMP(0, 6);
#pragma unroll
            for (int i = 0; i < 4; ++i) ldsm_x4_t(yw[4 * i], yw[4 * i + 1], yw[4 * i + 2], yw[4 * i + 3], ya ^ ((i & 1) << 6) ^ ((i & 2) << 4));
            named_bar(2, 128);
#pragma unroll
            for (int i = 0; i < 16; ++i) {
                if (SLOT5 < 32 && i == 8) mbar_wait(bar_o1, 0);
                sts128(sbase + (i & 8 ? OFF_O1 : OFF_CU) + (i & 3) * 8192 + (w4 * 16 + g + (i & 4) * 2) * 128 + (((2 * t4) ^ g) << 4), xv[i].x, xv[i].y, xv[i].z,
                       hfma(g2[i >> 2], xd[i], hmul(omg[i >> 2], hmul(xv[i].w, yw[i]))));
                if ((i & 7) == 7) {
                    __syncwarp();
                    if (lane == 0) mbar_arrive(bar_bias + (i & 8));
                }
            }
            if (t == 0) STAMP(0, 7);
            }
        }
    }
    }
}

void make_map(CUtensorMap* m, const void* ptr, int rank, const cuuint64_t* dims, const cuuint64_t* strides, const cuuint32_t* box,
              CUtensorMapSwizzle swz, bool f32 = false) {
    cuuint32_t es[5] = {1, 1, 1, 1, 1};
    get_encode()(m, f32 ? CU_TENSOR_MAP_DATA_TYPE_FLOAT32 : CU_TENSOR_MAP_DATA_TYPE_BFLOAT16, rank, const_cast<void*>(ptr), dims, strides, box, es,
                 CU_TENSOR_MAP_INTERLEAVE_NONE, swz, CU_TENSOR_MAP_L2_PROMOTION_L2_256B, CU_TENSOR_MAP_FLOAT_OOB_FILL_NONE);
}
void make_map_2d(CUtensorMap* m, const void* ptr, uint64_t inner, uint64_t outer, uint32_t box_in, uint32_t box_out) {
    cuuint64_t dims[2] = {inner, outer};
    cuuint64_t strides[1] = {inner * 2};
    cuuint32_t box[2] = {box_in, box_out};
    make_map(m, ptr, 2, dims, strides, box, CU_TENSOR_MAP_SWIZZLE_128B);
}
void make_map_conv(CUtensorMap* m, const void* p, uint32_t nch = 2) {
    cuuint64_t dims[4] = {32, 32, 2, 1024};
    cuuint64_t strides[3] = {128, 64, 4096};
    cuuint32_t box[4] = {32, 32, 2, nch};
    make_map(m, p, 4, dims, strides, box, CU_TENSOR_MAP_SWIZZLE_64B);
}

}

extern "C" void kernel_launch(void* const* d_in, const int* in_sizes, int n_in, void* d_out, int out_size) {
    const __nv_bfloat16* x = (const __nv_bfloat16*)d_in[0];
    const __nv_bfloat16* lam_re = (const __nv_bfloat16*)d_in[1];
    const __nv_bfloat16* lam_im = (const __nv_bfloat16*)d_in[2];
    const __nv_bfloat16* b_re = (const __nv_bfloat16*)d_in[3];
    const __nv_bfloat16* b_im = (const __nv_bfloat16*)d_in[4];
    const __nv_bfloat16* c_re = (const __nv_bfloat16*)d_in[5];
    const __nv_bfloat16* c_im = (const __nv_bfloat16*)d_in[6];
    const __nv_bfloat16* log_dt = (const __nv_bfloat16*)d_in[7];
    const __nv_bfloat16* dskip = (const __nv_bfloat16*)d_in[8];
    const __nv_bfloat16* kin = (const __nv_bfloat16*)d_in[10];
    const __nv_bfloat16* vin = (const __nv_bfloat16*)d_in[11];
    const __nv_bfloat16* shift_k = (const __nv_bfloat16*)d_in[12];
    const __nv_bfloat16* ssm_k = (const __nv_bfloat16*)d_in[13];
    const __nv_bfloat16* ssm_D = (const __nv_bfloat16*)d_in[14];
    const __nv_bfloat16* gate_w = (const __nv_bfloat16*)d_in[15];
    float* out = (float*)d_out;

    void *yptr = nullptr, *kvtptr = nullptr;
    cudaGetSymbolAddress(&yptr, g_y2);
    cudaGetSymbolAddress(&kvtptr, g_kvT);

    Maps maps;
    {
        cuuint64_t dims[5] = {1024, 2, 4, 32, 8};
        cuuint64_t strides[4] = {2048, 64 * 2048, 2 * 2048, 256 * 2048};
        cuuint32_t box[5] = {64, 2, 4, 32, 1};
        make_map(&maps.x5, x, 5, dims, strides, box, CU_TENSOR_MAP_SWIZZLE_128B);
    }
    int bmode = 0;
    {
        const uint64_t a = (uint64_t)b_re, b = (uint64_t)b_im;
        const uint64_t delta = a < b ? b - a : a - b;
        if (delta != 0 && (delta & 15) == 0 && delta < (1ull << 40)) bmode = a < b ? 1 : 2;
        cuuint64_t dims[4] = {1024, 8, 2, 128};
        cuuint64_t strides[3] = {2048, bmode ? delta : 16, 16384};
        cuuint32_t box[4] = {64, 8, 2, 4};
        make_map(&maps.b4, a < b ? b_re : b_im, 4, dims, strides, box, CU_TENSOR_MAP_SWIZZLE_128B);
    }
    make_map_2d(&maps.bre, b_re, 1024, 1024, 64, 8);
    make_map_2d(&maps.bim, b_im, 1024, 1024, 64, 8);
    {
        cuuint64_t dims[3] = {S_LEN, 128, 8};
        cuuint64_t strides[2] = {8 * 4096, 4096};
        cuuint32_t box[3] = {64, 16, 2};
        make_map(&maps.kvst, kvtptr, 3, dims, strides, box, CU_TENSOR_MAP_SWIZZLE_128B);
    }
    make_map_conv(&maps.sk, ssm_k, 1);
    for (int i = 0; i < 2; ++i) {
        cuuint64_t dims[5] = {1024, 2, 4, 4, 32};
        cuuint64_t strides[4] = {2048, 8 * 2048, 2 * 2048, 32 * 2048};
        cuuint32_t box[5] = {64, 2, 4, 4, 4};
        make_map(i ? &maps.cim : &maps.cre, i ? c_im : c_re, 5, dims, strides, box, CU_TENSOR_MAP_SWIZZLE_128B);
    }
    {
        cuuint64_t dims[5] = {S_LEN, 2, 4, 4, 32};
        cuuint64_t strides[4] = {4096, 8 * 4096, 2 * 4096, 32 * 4096};
        cuuint32_t box[5] = {64, 2, 4, 1, 4};
        make_map(&maps.yt, yptr, 5, dims, strides, box, CU_TENSOR_MAP_SWIZZLE_128B);
        box[3] = 3;
        make_map(&maps.yt3, yptr, 5, dims, strides, box, CU_TENSOR_MAP_SWIZZLE_128B);
    }
    {
        cuuint64_t dims[5] = {D_DIM, 8, 4, 8, 8};
        cuuint64_t strides[4] = {4096, 64 * 4096, 8 * 4096, 256 * 4096};
        cuuint32_t box[5] = {32, 8, 4, 2, 1};
        make_map(&maps.out, out, 5, dims, strides, box, CU_TENSOR_MAP_SWIZZLE_128B, true);
    }

    auto kern = bmode == 1 ? fused_kernel<1> : bmode == 2 ? fused_kernel<2> : fused_kernel<0>;
    cudaFuncSetAttribute(kern, cudaFuncAttributeMaxDynamicSharedMemorySize, SMEM_BYTES);
    static int grid = 0;
    if (!grid) {
        int dev = 0, sms = 0;
        cudaGetDevice(&dev);
        cudaDeviceGetAttribute(&sms, cudaDevAttrMultiProcessorCount, dev);
        grid = sms == 132 ? 132 : 128;
    }
    kern<<<grid, 512, SMEM_BYTES>>>(x, b_re, b_im, kin, vin, ssm_k, shift_k, ssm_D, lam_re, lam_im, log_dt, gate_w, dskip, c_re, c_im, maps);
}
```

```cpp
#include <cuda_runtime.h>
#include <cuda_bf16.h>
#include <cuda.h>
#include <stdint.h>
#include <type_traits>

namespace {
__device__ __forceinline__ uint32_t smem_u32(const void* p) { return (uint32_t)__cvta_generic_to_shared(p); }
__device__ __forceinline__ void mbar_init(uint32_t bar, uint32_t count) {
    asm volatile("mbarrier.init.shared::cta.b64 [%0], %1;" ::"r"(bar), "r"(count) : "memory");
}
__device__ __forceinline__ void mbar_expect_tx(uint32_t bar, uint32_t bytes) {
    asm volatile("mbarrier.arrive.expect_tx.shared::cta.b64 _, [%0], %1;" ::"r"(bar), "r"(bytes) : "memory");
}
__device__ __forceinline__ void mbar_arrive(uint32_t bar) {
    asm volatile("mbarrier.arrive.shared::cta.b64 _, [%0];" ::"r"(bar) : "memory");
}
__device__ __forceinline__ void mbar_wait(uint32_t bar, uint32_t parity) {
    asm volatile(
        "{\n"
        ".reg .pred p;\n"
        ".reg .u32 n;\n"
        "mov.u32 n, 0;\n"
        "LAB_WAIT:\n"
        "mbarrier.try_wait.parity.shared::cta.b64 p, [%0], %1;\n"
        "@p bra LAB_DONE;\n"
        "add.u32 n, n, 1;\n"
        "setp.lt.u32 p, n, 0x400000;\n"
        "@p bra LAB_WAIT;\n"
        "trap;\n"
        "LAB_DONE:\n"
        "}\n" ::"r"(bar), "r"(parity) : "memory");
}
__device__ __forceinline__ void tma_load_2d(uint32_t dst, const CUtensorMap* map, uint32_t bar, int c0, int c1) {
    asm volatile(
        "cp.async.bulk.tensor.2d.shared::cluster.global.mbarrier::complete_tx::bytes [%0], [%1, {%3, %4}], [%2];"
        ::"r"(dst), "l"((uint64_t)map), "r"(bar), "r"(c0), "r"(c1) : "memory");
}
__device__ __forceinline__ void tma_load_4d(uint32_t dst, const CUtensorMap* map, uint32_t bar, int c0, int c1, int c2, int c3) {
    asm volatile(
        "cp.async.bulk.tensor.4d.shared::cluster.global.mbarrier::complete_tx::bytes [%0], [%1, {%3, %4, %5, %6}], [%2];"
        ::"r"(dst), "l"((uint64_t)map), "r"(bar), "r"(c0), "r"(c1), "r"(c2), "r"(c3) : "memory");
}
__device__ __forceinline__ void tma_load_5d(uint32_t dst, const CUtensorMap* map, uint32_t bar, int c0, int c1, int c2, int c3, int c4) {
    asm volatile(
        "cp.async.bulk.tensor.5d.shared::cluster.global.mbarrier::complete_tx::bytes [%0], [%1, {%3, %4, %5, %6, %7}], [%2];"
        ::"r"(dst), "l"((uint64_t)map), "r"(bar), "r"(c0), "r"(c1), "r"(c2), "r"(c3), "r"(c4) : "memory");
}
__device__ __forceinline__ void bulk_load(uint32_t dst, const void* src, uint32_t bytes, uint32_t bar) {
    asm volatile("cp.async.bulk.shared::cluster.global.mbarrier::complete_tx::bytes [%0], [%1], %2, [%3];"
                 ::"r"(dst), "l"(src), "r"(bytes), "r"(bar) : "memory");
}
__device__ __forceinline__ void tma_store_3d(const CUtensorMap* map, uint32_t src, int c0, int c1, int c2) {
    asm volatile("cp.async.bulk.tensor.3d.global.shared::cta.bulk_group [%0, {%2, %3, %4}], [%1];"
                 ::"l"((uint64_t)map), "r"(src), "r"(c0), "r"(c1), "r"(c2) : "memory");
}
__device__ __forceinline__ void bulk_commit() { asm volatile("cp.async.bulk.commit_group;" ::: "memory"); }
__device__ __forceinline__ void bulk_wait0() { asm volatile("cp.async.bulk.wait_group 0;" ::: "memory"); }
__device__ __forceinline__ void bulk_wait_read0() { asm volatile("cp.async.bulk.wait_group.read 0;" ::: "memory"); }
__device__ __forceinline__ void fence_async_smem() { asm volatile("fence.proxy.async.shared::cta;" ::: "memory"); }
__device__ __forceinline__ void named_bar(int id, int n) { asm volatile("bar.sync %0, %1;" ::"r"(id), "r"(n) : "memory"); }
__device__ __forceinline__ void sts128(uint32_t addr, uint32_t a, uint32_t b, uint32_t c, uint32_t d) {
    asm volatile("st.shared.v4.b32 [%0], {%1, %2, %3, %4};" ::"r"(addr), "r"(a), "r"(b), "r"(c), "r"(d) : "memory");
}
__device__ __forceinline__ void prefetch_map(const CUtensorMap* m) {
    asm volatile("prefetch.tensormap [%0];" ::"l"((uint64_t)m) : "memory");
}
__device__ __forceinline__ void wgmma_fence() { asm volatile("wgmma.fence.sync.aligned;" ::: "memory"); }
__device__ __forceinline__ void wgmma_commit() { asm volatile("wgmma.commit_group.sync.aligned;" ::: "memory"); }
template <int N>
__device__ __forceinline__ void wgmma_wait() { asm volatile("wgmma.wait_group.sync.aligned %0;" ::"n"(N) : "memory"); }
template <int N>
__device__ __forceinline__ void fence_regs(float (&a)[N]) {
#pragma unroll
    for (int i = 0; i < N; ++i) asm volatile("" : "+f"(a[i])::"memory");
}
template <int N>
__device__ __forceinline__ void fence_regs(uint32_t (&a)[N]) {
#pragma unroll
    for (int i = 0; i < N; ++i) asm volatile("" : "+r"(a[i])::"memory");
}
#define R8(a, i) "+f"(a[i + 0]), "+f"(a[i + 1]), "+f"(a[i + 2]), "+f"(a[i + 3]), "+f"(a[i + 4]), "+f"(a[i + 5]), "+f"(a[i + 6]), "+f"(a[i + 7])
#define REGS32 "{%0, %1, %2, %3, %4, %5, %6, %7, %8, %9, %10, %11, %12, %13, %14, %15, %16, %17, %18, %19, %20, %21, %22, %23, %24, %25, %26, %27, %28, %29, %30, %31}"
#define REGS16 "{%0, %1, %2, %3, %4, %5, %6, %7, %8, %9, %10, %11, %12, %13, %14, %15}"

__host__ __device__ constexpr uint32_t desc_hi(uint32_t sbo, uint32_t mode) { return (sbo >> 4) | (mode << 30); }
__device__ __forceinline__ uint32_t desc_lo(uint32_t saddr, uint32_t lbo) { return ((saddr & 0x3FFFF) >> 4) | ((lbo >> 4) << 16); }
constexpr uint32_t HI128 = desc_hi(1024, 1), HI64 = desc_hi(512, 2);
#define W8(a, i) "=f"(a[i + 0]), "=f"(a[i + 1]), "=f"(a[i + 2]), "=f"(a[i + 3]), "=f"(a[i + 4]), "=f"(a[i + 5]), "=f"(a[i + 6]), "=f"(a[i + 7])
template <int TA, int TB, int ACC, uint32_t AHI, uint32_t BHI>
__device__ __forceinline__ void wgmma_n64_ss(float (&d)[32], uint32_t alo, uint32_t blo) {
#define N64_TEXT "{\n.reg .pred p;\n.reg .b64 da, db;\nsetp.ne.b32 p, %36, 0;\nmov.b64 da, {%32, %37};\nmov.b64 db, {%33, %38};\n" \
        "wgmma.mma_async.sync.aligned.m64n64k16.f32.bf16.bf16 " REGS32 ", da, db, p, 1, 1, %34, %35;\n}\n"
    if (ACC) asm volatile(N64_TEXT : R8(d, 0), R8(d, 8), R8(d, 16), R8(d, 24) : "r"(alo), "r"(blo), "n"(TA), "n"(TB), "n"(ACC), "n"(AHI), "n"(BHI));
    else asm volatile(N64_TEXT : W8(d, 0), W8(d, 8), W8(d, 16), W8(d, 24) : "r"(alo), "r"(blo), "n"(TA), "n"(TB), "n"(ACC), "n"(AHI), "n"(BHI));
}
template <int ACC, int SA>
__device__ __forceinline__ void wgmma_n32_tt(float (&d)[16], uint32_t alo, uint32_t blo) {
#define N32T_TEXT "{\n.reg .pred p;\n.reg .b64 da, db;\nsetp.ne.b32 p, %18, 0;\nmov.b64 da, {%16, %19};\nmov.b64 db, {%17, %20};\n" \
        "wgmma.mma_async.sync.aligned.m64n32k16.f32.bf16.bf16 " REGS16 ", da, db, p, %21, 1, 1, 1;\n}\n"
    if (ACC) asm volatile(N32T_TEXT : R8(d, 0), R8(d, 8) : "r"(alo), "r"(blo), "n"(ACC), "n"(HI64), "n"(HI128), "n"(SA));
    else asm volatile(N32T_TEXT : W8(d, 0), W8(d, 8) : "r"(alo), "r"(blo), "n"(ACC), "n"(HI64), "n"(HI128), "n"(SA));
}
__device__ __forceinline__ void wgmma_n16_rs(float (&d)[8], const uint32_t (&a)[4], uint32_t blo) {
    asm volatile("{\n.reg .pred p;\n.reg .b64 db;\nsetp.ne.b32 p, 0, 0;\nmov.b64 db, {%12, %13};\n"
        "wgmma.mma_async.sync.aligned.m64n16k16.f32.bf16.bf16 {%0, %1, %2, %3, %4, %5, %6, %7}, {%8, %9, %10, %11}, db, p, 1, 1, 0;\n}\n"
        : W8(d, 0) : "r"(a[0]), "r"(a[1]), "r"(a[2]), "r"(a[3]), "r"(blo), "n"(HI128));
}

__device__ __forceinline__ float bf16r(float x) { return __bfloat162float(__float2bfloat16_rn(x)); }
__device__ __forceinline__ uint32_t pack_bf16(float lo, float hi) {
    __nv_bfloat162 v = __floats2bfloat162_rn(lo, hi);
    return *reinterpret_cast<uint32_t*>(&v);
}
__device__ __forceinline__ __nv_bfloat162 as_bf2(uint32_t w) { return *reinterpret_cast<__nv_bfloat162*>(&w); }
__device__ __forceinline__ uint32_t as_u32(__nv_bfloat162 v) { return *reinterpret_cast<uint32_t*>(&v); }
__device__ __forceinline__ float bf_lo(uint32_t w) { return __uint_as_float(w << 16); }
__device__ __forceinline__ float bf_hi(uint32_t w) { return __uint_as_float(w & 0xFFFF0000u); }
__device__ __forceinline__ void ldsm_x4_t(uint32_t& r0, uint32_t& r1, uint32_t& r2, uint32_t& r3, uint32_t addr) {
    asm volatile("ldmatrix.sync.aligned.m8n8.x4.trans.shared.b16 {%0,%1,%2,%3}, [%4];"
                 : "=r"(r0), "=r"(r1), "=r"(r2), "=r"(r3) : "r"(addr) : "memory");
}
__device__ __forceinline__ void stsm_x4(uint32_t addr, uint32_t r0, uint32_t r1, uint32_t r2, uint32_t r3) {
    asm volatile("stmatrix.sync.aligned.m8n8.x4.shared.b16 [%0], {%1,%2,%3,%4};"
                 ::"r"(addr), "r"(r0), "r"(r1), "r"(r2), "r"(r3) : "memory");
}
__device__ __forceinline__ void stsm_x4_t(uint32_t addr, uint32_t r0, uint32_t r1, uint32_t r2, uint32_t r3) {
    asm volatile("stmatrix.sync.aligned.m8n8.x4.trans.shared.b16 [%0], {%1,%2,%3,%4};"
                 ::"r"(addr), "r"(r0), "r"(r1), "r"(r2), "r"(r3) : "memory");
}
__device__ __forceinline__ uint32_t lds32(uint32_t addr) {
    uint32_t v;
    asm volatile("ld.shared.b32 %0, [%1];" : "=r"(v) : "r"(addr));
    return v;
}

typedef CUresult (*EncodeFn)(CUtensorMap*, CUtensorMapDataType, cuuint32_t, void*, const cuuint64_t*, const cuuint64_t*,
                             const cuuint32_t*, const cuuint32_t*, CUtensorMapInterleave, CUtensorMapSwizzle,
                             CUtensorMapL2promotion, CUtensorMapFloatOOBfill);
EncodeFn get_encode() {
    static EncodeFn fn = nullptr;
    if (!fn) {
        void* p = nullptr;
        cudaDriverEntryPointQueryResult qres;
        cudaGetDriverEntryPoint("cuTensorMapEncodeTiled", &p, cudaEnableDefault, &qres);
        fn = (EncodeFn)p;
    }
    return fn;
}
}
namespace {
constexpr double c_pi = 3.14159265358979323846;
constexpr double c_cos256(int i) {
    i &= 255;
    if (i > 128) i = 256 - i;
    double sgn = 1.0;
    if (i > 64) { i = 128 - i; sgn = -1.0; }
    if (i == 64) return 0.0;
    double x = 2.0 * c_pi * i / 256.0, x2 = x * x, term = 1.0, sum = 1.0;
    for (int k = 1; k < 20; ++k) { term *= -x2 / ((2 * k - 1) * (2 * k)); sum += term; }
    return sgn * sum;
}
constexpr uint32_t c_bf16(double v) {
    if (v == 0.0) return 0u;
    uint32_t s = v < 0 ? 0x8000u : 0u;
    double a = v < 0 ? -v : v;
    int e = 0;
    while (a >= 2.0) { a *= 0.5; ++e; }
    while (a < 1.0) { a *= 2.0; --e; }
    int r = (int)(a * 128.0 + 0.5);
    if (r == 256) { r = 128; ++e; }
    return s | (uint32_t)((e + 127) << 7) | (uint32_t)(r - 128);
}
__host__ __device__ constexpr int conv_k1(int r) { return (r & 8) ? 63 - (((r >> 4) << 3) | (r & 7)) : (((r >> 4) << 3) | (r & 7)); }
struct ConvTab { uint32_t w[96 * 32]; };
constexpr ConvTab make_conv_tab() {
    ConvTab t{};
    uint32_t cs[256] = {};
    for (int i = 0; i < 256; ++i) cs[i] = c_bf16(c_cos256(i));
    for (int n = 0; n < 96; ++n)
        for (int c = 0; c < 64; ++c) {
            int a = 0;
            if (n < 32) {
                const int ro = (n >> 3) & 1, ri = n & 7, co = (c >> 3) & 1, ci = c & 7;
                a = n < 16 ? 8 * ci * (4 * ri + (c >> 4)) : 8 * ri * (4 * ci + (c >> 4));
                a += (ro == co) ? 0 : (ro == 0) ? 192 : 64;
            } else {
                const int r = n - 32, n1 = 2 * (c & 31) + (c >> 5);
                a = n1 * (2 * (((r >> 4) << 3) | (r & 7)) + 1) + ((r & 8) ? 64 : 0);
            }
            const int off = n * 128 + (((c >> 3) ^ (n & 7)) << 4) + (c & 7) * 2;
            t.w[off >> 2] |= cs[a & 255] << ((off & 2) * 8);
        }
    return t;
}
__device__ __align__(128) constexpr ConvTab g_conv_tab = make_conv_tab();

struct Twiddle { uint32_t r[8], i[8], n[8]; };
constexpr double c_cospi(double x) {
    double sgn = 1.0;
    if (x > 0.5) { x = 1.0 - x; sgn = -1.0; }
    const double y = c_pi * x, y2 = y * y;
    double term = 1.0, sum = 1.0;
    for (int k = 1; k < 12; ++k) { term *= -y2 / ((2 * k - 1) * (2 * k)); sum += term; }
    return sgn * sum;
}
struct TwTab { uint32_t w[3072]; };
constexpr TwTab make_tw_tab() {
    TwTab t{};
    for (int th = 0; th < 128; ++th)
        for (int q = 0; q < 8; ++q)
            for (int e = 0; e < 2; ++e) {
                const int k1 = conv_k1(16 * (th >> 5) + 8 * (q & 1) + ((th & 31) >> 2)), n2 = 8 * (q >> 1) + 2 * (th & 3) + e;
                const double x = (double)(n2 * (2 * k1 + 1)) / 4096.0;
                const double cs = c_cospi(x), sn = n2 == 0 ? 0.0 : c_cospi(x > 0.5 ? x - 0.5 : 0.5 - x);
                t.w[((q >> 2) * 128 + th) * 4 + (q & 3)] |= c_bf16(cs * 0.0625) << (16 * e);
                t.w[((2 + (q >> 2)) * 128 + th) * 4 + (q & 3)] |= c_bf16(-sn * 0.0625) << (16 * e);
                t.w[((4 + (q >> 2)) * 128 + th) * 4 + (q & 3)] |= c_bf16(sn * 0.0625) << (16 * e);
            }
    return t;
}
__device__ __align__(128) constexpr TwTab g_tw_tab = make_tw_tab();
__device__ __forceinline__ void load_twiddle(Twiddle& tw, const uint4* p) {
#pragma unroll
    for (int q = 0; q < 2; ++q) {
        const uint4 a = __ldg(p + q * 128);
        const uint4 b = __ldg(p + (2 + q) * 128);
        tw.r[4 * q] = a.x; tw.r[4 * q + 1] = a.y; tw.r[4 * q + 2] = a.z; tw.r[4 * q + 3] = a.w;
        const uint4 n = __ldg(p + (4 + q) * 128);
        tw.n[4 * q] = n.x; tw.n[4 * q + 1] = n.y; tw.n[4 * q + 2] = n.z; tw.n[4 * q + 3] = n.w;
        tw.i[4 * q] = b.x; tw.i[4 * q + 1] = b.y; tw.i[4 * q + 2] = b.z; tw.i[4 * q + 3] = b.w;
    }
}

__device__ __forceinline__ int fresh_tid() { int v; asm volatile("mov.u32 %0, %tid.x;" : "=r"(v)); return v; }
__device__ __forceinline__ uint32_t hmul(uint32_t a, uint32_t b) { return as_u32(__hmul2_rn(as_bf2(a), as_bf2(b))); }
__device__ __forceinline__ uint32_t hadd(uint32_t a, uint32_t b) { return as_u32(__hadd2_rn(as_bf2(a), as_bf2(b))); }
__device__ __forceinline__ uint32_t hsub(uint32_t a, uint32_t b) { return as_u32(__hsub2_rn(as_bf2(a), as_bf2(b))); }
__device__ __forceinline__ uint32_t hfma(uint32_t a, uint32_t b, uint32_t c) { return as_u32(__hfma2(as_bf2(a), as_bf2(b), as_bf2(c))); }

__device__ __forceinline__ void conv_dft8(float (&x)[4][8], const uint32_t (&f)[4][4], uint32_t blo) {
#pragma unroll
    for (int r = 0; r < 4; ++r) wgmma_n16_rs(x[r], f[r], blo + 2 * r);
}
template <class T, int N>
__device__ __forceinline__ void fence_regs4(T (&a)[4][N]) { fence_regs(a[0]); fence_regs(a[1]); fence_regs(a[2]); fence_regs(a[3]); }
__device__ __forceinline__ void conv_s1(float (&dE)[32], float (&dO)[32], uint32_t tlo, uint32_t ulo) {
    wgmma_n64_ss<0, 1, 0, HI128, HI64>(dE, tlo + 256, ulo);
    wgmma_n64_ss<0, 1, 0, HI128, HI64>(dO, tlo + 256 + 4, ulo + 128);
    wgmma_n64_ss<0, 1, 1, HI128, HI64>(dE, tlo + 256 + 2, ulo + 64);
    wgmma_n64_ss<0, 1, 1, HI128, HI64>(dO, tlo + 256 + 6, ulo + 192);
}
template <int S>
__device__ __forceinline__ void conv_t1(const float (&dE)[32], const float (&dO)[32], const Twiddle& tw, float dsk, uint32_t (&f)[4][4]) {
    uint32_t ar[8], ai[8], fs[8], fd[8];
#pragma unroll
    for (int j = 0; j < 4; ++j) {
        const int i = 16 * S + 4 * j;
        const uint32_t e0 = pack_bf16(i == 16 ? dE[i] + dsk : dE[i], dE[i + 1]), e1 = pack_bf16(dE[i + 2], dE[i + 3]);
        const uint32_t o0 = pack_bf16(dO[i], dO[i + 1]), o1 = pack_bf16(dO[i + 2], dO[i + 3]);
        ar[2 * j] = hadd(e0, o0); ai[2 * j] = hadd(e1, o1);
        ar[2 * j + 1] = hsub(e0, o0); ai[2 * j + 1] = hsub(o1, e1);
    }
#pragma unroll
    for (int q = 0; q < 4; ++q) {
        const uint32_t pr = hfma(ar[q], tw.r[q], hmul(ai[q], tw.n[q])), pi = hfma(ar[q], tw.i[q], hmul(ai[q], tw.r[q]));
        fs[q] = hfma(ar[4 + q], tw.r[4 + q], hfma(ai[4 + q], tw.n[4 + q], pr));
        fs[4 + q] = hfma(ar[4 + q], tw.i[4 + q], hfma(ai[4 + q], tw.r[4 + q], pi));
        fd[q] = hfma(pr, 0xC000C000u, fs[q]);
        fd[4 + q] = hfma(pi, 0xC000C000u, fs[4 + q]);
    }
#pragma unroll
    for (int h = 0; h < 2; ++h) {
        f[0][h] = hadd(fs[h], fs[2 + h]); f[0][2 + h] = hadd(fs[4 + h], fs[6 + h]);
        f[2][h] = hsub(fs[h], fs[2 + h]); f[2][2 + h] = hsub(fs[4 + h], fs[6 + h]);
        f[1][h] = hadd(fd[h], fd[6 + h]); f[1][2 + h] = hsub(fd[4 + h], fd[2 + h]);
        f[3][h] = hsub(fd[h], fd[6 + h]); f[3][2 + h] = hadd(fd[4 + h], fd[2 + h]);
    }
}
__device__ __forceinline__ void conv_prod(const float (&xu)[8], const float (&xk)[8], uint32_t (&f)[4]) {
#pragma unroll
    for (int h = 0; h < 2; ++h) {
        float pr[2], pi[2];
#pragma unroll
        for (int e = 0; e < 2; ++e) {
            const float ur = xu[2 * h + e], ui = xu[4 + 2 * h + e], kr = xk[2 * h + e], ki = xk[4 + 2 * h + e];
            pr[e] = fmaf(ur, kr, -ui * ki);
            pi[e] = fmaf(-ur, ki, -ui * kr);
        }
        f[h] = pack_bf16(pr[0], pr[1]);
        f[2 + h] = pack_bf16(pi[0], pi[1]);
    }
}
template <bool SECOND, class G>
__device__ __forceinline__ void conv_channel(float (&dE)[32], float (&dO)[32], const Twiddle& tw, float dsk, uint32_t tlo, uint32_t nxt,
                                             uint32_t wre, uint32_t wim, int bar, G before_next) {
    float xu[4][8], xk[4][8];
    {
        uint32_t fu[4][4], fk[4][4];
        conv_t1<0>(dE, dO, tw, 0.f, fu);
        wgmma_fence();
        conv_dft8(xu, fu, tlo);
        wgmma_commit();
        conv_t1<1>(dE, dO, tw, dsk, fk);
        wgmma_fence();
        conv_dft8(xk, fk, tlo);
        wgmma_commit();
        before_next();
        wgmma_wait<0>();
        fence_regs4(xu); fence_regs4(xk);
        fence_regs4(fu); fence_regs4(fk);
    }
    uint32_t fp[4][4];
#pragma unroll
    for (int r = 0; r < 4; ++r) conv_prod(xu[r], xk[r], fp[r]);
    wgmma_fence();
    conv_dft8(xu, fp, tlo + 128);
    wgmma_commit();
    if (!SECOND || nxt) {
        if (SECOND) wgmma_fence();
        conv_s1(dE, dO, tlo, nxt);
        wgmma_commit();
        wgmma_wait<1>();
    } else {
        wgmma_wait<0>();
#pragma unroll
        for (int i = 0; i < 32; ++i) { dE[i] = 0.f; dO[i] = 0.f; }
        fence_regs(dE); fence_regs(dO);
    }
    fence_regs4(xu);
    fence_regs4(fp);
    uint32_t zr[8], zi[8], wr[8], wi[8];
#pragma unroll
    for (int h = 0; h < 2; ++h) {
        uint32_t yr[4], yi[4];
#pragma unroll
        for (int r = 0; r < 4; ++r) { yr[r] = pack_bf16(xu[r][2 * h], xu[r][2 * h + 1]); yi[r] = pack_bf16(xu[r][4 + 2 * h], xu[r][5 + 2 * h]); }
        const uint32_t u0r = hadd(yr[0], yr[2]), u0i = hadd(yi[0], yi[2]), u1r = hsub(yr[0], yr[2]), u1i = hsub(yi[0], yi[2]);
        const uint32_t v0r = hadd(yr[1], yr[3]), v0i = hadd(yi[1], yi[3]), v1r = hsub(yr[1], yr[3]), v1i = hsub(yi[1], yi[3]);
        zr[h] = hadd(u0r, v0r); zi[h] = hadd(u0i, v0i); zr[4 + h] = hsub(u0r, v0r); zi[4 + h] = hsub(u0i, v0i);
        zr[2 + h] = hadd(u1r, v1i); zi[2 + h] = hsub(u1i, v1r); zr[6 + h] = hsub(u1r, v1i); zi[6 + h] = hadd(u1i, v1r);
    }
#pragma unroll
    for (int q = 0; q < 8; ++q) {
        wr[q] = hfma(zr[q], tw.r[q], hmul(zi[q], tw.n[q]));
        wi[q] = hfma(zr[q], tw.i[q], hmul(zi[q], tw.r[q]));
    }
    if (SECOND) named_bar(bar, 128);
    stsm_x4(wre, hadd(wr[0], wr[1]), hadd(wr[2], wr[3]), hadd(wr[4], wr[5]), hadd(wr[6], wr[7]));
    stsm_x4(wre + 512, hsub(wi[1], wi[0]), hsub(wi[3], wi[2]), hsub(wi[5], wi[4]), hsub(wi[7], wi[6]));
    stsm_x4(wim, hsub(wr[1], wr[0]), hsub(wr[3], wr[2]), hsub(wr[5], wr[4]), hsub(wr[7], wr[6]));
    stsm_x4(wim + 512, hadd(wi[0], wi[1]), hadd(wi[2], wi[3]), hadd(wi[4], wi[5]), hadd(wi[6], wi[7]));
}
template <class G>
__device__ __forceinline__ void conv_pair(float (&dE)[32], float (&dO)[32], const Twiddle& tw, uint32_t dd, uint32_t tlo, uint32_t u0, uint32_t un,
                                          uint32_t lo, int BAR, G before_next) {
    conv_channel<false>(dE, dO, tw, bf_lo(dd), tlo, desc_lo(u0 + 4096, 8192), u0 + lo, u0 + 8192 + lo, BAR, []() {});
    wgmma_wait<0>();
    fence_regs(dE); fence_regs(dO);
    conv_channel<true>(dE, dO, tw, bf_hi(dd), tlo, un == u0 ? 0 : desc_lo(un, 8192), u0 + 4096 + lo, u0 + 12288 + lo, BAR, before_next);
    fence_async_smem();
    named_bar(BAR, 128);
    float ye[16], yo[16];
    wgmma_fence();
    const uint32_t wlo = desc_lo(u0, 4096);
    wgmma_n32_tt<0, 1>(ye, wlo, tlo + 256);
    wgmma_n32_tt<0, -1>(yo, wlo + 512, tlo + 256 + 4);
#pragma unroll
    for (int k = 1; k < 4; ++k) {
        wgmma_n32_tt<1, 1>(ye, wlo + 64 * k, tlo + 256 + 128 * k);
        wgmma_n32_tt<1, -1>(yo, wlo + 512 + 64 * k, tlo + 256 + 4 + 128 * k);
    }
    wgmma_commit();
    wgmma_wait<0>();
    fence_regs(ye); fence_regs(yo);
    fence_regs(dE); fence_regs(dO);
    named_bar(BAR, 128);
    const int t = fresh_tid();
    const uint32_t ya = u0 + (t & 64) * 64 + (t & 31) * 64 + (((((t >> 4) & 2) ^ (t >> 1)) & 3) << 4);
#pragma unroll
    for (int h = 0; h < 2; ++h) {
        stsm_x4_t(ya ^ (16 * h), pack_bf16(ye[2 * h], ye[2 * h + 1]), pack_bf16(ye[4 + 2 * h], ye[5 + 2 * h]),
                  pack_bf16(ye[8 + 2 * h], ye[9 + 2 * h]), pack_bf16(ye[12 + 2 * h], ye[13 + 2 * h]));
        stsm_x4_t((ya ^ (16 * h)) + 2048, pack_bf16(yo[2 * h], yo[2 * h + 1]), pack_bf16(yo[4 + 2 * h], yo[5 + 2 * h]),
                  pack_bf16(yo[8 + 2 * h], yo[9 + 2 * h]), pack_bf16(yo[12 + 2 * h], yo[13 + 2 * h]));
    }
    fence_async_smem();
    __syncwarp();
}
}

namespace {

constexpr int S_LEN = 2048;
constexpr int D_DIM = 1024;

#define REG_P 24
#define REG_AB 168
#define REG_C 152
#define G1Q 4
#define SKEW1 4
#define SKEW2 6
#define QD 4
#define QKB 18
#define QD2 6
#define SLOT4 16
#define SLOT5 27
#define EPF 2
#define PFD 7
#define TK_PF0 0
#define TK_KV0 2
#define TK_KV1 4
#define TK_C 8
#define GAP_PF 300
#define GAP_KV 50
#define GAP_ST 50
#define GAP_CV 100
#define GAP_HB 100
#define GAP_Y 100
#define GAP_X 150
#define ALTMAP 0

__device__ __align__(1024) __nv_bfloat16 g_H[2 * D_DIM * S_LEN];
__device__ __align__(1024) __nv_bfloat16 g_y2[D_DIM * S_LEN];
__device__ __align__(1024) __nv_bfloat16 g_kvT[D_DIM * S_LEN];
__device__ __align__(128) float g_gate[S_LEN];
__device__ __align__(128) unsigned long long g_agg[8 * D_DIM];
__device__ __align__(128) unsigned int g_cnt[56 * 32];

#define STAMP(k, s) do { } while (0)
#define SAMPLE(i) do { } while (0)

__device__ __forceinline__ void tma_store_5d(const CUtensorMap* map, uint32_t src, int c0, int c1, int c2, int c3, int c4) {
    asm volatile("cp.async.bulk.tensor.5d.global.shared::cta.bulk_group [%0, {%2, %3, %4, %5, %6}], [%1];"
                 ::"l"((uint64_t)map), "r"(src), "r"(c0), "r"(c1), "r"(c2), "r"(c3), "r"(c4) : "memory");
}
#define ELECT "{\n.reg .pred p;\nelect.sync _|p, 0xffffffff;\n@p "
__device__ __forceinline__ void e_expect_tx(uint32_t bar, uint32_t bytes) {
    asm volatile(ELECT "mbarrier.arrive.expect_tx.shared::cta.b64 _, [%0], %1;\n}" ::"r"(bar), "r"(bytes) : "memory");
}
__device__ __forceinline__ void e_arrive(uint32_t bar) {
    asm volatile(ELECT "mbarrier.arrive.shared::cta.b64 _, [%0];\n}" ::"r"(bar) : "memory");
}
__device__ __forceinline__ void e_load_4d(uint32_t dst, const CUtensorMap* map, uint32_t bar, int c0, int c1, int c2, int c3) {
    asm volatile(ELECT "cp.async.bulk.tensor.4d.shared::cluster.global.mbarrier::complete_tx::bytes [%0], [%1, {%3, %4, %5, %6}], [%2];\n}"
        ::"r"(dst), "l"((uint64_t)map), "r"(bar), "r"(c0), "r"(c1), "r"(c2), "r"(c3) : "memory");
}
__device__ __forceinline__ void e_load_5d(uint32_t dst, const CUtensorMap* map, uint32_t bar, int c0, int c1, int c2, int c3, int c4) {
    asm volatile(ELECT "cp.async.bulk.tensor.5d.shared::cluster.global.mbarrier::complete_tx::bytes [%0], [%1, {%3, %4, %5, %6, %7}], [%2];\n}"
        ::"r"(dst), "l"((uint64_t)map), "r"(bar), "r"(c0), "r"(c1), "r"(c2), "r"(c3), "r"(c4) : "memory");
}
__device__ __forceinline__ void e_bulk_load(uint32_t dst, const void* src, uint32_t bytes, uint32_t bar) {
    asm volatile(ELECT "cp.async.bulk.shared::cluster.global.mbarrier::complete_tx::bytes [%0], [%1], %2, [%3];\n}"
                 ::"r"(dst), "l"(src), "r"(bytes), "r"(bar) : "memory");
}
__device__ __forceinline__ void l2_prefetch(const void* p, uint32_t bytes) {
    asm volatile("cp.async.bulk.prefetch.L2.global [%0], %1;" ::"l"(p), "r"(bytes) : "memory");
}
__device__ __forceinline__ void l2_prefetch_4d(const CUtensorMap* map, int c0, int c1, int c2, int c3) {
    asm volatile("cp.async.bulk.prefetch.tensor.4d.L2.global [%0, {%1, %2, %3, %4}];" ::"l"((uint64_t)map), "r"(c0), "r"(c1), "r"(c2), "r"(c3) : "memory");
}
__device__ __forceinline__ void l2_prefetch_5d(const CUtensorMap* map, int c0, int c1, int c2, int c3, int c4) {
    asm volatile("cp.async.bulk.prefetch.tensor.5d.L2.global [%0, {%1, %2, %3, %4, %5}];" ::"l"((uint64_t)map), "r"(c0), "r"(c1), "r"(c2), "r"(c3), "r"(c4) : "memory");
}
__device__ __forceinline__ unsigned int ld_relaxed(const unsigned int* p) {
    unsigned int v;
    asm volatile("ld.relaxed.gpu.global.u32 %0, [%1];" : "=r"(v) : "l"(p) : "memory");
    return v;
}
__device__ __forceinline__ void fence_async_global() { asm volatile("fence.proxy.async.global;" ::: "memory"); }
__device__ __forceinline__ void wait_counter(const unsigned int* p, unsigned int target) {
    unsigned int v;
    int it = 0;
    do { asm volatile("ld.acquire.gpu.global.u32 %0, [%1];" : "=r"(v) : "l"(p) : "memory"); } while (v != target && ++it < (1 << 22));
    fence_async_global();
}
__device__ __forceinline__ void red_release(unsigned int* p, unsigned int n) {
    asm volatile("red.release.gpu.global.add.u32 [%0], %1;" ::"l"(p), "r"(n) : "memory");
}
__device__ __forceinline__ uint4 ldg128(const void* p) {
    uint4 v;
    asm volatile("ld.global.nc.v4.u32 {%0,%1,%2,%3}, [%4];" : "=r"(v.x), "=r"(v.y), "=r"(v.z), "=r"(v.w) : "l"(p));
    return v;
}
__device__ __forceinline__ void stg128(void* p, uint32_t a, uint32_t b, uint32_t c, uint32_t d) {
    asm volatile("st.global.v4.b32 [%0], {%1, %2, %3, %4};" ::"l"(p), "r"(a), "r"(b), "r"(c), "r"(d) : "memory");
}

template <int TA>
__device__ __forceinline__ void wgmma_n128(float (&d)[64], uint32_t alo, uint32_t blo, int acc) {
    asm volatile(
        "{\n.reg .pred p;\n.reg .b64 da, db;\nsetp.ne.b32 p, %67, 0;\nmov.b64 da, {%64, %69};\nmov.b64 db, {%65, %66};\n"
        "wgmma.mma_async.sync.aligned.m64n128k16.f32.bf16.bf16 "
        "{%0, %1, %2, %3, %4, %5, %6, %7, %8, %9, %10, %11, %12, %13, %14, %15, "
        "%16, %17, %18, %19, %20, %21, %22, %23, %24, %25, %26, %27, %28, %29, %30, %31, "
        "%32, %33, %34, %35, %36, %37, %38, %39, %40, %41, %42, %43, %44, %45, %46, %47, "
        "%48, %49, %50, %51, %52, %53, %54, %55, %56, %57, %58, %59, %60, %61, %62, %63}, "
        "da, db, p, 1, 1, %68, 0;\n"
        "}\n"
        : R8(d, 0), R8(d, 8), R8(d, 16), R8(d, 24), R8(d, 32), R8(d, 40), R8(d, 48), R8(d, 56)
        : "r"(alo), "r"(blo), "n"(HI128), "r"(acc), "n"(TA), "n"(TA ? HI64 : HI128));
}

constexpr int NST = 6;
constexpr int XTRA = SKEW1 - 4;
static_assert(SKEW1 >= 4 && SKEW1 <= 12, "skew");
constexpr int OFF_BB = 4 * 32768;
constexpr int OFF_CT = 5 * 32768;
constexpr int OFF_CU = OFF_CT + 32768;
__host__ __device__ constexpr uint32_t conv_buf(int p) { return OFF_CT + 16384 + (p == 3 ? 0 : p) * 16384; }
constexpr int OFF_PAR = OFF_CU + 32768;
constexpr int OFF_BAR = OFF_PAR + 2048;
constexpr int SMEM_BYTES = OFF_BAR + 896;
static_assert(SMEM_BYTES <= 232448, "smem layout");

struct Ring { unsigned long long w[2]; };
constexpr Ring make_ring() {
    Ring r{};
    int st = 0, uses[NST] = {};
    for (int kb = 0; kb < 32; ++kb) {
        r.w[kb >> 4] |= (unsigned long long)(st | (uses[st]++ & 1) << 3) << (4 * (kb & 15));
        if (++st >= (kb + 1 < SLOT4 ? 4 : kb + 1 < SLOT5 ? 5 : 6)) st = 0;
    }
    return r;
}
constexpr unsigned long long RING0 = make_ring().w[0], RING1 = make_ring().w[1];
__host__ __device__ constexpr uint32_t ring_code(int kb) { return (uint32_t)((kb < 16 ? RING0 : RING1) >> (4 * (kb & 15))) & 15u; }
__host__ __device__ constexpr int ring_slot(int kb) { return ring_code(kb) & 7; }
__host__ __device__ constexpr uint32_t ring_par(int kb) { return ring_code(kb) >> 3; }
constexpr int OFF_O1 = SLOT5 < 32 ? ring_slot(SKEW2 == 6 ? 26 : 31 - SKEW2) * 32768 : OFF_CT;

struct Maps {
    CUtensorMap x5, b4, cre, cim, sk, yt, yt3, out, kvst, bre, bim;
};

__device__ __forceinline__ void cmul(float& r, float& i, float ar, float ai, float br, float bi) {
    const float a = ar * br - ai * bi, b = ar * bi + ai * br;
    r = a; i = b;
}
__device__ __forceinline__ void csqr(float& r, float& i) { const float a = r * r - i * i, b = 2.f * r * i; r = a; i = b; }
__device__ __forceinline__ float after(float v, float dep) { return __float_as_uint(dep) == 0x7fedcba9u ? dep : v; }

template <int BMODE>
__global__ void __launch_bounds__(512, 1)
fused_kernel(const __nv_bfloat16* __restrict__ x, const __nv_bfloat16* __restrict__ b_re, const __nv_bfloat16* __restrict__ b_im,
             const __nv_bfloat16* __restrict__ kin, const __nv_bfloat16* __restrict__ vin, const __nv_bfloat16* __restrict__ ssm_k,
             const __nv_bfloat16* __restrict__ shift_k, const __nv_bfloat16* __restrict__ ssm_D,
             const __nv_bfloat16* __restrict__ lam_re, const __nv_bfloat16* __restrict__ lam_im,
             const __nv_bfloat16* __restrict__ log_dt, const __nv_bfloat16* __restrict__ gate_w,
             const __nv_bfloat16* __restrict__ dskip,
             const __nv_bfloat16* __restrict__ c_re, const __nv_bfloat16* __restrict__ c_im,
             const __grid_constant__ Maps maps) {
    constexpr bool MERGED = BMODE != 0, SW = BMODE == 2;
    extern __shared__ __align__(1024) unsigned char smem_raw[];
    const uint32_t sbase = smem_u32(smem_raw);
    const uint32_t bar_full = sbase + OFF_BAR;
    const uint32_t bar_empty = bar_full + 32;
    const uint32_t bar_full2 = bar_empty + 32;
    const uint32_t bar_empty2 = bar_full2 + 48;
    const uint32_t bar_k = bar_empty2 + 48;
    const uint32_t bar_tab = bar_k + 32;
    const uint32_t bar_ab = bar_tab + 8;
    const uint32_t bar_adone = bar_ab + 8;
    const uint32_t bar_par = bar_adone + 8;
    const uint32_t bar_y = bar_par + 8;
    const uint32_t bar_rel = bar_y + 8;
    const uint32_t bar_kvrel = bar_rel + 8;
    const uint32_t bar_yrel = bar_kvrel + 8;
    const uint32_t bar_y1 = bar_yrel + 8;
    const uint32_t bar_fh = bar_y1 + 8;
    const uint32_t bar_o1 = bar_fh + 8;
    const uint32_t bar_tick = bar_o1 + 8;
    const uint32_t bar_stg = bar_tick + 104;
    const uint32_t bar_bias = bar_stg + 112;
    const uint32_t bar_hw = bar_bias + 16;
    const uint32_t bar_gate = bar_hw + 8;
    const uint32_t bar_g2 = bar_gate + 8;
    const uint32_t w_bid = bar_full + 600, w_dsk = bar_full + 608, w_ones = bar_full + 640;
    const int tid = threadIdx.x ^ (((threadIdx.x + 128) & 256) ? 0 : 384);
    if (tid == 384) { prefetch_map(&maps.x5); prefetch_map(&maps.b4); }
    if (EPF && (threadIdx.x >> 5) - 1u < EPF && blockIdx.x < 128) {
        const int ln = threadIdx.x & 31;
        const __nv_bfloat16* p = ln < 16 ? x + (size_t)(blockIdx.x * 16 + ln) * D_DIM : ((ln & 8) ? b_im : b_re) + (size_t)(blockIdx.x * 8 + (ln & 7)) * D_DIM;
        asm volatile("prefetch.global.L2 [%0];" ::"l"(p + ((threadIdx.x >> 5) - 1) * 64) : "memory");
    }
    int bid;
    {
        unsigned int sm, nsm;
        asm volatile("mov.u32 %0, %smid;" : "=r"(sm));
        asm volatile("mov.u32 %0, %nsmid;" : "=r"(nsm));
        const int tpc = sm >> 1, q7 = ((tpc - 32) * 37) >> 8;
        const int gp = tpc < 32 ? tpc & 7 : tpc < 60 ? tpc - 31 - 7 * q7 : 0;
        const int ix = tpc < 32 ? tpc >> 3 : tpc < 60 ? q7 + 4 : ALTMAP ? (tpc - 56) ^ 2 : tpc - 58;
        bid = (ALTMAP ? tpc >= 64 : (tpc | 1) == 61) ? 128 : (4 * (gp >> 1) + (ix >> 1)) * 8 + 4 * (gp & 1) + 2 * (ix & 1) + (sm & 1);
        if (gridDim.x != 132 || nsm != 132) bid = blockIdx.x;
    }
    const int tt = bid >> 3, dt = bid & 7;
    const int ti = tt >> 1;
    const int cg = (dt >> 2) * 8 + (tt & 1) * 4 + (dt & 3);
    if (MERGED && threadIdx.x == 0 && bid < 128) {
        mbar_init(bar_full, 1);
        asm volatile("fence.mbarrier_init.release.cluster;" ::: "memory");
        mbar_expect_tx(bar_full, 49152);
        tma_load_4d(sbase + OFF_CU, &maps.b4, bar_full, 0, 0, 0, cg * 4);
        tma_load_5d(sbase + ((0 - XTRA) & 3) * 32768, &maps.x5, bar_full, 0, 0, 0, 0, ti);
        tma_load_4d(sbase + OFF_BB, &maps.b4, bar_full, 0, 0, 0, 64 + cg * 4);
    }
    __syncwarp();
    const int warp = __shfl_sync(0xffffffffu, tid >> 5, 0), wg = warp >> 2, lane = tid & 31;
    if (warp == 12 && bid < 128) {
        if (lane == 0) {
#pragma unroll
            for (int s = MERGED; s < 4; ++s) mbar_init(bar_full + 8 * s, 1);
            asm volatile("fence.mbarrier_init.release.cluster;" ::: "memory");
        }
        __syncwarp();
        asm volatile("bar.arrive 4, 512;" ::: "memory");
        if (MERGED) {
#pragma unroll 1
            for (int it = 1; it < 4; ++it) {
                e_expect_tx(bar_full + 8 * it, 49152);
                e_load_4d(sbase + OFF_CU + it * 8192, &maps.b4, bar_full + 8 * it, it * 64, 0, 0, cg * 4);
                e_load_5d(sbase + ((it - XTRA) & 3) * 32768, &maps.x5, bar_full + 8 * it, it * 64, 0, 0, 0, ti);
                e_load_4d(sbase + OFF_BB + it * 8192, &maps.b4, bar_full + 8 * it, it * 64, 0, 0, 64 + cg * 4);
            }
        }
    }
    if (bid >= 128) {
        if (tid == 0) {
            __nanosleep(2000);
            const unsigned int target = (ld_relaxed(&g_cnt[32 * 32]) & ~63u) + 64u;
            for (int i = 0; i < 8; ++i)
                for (int it = 0; ld_relaxed(&g_cnt[(40 + i) * 32]) != target && it < (1 << 12); ++it) __nanosleep(500);
        }
        return;
    }
    if (wg == 0) {
        asm volatile("setmaxnreg.dec.sync.aligned.u32 %0;" ::"n"(REG_P));
        if (tid == 32) {
            if (sbase & 1023) __trap();
#pragma unroll
            for (int s = 0; s < 4; ++s) mbar_init(bar_empty + 8 * s, 2);
#pragma unroll
            for (int s = 0; s < NST; ++s) { mbar_init(bar_full2 + 8 * s, 1); mbar_init(bar_empty2 + 8 * s, 1); }
            mbar_init(bar_k, 1); mbar_init(bar_k + 8, 1); mbar_init(bar_k + 16, 1); mbar_init(bar_k + 24, 1);
            mbar_init(bar_tab, 1);
            mbar_init(bar_ab, 1);
            mbar_init(bar_adone, 4);
            mbar_init(bar_par, 2);
            asm volatile("fence.mbarrier_init.release.cluster;" ::: "memory");
        } else if (tid == 64) {
#pragma unroll
            for (int s = 0; s < 20; ++s) mbar_init(bar_y + 8 * s, 1);
        } else if (tid == 96) {
#pragma unroll
            for (int s = 0; s < 11; ++s) mbar_init(bar_stg + 8 * s, 4);
        } else if (tid == 0) {
#pragma unroll
            for (int s = 11; s < 19; ++s) mbar_init(bar_stg + 8 * s, 4);
            asm volatile("st.shared.b32 [%0], %1;" ::"r"(w_bid), "r"(bid) : "memory");
        }
        __syncwarp();
        asm volatile("bar.sync 4, 512;" ::: "memory");
        if (warp == 0) {
#pragma unroll 1
            for (int it = MERGED ? 4 : 0; it < 16 + XTRA; ++it) {
                const int st = it & 3, kb = it < 16 ? it : it - SKEW1;
                const bool fa = it < 16, fb = it < 16 - SKEW1 || it >= 12;
                const uint32_t bf = bar_full + 8 * st;
                mbar_wait(bar_empty + 8 * st, ((it >> 2) & 1) ^ 1);
                e_expect_tx(bf, fa && fb ? 49152 : 40960);
                e_load_5d(sbase + ((it - XTRA) & 3) * 32768, &maps.x5, bf, kb * 64, 0, 0, 0, ti);
                if (MERGED) {
                    if (fa) e_load_4d(sbase + OFF_CU + st * 8192, &maps.b4, bf, kb * 64, 0, 0, cg * 4);
                    if (fb) e_load_4d(sbase + OFF_BB + st * 8192, &maps.b4, bf, kb * 64, 0, 0, 64 + cg * 4);
                } else {
                    if (lane < 16 && ((lane & 8) ? fb : fa))
                        tma_load_2d(sbase + ((lane & 8) ? OFF_BB : OFF_CU) + st * 8192 + (lane & 7) * 1024, (lane & 1) ? &maps.bim : &maps.bre, bf,
                                    kb * 64, (lane >> 3) * 512 + cg * 32 + ((lane & 7) >> 1) * 8);
                    __syncwarp();
                }
                if (it >= 4 && it < 16) e_arrive(bar_tick + 8 * (it - 3));
                if (lane == 0) STAMP(1, 16 + it);
                if (lane == 0 && it < 16) SAMPLE(it - 3);
            }
#pragma unroll 1
            for (int kb = 0; kb < 32; ++kb) {
                const int st = ring_slot(kb);
                const uint32_t bf = bar_full2 + 8 * st;
                mbar_wait(bar_empty2 + 8 * st, ring_par(kb));
                e_expect_tx(bf, 32768);
                e_load_5d(sbase + st * 32768 + 16384, &maps.cre + ((kb >> 3) & 1), bf, ((kb >> 4) * 8 + (kb & 7)) * 64, 0, 0, 0, dt * 4);
                if (lane == 0) STAMP(2, 16 + kb);
                if (lane == 0 && (kb & 3) == 0) SAMPLE(13 + (kb >> 2));
            }
        } else if (warp == 1) {
            if (MERGED && PFD && lane == 0) {
#pragma unroll 1
                for (int n = -1; n + PFD < 16; ++n) {
                    if (n >= 0) mbar_wait(bar_tick + 8 * n, 0);
                    if (cg >= 4 && (cg < 6 ? -1 : max(cg - PFD, 0)) == n) l2_prefetch_5d(&maps.x5, cg * 64, 0, 0, 0, ti);
                    if (ti >= 2 && (ti < 3 ? -1 : max(2 * ti - PFD, 0)) == n) {
#pragma unroll 1
                        for (int i = 0; i < 4; ++i) l2_prefetch_4d(&maps.b4, (2 * ti + (i >> 1)) * 64, 0, 0, (i & 1) * 64 + cg * 4);
                    }
                }
            }
            __syncwarp();
            const char* hp = reinterpret_cast<const char*>(g_H) + (size_t)tt * 262144;
            mbar_wait(bar_adone, 0);
            e_expect_tx(bar_k + 8, 16384);
            e_expect_tx(bar_k + 16, 16384);
#pragma unroll 1
            for (int c = 2; c < 6; ++c) {
                e_load_4d(sbase + conv_buf(0) + (c >> 1) * 16384 + (c & 1) * 4096 + 8192, &maps.sk, bar_k + 8 * (c >> 1), 0, 0, 0, bid * 8 + c);
                if (GAP_CV) __nanosleep(GAP_CV);
            }
            mbar_wait(bar_kvrel, 0);
            const unsigned int target = lds32(w_bid + 4);
            mbar_wait(bar_rel, 0);
#pragma unroll 1
            for (int q = 0; q < 2; ++q) {
                if (lane == 0) STAMP(0, 8 + 4 * q);
                if (q == 0) wait_counter(&g_cnt[(2 * ti) * 32], target);
                else { mbar_wait(bar_fh, 0); fence_async_global(); }
                if (lane == 0) STAMP(0, 9 + 4 * q);
#pragma unroll 1
                for (int kb = 0; kb < 16; ++kb) {
                    const int st = ring_slot(16 * q + kb);
                    mbar_wait(bar_empty2 + 8 * st, ring_par(16 * q + kb));
                    e_bulk_load(sbase + st * 32768, hp + kb * 16384, 16384, bar_full2 + 8 * st);
                }
                hp += 4194304;
            }
        } else if (warp == 2) {
            if (lane == 0) {
                mbar_wait(bar_tick + 8, 0);
                const unsigned int target = (ld_relaxed(&g_cnt[(40 + dt) * 32]) & ~63u) + 64u;
                asm volatile("st.shared.b32 [%0], %1;" ::"r"(w_bid + 4), "r"(target) : "memory");
                prefetch_map(&maps.kvst); prefetch_map(&maps.sk);
#pragma unroll 1
                for (int bt = 0; bt < 2; ++bt) {
                    mbar_wait(bar_stg + 8 * bt, 0);
#pragma unroll 1
                    for (int i = 0; i < 4; ++i) {
                        if (i) __nanosleep(GAP_ST);
                        tma_store_3d(&maps.kvst, sbase + OFF_CT + bt * 16384 + i * 4096, (tt & 1) * 1024 + ti * 128 + 64 * bt, dt * 16, 2 * i);
                    }
                    bulk_commit();
                }
                bulk_wait0();
                fence_async_global();
                red_release(&g_cnt[(40 + dt) * 32], 4);
                mbar_arrive(bar_kvrel);
                STAMP(0, 23);
                mbar_expect_tx(bar_tab, 12288);
                bulk_load(sbase + OFF_CT, &g_conv_tab, 12288, bar_tab);
                mbar_expect_tx(bar_k, 16384);
                tma_load_4d(sbase + conv_buf(0) + 8192, &maps.sk, bar_k, 0, 0, 0, bid * 8);
                tma_load_4d(sbase + conv_buf(0) + 12288, &maps.sk, bar_k, 0, 0, 0, bid * 8 + 1);
                wait_counter(&g_cnt[(40 + (bid >> 4)) * 32], target);
                STAMP(0, 19);
#pragma unroll 1
                for (int p = 0; p < 3; ++p) {
                    if (p == 1) mbar_wait(bar_adone, 0);
                    bulk_load(sbase + conv_buf(p), g_kvT + (size_t)(bid * 8 + 2 * p) * 2048, 8192, bar_k + 8 * p);
                    if (GAP_CV) __nanosleep(GAP_CV);
                }
                prefetch_map(&maps.out); prefetch_map(&maps.yt); prefetch_map(&maps.yt3);
#pragma unroll 1
                for (int p = 0; p < 4; ++p) {
                    mbar_wait(bar_stg + 16 + 8 * p, 0);
                    if (p == 0) {
                        mbar_expect_tx(bar_k + 24, 16384);
                        tma_load_4d(sbase + conv_buf(3) + 8192, &maps.sk, bar_k + 24, 0, 0, 0, bid * 8 + 6);
                        mbar_wait(bar_g2, 0);
                        tma_load_4d(sbase + conv_buf(3) + 12288, &maps.sk, bar_k + 24, 0, 0, 0, bid * 8 + 7);
                    }
#pragma unroll 1
                    for (int i = 0; i < 2; ++i) {
                        if (i) __nanosleep(GAP_Y);
                        asm volatile("cp.async.bulk.global.shared::cta.bulk_group [%0], [%1], 4096;"
                                     ::"l"(g_y2 + (size_t)(bid * 8 + 2 * p + i) * 2048), "r"(sbase + conv_buf(p) + i * 4096) : "memory");
                    }
                    bulk_commit();
                    STAMP(0, 24 + p);
                    if (p == 0) {
                        bulk_wait_read0();
                        bulk_load(sbase + conv_buf(3), g_kvT + (size_t)(bid * 8 + 6) * 2048, 8192, bar_k + 24);
                    }
                    if (p == 2) {
                        bulk_wait0();
                        fence_async_global();
                        red_release(&g_cnt[(48 + (bid >> 4)) * 32], 4);
                        mbar_arrive(bar_yrel);
                        STAMP(0, 3);
                    }
                }
                bulk_wait0();
                mbar_arrive(bar_empty2 + 40);
                fence_async_global();
                red_release(&g_cnt[(32 + (bid >> 4)) * 32], 4);
                STAMP(0, 2);
                wait_counter(&g_cnt[(32 + dt) * 32], target);
                STAMP(0, 5);
                mbar_expect_tx(bar_y, 8192);
#pragma unroll 1
                for (int i = 6; i < 8; ++i)
                    tma_load_5d(sbase + OFF_CU + i * 4096, &maps.yt, bar_y, (tt & 1) * 1024 + ti * 128 + (i & 1) * 64, 0, 0, i >> 1, dt * 4);
#pragma unroll 1
                for (int i = 0; i < 8; ++i) {
                    mbar_wait(bar_stg + 48 + 8 * i, 0);
                    tma_store_5d(&maps.out, sbase + ((i & 4) ? OFF_O1 : OFF_CU) + (i & 3) * 8192, dt * 128 + (i & 3) * 32, 0, 0, (tt & 1) * 4 + ((i & 4) >> 1), ti);
                    bulk_commit();
                }
                bulk_wait_read0();
                STAMP(2, 3);
                SAMPLE(21);
            }
        } else if (lane == 0) {
            mbar_wait(bar_tick + 8 * TK_PF0, 0);
#pragma unroll 1
            for (int i = 0; i < 8; ++i) {
                l2_prefetch(((i & 1) ? vin : kin) + (size_t)(ti * 256 + 32 * (i & 4) + (bid & 15) * 8 + 2 * (i & 2)) * D_DIM, 8192);
                __nanosleep(GAP_PF);
            }
            if (bid < 3) l2_prefetch(reinterpret_cast<const char*>(&g_conv_tab) + bid * 4096, 4096);
            prefetch_map(&maps.cre); prefetch_map(&maps.cim);
            mbar_wait(bar_tick + 8 * TK_C, 0);
#pragma unroll 1
            for (int i = 0; i < 8; ++i) {
                l2_prefetch((i & 1) ? ((i & 4) ? c_im : c_re) + (size_t)bid * 8192 + (i & 2) * 2048 : ssm_k + (size_t)bid * 16384 + (i >> 1) * 4096, 8192);
                __nanosleep(GAP_PF);
            }
            const unsigned int target = (ld_relaxed(&g_cnt[(2 * ti + 1) * 32]) & ~63u) + 64u;
            mbar_wait(bar_gate, 0);
            mbar_wait(bar_hw, 0);
            mbar_wait(bar_g2, 0);
            char* hp = reinterpret_cast<char*>(g_H) + (size_t)((16 + 2 * ti) * 16 + (cg >> 1)) * 16384 + (cg & 1) * 2048;
#pragma unroll 1
            for (int i = 0; i < 16; ++i) {
                asm volatile("cp.async.bulk.global.shared::cta.bulk_group [%0], [%1], 2048;"
                             ::"l"(hp + (i & 3) * 4096 + ((i >> 2) & 1) * 262144 + (i >> 3) * 131072), "r"(sbase + OFF_BB + i * 2048) : "memory");
                __nanosleep(GAP_HB);
            }
            bulk_commit();
            bulk_wait0();
            mbar_arrive(bar_empty2 + 32);
            fence_async_global();
            red_release(&g_cnt[(2 * ti + 1) * 32], 4);
            STAMP(0, 38);
            wait_counter(&g_cnt[(2 * ti + 1) * 32], target);
            mbar_arrive(bar_fh);
        }
    } else {
    if (wg == 3) {
        if (warp != 12) asm volatile("bar.sync 4, 512;" ::: "memory");
        named_bar(3, 128);
        asm volatile("setmaxnreg.inc.sync.aligned.u32 %0;" ::"n"(REG_C));
        const int t = tid & 127, w4 = t >> 5;
        if (t == 0) SAMPLE(0);
        mbar_wait(bar_tick, 0);
        if (t < 64) {
            const int ch = (t >> 5) * 512 + cg * 32 + (t & 31);
            unsigned long long oldagg;
            asm volatile("ld.relaxed.gpu.global.u64 %0, [%1];" : "=l"(oldagg) : "l"(&g_agg[ti * D_DIM + ch]) : "memory");
            const float Lr = __bfloat162float(lam_re[ch]), Li = __bfloat162float(lam_im[ch]);
            const float dtv = bf16r(expf(__bfloat162float(log_dt[ch])));
            const unsigned int tag = ((((unsigned int)oldagg & 1u) | ((unsigned int)(oldagg >> 31) & 2u)) + 1u) & 3u;
            const float er = expf(dtv * Lr);
            float s, c;
            sincospif(dtv * Li * 0.318309886183790672f, &s, &c);
            const float lr = er * c, li = er * s;
            const float nr = lr - 1.f, ni = li;
            const float den = Lr * Lr + Li * Li;
            const float cr = 2.f * (nr * Lr + ni * Li) / den, ci = 2.f * (ni * Lr - nr * Li) / den;
            float pr = lr, pi = -li;
#pragma unroll
            for (int i = 0; i < 5; ++i) csqr(pr, pi);
            sts128(sbase + OFF_PAR + t * 32, __float_as_uint(lr), __float_as_uint(-li), __float_as_uint(cr), __float_as_uint(ci));
            sts128(sbase + OFF_PAR + t * 32 + 16, __float_as_uint(pr), __float_as_uint(pi), tag, 0);
            __syncwarp();
            if (lane == 0) mbar_arrive(bar_par);
        }
        if (t >= 120) asm volatile("st.shared.b32 [%0], %1;" ::"r"(w_dsk - 480 + 4 * t),
                                   "r"(t < 124 ? __ldg(reinterpret_cast<const uint32_t*>(ssm_D + bid * 8) + (t & 3)) : 0u) : "memory");
        if (t < 64) asm volatile("st.shared.b32 [%0], %1;" ::"r"(w_ones + 4 * t), "r"(0x3F803F80u) : "memory");
        {
            const int cq = lane & 15, rg = (lane >> 4) + 2 * w4;
            uint32_t sk[4][4];
#pragma unroll
            for (int c = 0; c < 4; ++c) {
                const uint4 w = ldg128(shift_k + (size_t)(dt * 128 + 8 * cq + 2 * c) * 4);
                sk[0][c] = __byte_perm(w.x, w.z, 0x5410); sk[1][c] = __byte_perm(w.x, w.z, 0x7632);
                sk[2][c] = __byte_perm(w.y, w.w, 0x5410); sk[3][c] = __byte_perm(w.y, w.w, 0x7632);
            }
#pragma unroll 1
            for (int bt = 0; bt < 2; ++bt) {
                const int t0 = ti * 256 + 128 * bt + 16 * (rg & 4) + 32 * (tt & 1) + 8 * (rg & 3);
                mbar_wait(bar_tick + 8 * (bt ? TK_KV1 : TK_KV0), 0);
                if (t == 0) STAMP(0, 30 + 3 * bt);
                uint4 kk[11], vv[8];
                const __nv_bfloat16* kp = kin + (size_t)t0 * D_DIM + dt * 128 + 8 * cq;
                const __nv_bfloat16* vp = vin + (size_t)t0 * D_DIM + dt * 128 + 8 * cq;
#pragma unroll
                for (int i = 0; i < 11; ++i) {
                    if (i < 3 && t0 == 0) kk[i] = make_uint4(0, 0, 0, 0);
                    else kk[i] = ldg128(kp + (i - 3) * D_DIM);
                    if (i == 6 || i == 10) __nanosleep(GAP_KV);
                }
#pragma unroll
                for (int i = 0; i < 8; ++i) { vv[i] = ldg128(vp + i * D_DIM); if (i == 3) __nanosleep(GAP_KV); }
                const uint32_t ua = sbase + OFF_CT + bt * 16384 + cq * 128 + ((rg ^ ((2 * ti + bt) & 3) ^ (cq & 7)) << 4);
#pragma unroll
                for (int c = 0; c < 4; ++c) {
                    uint32_t res[8];
#pragma unroll
                    for (int i = 0; i < 8; ++i) {
                        uint32_t ks = hmul((&kk[i].x)[c], sk[3][c]);
                        ks = hfma((&kk[i + 1].x)[c], sk[2][c], ks);
                        ks = hfma((&kk[i + 2].x)[c], sk[1][c], ks);
                        ks = hfma((&kk[i + 3].x)[c], sk[0][c], ks);
                        res[i] = hmul(ks, (&vv[i].x)[c]);
                    }
                    sts128(ua + (2 * c) * 2048, __byte_perm(res[0], res[1], 0x5410), __byte_perm(res[2], res[3], 0x5410),
                           __byte_perm(res[4], res[5], 0x5410), __byte_perm(res[6], res[7], 0x5410));
                    sts128(ua + (2 * c + 1) * 2048, __byte_perm(res[0], res[1], 0x7632), __byte_perm(res[2], res[3], 0x7632),
                           __byte_perm(res[4], res[5], 0x7632), __byte_perm(res[6], res[7], 0x7632));
                }
                fence_async_smem();
                __syncwarp();
                if (lane == 0) mbar_arrive(bar_stg + 8 * bt);
                if (t == 0) STAMP(0, 21 + bt);
            }
        }
        {
            const int row = bid * 16 + (t >> 3);
            uint4 xv[16];
#pragma unroll
            for (int n = 0; n < 16; ++n) {
                xv[n] = ldg128(x + (size_t)row * D_DIM + ((t & 7) + 8 * n) * 8);
                if ((n & 3) == 3) __nanosleep(GAP_KV);
            }
#pragma unroll
            for (int n8 = 0; n8 < 16; n8 += 8) {
                uint4 wv[8];
#pragma unroll
                for (int n = 0; n < 8; ++n) wv[n] = ldg128(gate_w + ((t & 7) + 8 * (n8 + n)) * 8);
#pragma unroll
                for (int n = 0; n < 8; ++n) {
                    uint4& p = xv[n8 + n];
                    p.x = hmul(p.x, wv[n].x); p.y = hmul(p.y, wv[n].y); p.z = hmul(p.z, wv[n].z); p.w = hmul(p.w, wv[n].w);
                }
            }
            float d[4] = {0.f, 0.f, 0.f, 0.f};
            fence_regs(d);
            named_bar(3, 128);
            wgmma_fence();
#pragma unroll
            for (int n = 0; n < 16; ++n)
                asm volatile("{\n.reg .b64 db;\nmov.b64 db, {%8, 8};\n"
                             "wgmma.mma_async.sync.aligned.m64n8k16.f32.bf16.bf16 {%0, %1, %2, %3}, {%4, %5, %6, %7}, db, 1, 1, 1, 0;\n}\n"
                             : "+f"(d[0]), "+f"(d[1]), "+f"(d[2]), "+f"(d[3]) : "r"(xv[n].x), "r"(xv[n].y), "r"(xv[n].z), "r"(xv[n].w), "r"(desc_lo(w_ones, 128)));
            wgmma_commit();
            wgmma_wait<0>();
            fence_regs(d);
#pragma unroll
            for (int n = 0; n < 16; ++n) asm volatile("" ::"r"(xv[n].x), "r"(xv[n].y), "r"(xv[n].z), "r"(xv[n].w) : "memory");
            float sum = d[0] + d[2];
            sum += __shfl_xor_sync(0xffffffffu, sum, 4);
            if ((t & 7) == 0) g_gate[row] = bf16r(1.f / (1.f + expf(-bf16r(sum))));
            if (t == 0) STAMP(0, 4);
            __syncwarp();
            if (lane == 0) mbar_arrive(bar_gate);
        }
    } else {
        asm volatile("setmaxnreg.inc.sync.aligned.u32 %0;" ::"n"(REG_AB));
        if (tid == 128) STAMP(1, 54);
        asm volatile("bar.sync 4, 512;" ::: "memory");
        if (tid == 128) STAMP(1, 55);
        const int cw = wg - 1;
        const int t = tid & 127, w4 = t >> 5, g = lane >> 2, t4 = lane & 3;
        {
            float a0[64], a1[64];
            auto release = [&](int it) {
                if (it < 12 + XTRA && t <= ((it >= 16 - SKEW1 && it < 12) || it >= 16)) mbar_arrive(bar_empty + 8 * (it & 3));
            };
#pragma unroll 1
            for (int kb = 0; kb < 16; ++kb) {
                const int it = cw == 1 && kb >= 16 - SKEW1 ? kb + XTRA : kb, st = it & 3;
                if (cw == 1 && kb == 16 - SKEW1) mbar_wait(bar_ab, 0);
                mbar_wait(bar_full + 8 * st, (it >> 2) & 1);
                if (kb == 0 && tid == 288) mbar_arrive(bar_tick);
                if (kb == 0 && t == 0) STAMP(1, 14 + cw);
                const uint32_t alo = desc_lo(sbase + (cw ? OFF_BB : OFF_CU) + st * 8192, 16), blo = desc_lo(sbase + ((it - XTRA) & 3) * 32768, 16);
                wgmma_fence();
#pragma unroll
                for (int j = 0; j < 8; ++j) {
                    if (j & 1) wgmma_n128<0>(a1, alo + (j & 6), blo + 1024 + (j & 6), j >> 1 ? 1 : kb);
                    else wgmma_n128<0>(a0, alo + (j & 6), blo + (j & 6), j >> 1 ? 1 : kb);
                    if (j == G1Q - 1) {
                        wgmma_commit();
                        wgmma_wait<1>();
                        if (kb > 0 && !(cw == 1 && kb == 16 - SKEW1)) release(it - 1);
                        if (cw == 1 && kb > 12) {
                            if (kb == 13) mbar_wait(bar_adone, 0);
                            if (t == 0) mbar_arrive(bar_empty2 + 8 * (kb - 13));
                        }
                        if (j < 7) wgmma_fence();
                    }
                }
                if (G1Q < 8) wgmma_commit();
                if (cw == 1 && kb == 15 - SKEW1) {
                    wgmma_wait<0>();
                    release(it);
                }
            }
            if (tid == 192) mbar_arrive(bar_ab);
            float mr, mi, cr, ci, p32r, p32i;
            uint32_t tag;
            mbar_wait(bar_par, 0);
            {
                const uint32_t par = sbase + OFF_PAR + (cw * 32 + w4 * 8 + g) * 32;
                uint32_t dummy;
                asm volatile("ld.shared.v4.f32 {%0,%1,%2,%3}, [%4];" : "=f"(mr), "=f"(mi), "=f"(cr), "=f"(ci) : "r"(par));
                asm volatile("ld.shared.v4.b32 {%0,%1,%2,%3}, [%4];" : "=f"(p32r), "=f"(p32i), "=r"(tag), "=r"(dummy) : "r"(par + 16));
            }
            const float l1i = SW ? mi : -mi;
            auto map = [&](float p, float q, float& r, float& i) {
                if (SW) { r = fmaf(cr, q, -ci * p); i = fmaf(-cr, p, -ci * q); }
                else { r = fmaf(cr, p, -ci * q); i = fmaf(-cr, q, -ci * p); }
            };
            float p64r = p32r, p64i = p32i;
            csqr(p64r, p64i);
            float p128r = p64r, p128i = p64i;
            csqr(p128r, p128i);
            wgmma_wait<0>();
            fence_regs(a0); fence_regs(a1);
            if (cw == 0) { release(15); if (lane == 0) mbar_arrive(bar_adone); }
            else if (t == 0) mbar_arrive(bar_empty2 + 24);
            if (t == 0) STAMP(1, 2 + 6 * cw);
            float hr = 0.f, hi = 0.f, ar = 0.f, ai = 0.f;
#pragma unroll
            for (int j = 0; j < 16; ++j)
#pragma unroll
                for (int e = 0; e < 2; ++e) {
                    const float nr = fmaf(mr, ar, fmaf(-l1i, ai, a0[4 * j + e])), ni = fmaf(mr, ai, fmaf(l1i, ar, a0[4 * j + 2 + e]));
                    const float or_ = fmaf(mr, hr, fmaf(-l1i, hi, a1[4 * j + e])), oi = fmaf(mr, hi, fmaf(l1i, hr, a1[2 + 4 * j + e]));
                    ar = nr; ai = ni; hr = or_; hi = oi;
                }
            map(ar, ai, ar, ai);
            map(hr, hi, hr, hi);
            hr += p32r * ar - p32i * ai; hi += p32r * ai + p32i * ar;
            {
                float vr = __shfl_up_sync(0xffffffffu, hr, 1, 4), vi = __shfl_up_sync(0xffffffffu, hi, 1, 4);
                if (t4 >= 1) { hr += p64r * vr - p64i * vi; hi += p64r * vi + p64i * vr; }
                vr = __shfl_up_sync(0xffffffffu, hr, 2, 4); vi = __shfl_up_sync(0xffffffffu, hi, 2, 4);
                if (t4 >= 2) { hr += p128r * vr - p128i * vi; hi += p128r * vi + p128i * vr; }
            }
            unsigned long long* ap = &g_agg[ti * D_DIM + cw * 512 + cg * 32 + w4 * 8 + g];
            if (t4 == 3) asm volatile("{\n.reg .b64 a;\nmov.b64 a, {%1, %2};\nst.relaxed.gpu.global.u64 [%0], a;\n}\n" ::"l"(ap),
                                      "r"((__float_as_uint(hr) & ~1u) | (tag & 1u)), "r"((__float_as_uint(hi) & ~1u) | (tag >> 1)) : "memory");
            float exr = __shfl_up_sync(0xffffffffu, hr, 1, 4), exi = __shfl_up_sync(0xffffffffu, hi, 1, 4);
            if (t4 == 0) { exr = 0.f; exi = 0.f; }
            if (t == 0) STAMP(1, 3 + 6 * cw);
            ci = after(ci, exr);
#pragma unroll
            for (int j = 0; j < 16; ++j)
#pragma unroll
                for (int e = 0; e < 2; ++e) {
                    map(a0[4 * j + e], a0[4 * j + 2 + e], a0[4 * j + e], a0[4 * j + 2 + e]);
                    map(a1[4 * j + e], a1[4 * j + 2 + e], a1[4 * j + e], a1[4 * j + 2 + e]);
                }
            float qr = 1.f, qi = 0.f, ur = 1.f, ui = 0.f;
            if (t4 & 1) { qr = p64r; qi = p64i; }
            if (t4 & 2) cmul(qr, qi, qr, qi, p128r, p128i);
            csqr(p128r, p128i);
            if (t4 & 1) { ur = p128r; ui = p128i; }
            csqr(p128r, p128i);
            if (t4 & 2) cmul(ur, ui, ur, ui, p128r, p128i);
            csqr(p128r, p128i);
            fence_regs(a0); fence_regs(a1);
            if (t == 0) STAMP(1, 7 + 6 * cw);
            if (ti > 0) {
                const unsigned long long tmask = 0x0000000100000001ull, tval = ((unsigned long long)(tag >> 1) << 32) | (tag & 1u);
                unsigned long long u0 = tval, u1 = tval;
                ap -= D_DIM * (1 + t4);
                int it = 0;
                do {
                    asm volatile("{\n.reg .pred p, q;\nsetp.gt.s32 p, %3, 0;\nsetp.gt.s32 q, %3, 4;\n@p ld.relaxed.gpu.global.u64 %0, [%2];\n"
                                 "@q ld.relaxed.gpu.global.u64 %1, [%2+-32768];\n}\n" : "+l"(u0), "+l"(u1) : "l"(ap), "r"(ti - t4) : "memory");
                } while (__any_sync(0xffffffffu, (((u0 ^ tval) | (u1 ^ tval)) & tmask) != 0) && ++it < (1 << 22));
                float Pr = __uint_as_float((unsigned)u1 & ~1u), Pi = __uint_as_float((unsigned)(u1 >> 32) & ~1u);
                cmul(Pr, Pi, Pr, Pi, p128r, p128i);
                Pr += __uint_as_float((unsigned)u0 & ~1u); Pi += __uint_as_float((unsigned)(u0 >> 32) & ~1u);
                cmul(Pr, Pi, Pr, Pi, ur, ui);
                Pr += __shfl_xor_sync(0xffffffffu, Pr, 1); Pi += __shfl_xor_sync(0xffffffffu, Pi, 1);
                Pr += __shfl_xor_sync(0xffffffffu, Pr, 2); Pi += __shfl_xor_sync(0xffffffffu, Pi, 2);
                exr += qr * Pr - qi * Pi;
                exi += qr * Pi + qi * Pr;
            }
            if (t == 0) STAMP(1, 4 + 6 * cw);
            char* hp = reinterpret_cast<char*>(g_H) + (size_t)((2 * ti) * 16 + (cg >> 1)) * 16384 + ((cg & 1) * 32 + w4 * 8 + g) * 64 + ((t4 ^ (g >> 1)) << 4);
            float fxr = ar + p32r * exr - p32i * exi, fxi = ai + p32r * exi + p32i * exr;
            const uint32_t hs = sbase + OFF_BB + (w4 * 8 + g) * 64 + ((t4 ^ (g >> 1)) << 4);
            if (cw == 1) named_bar(2, 128);
#pragma unroll
            for (int jj = 0; jj < 4; ++jj) {
                uint32_t pr[4], qq[4], pi[4], qi[4];
#pragma unroll
                for (int j4 = 0; j4 < 4; ++j4) {
                    const int j = jj * 4 + j4;
                    const float r0 = fmaf(mr, exr, fmaf(-mi, exi, a0[4 * j])), i0 = fmaf(mr, exi, fmaf(mi, exr, a0[4 * j + 2]));
                    const float r1 = fmaf(mr, fxr, fmaf(-mi, fxi, a1[4 * j])), i1 = fmaf(mr, fxi, fmaf(mi, fxr, a1[2 + 4 * j]));
                    exr = fmaf(mr, r0, fmaf(-mi, i0, a0[4 * j + 1]));
                    exi = fmaf(mr, i0, fmaf(mi, r0, a0[4 * j + 3]));
                    fxr = fmaf(mr, r1, fmaf(-mi, i1, a1[1 + 4 * j]));
                    fxi = fmaf(mr, i1, fmaf(mi, r1, a1[3 + 4 * j]));
                    pr[j4] = pack_bf16(r0, exr); pi[j4] = pack_bf16(i0, exi);
                    qq[j4] = pack_bf16(r1, fxr); qi[j4] = pack_bf16(i1, fxi);
                }
                if (cw == 0) {
                    stg128(hp + jj * 4096, pr[0], pr[1], pr[2], pr[3]);
                    stg128(hp + jj * 4096 + 262144, qq[0], qq[1], qq[2], qq[3]);
                    stg128(hp + jj * 4096 + 131072, pi[0], pi[1], pi[2], pi[3]);
                    stg128(hp + jj * 4096 + 393216, qi[0], qi[1], qi[2], qi[3]);
                } else {
                    sts128(hs + jj * 2048, pr[0], pr[1], pr[2], pr[3]);
                    sts128(hs + jj * 2048 + 8192, qq[0], qq[1], qq[2], qq[3]);
                    sts128(hs + jj * 2048 + 16384, pi[0], pi[1], pi[2], pi[3]);
                    sts128(hs + jj * 2048 + 24576, qi[0], qi[1], qi[2], qi[3]);
                }
            }
            if (t == 0) STAMP(1, 5 + 6 * cw);
            if (cw == 0) {
                named_bar(1, 128);
                if (t == 0) { red_release(&g_cnt[(2 * ti) * 32], 4); mbar_arrive(bar_rel); }
                if (t == 0) STAMP(1, 6);
                __syncwarp();
            } else {
                fence_async_smem();
                __syncwarp();
                if (lane == 0) mbar_arrive(bar_hw);
            }
            if (t == 0) STAMP(1, 50 + cw);
        }
        if (cw == 0) {
            float c0[64], c1[64];
            wgmma_fence();
#pragma unroll
            for (int i = 0; i < QD2; ++i) wgmma_commit();
            int pst = 0;
            auto kblock = [&](int kb, auto shallow) {
                const int t = fresh_tid() & 127, lane = t & 31;
                const int st = ring_slot(kb);
                mbar_wait(bar_full2 + 8 * st, ring_par(kb));
                if (kb == 0 && t == 0) STAMP(2, 6);
                if (kb == 0 && lane == 0) mbar_arrive(bar_g2);
                const uint32_t alo = desc_lo(sbase + st * 32768, 4096), blo = desc_lo(sbase + st * 32768 + 16384, 16);
                constexpr int Q = decltype(shallow)::value;
#pragma unroll
                for (int j = 0; j < 8; ++j) {
                    wgmma_fence();
                    if (j & 1) wgmma_n128<1>(c1, alo + 512 + 64 * (j >> 1), blo + 2 * (j >> 1), j >> 1 ? 1 : kb);
                    else wgmma_n128<1>(c0, alo + 64 * (j >> 1), blo + 2 * (j >> 1), j >> 1 ? 1 : kb);
                    wgmma_commit();
                    wgmma_wait<Q>();
                    if (j == Q - 1 && kb > 0 && t == 0) mbar_arrive(bar_empty2 + 8 * pst);
                }
                pst = st;
            };
#pragma unroll 1
            for (int kb = 0; kb < QKB; ++kb) kblock(kb, std::integral_constant<int, QD>());
#pragma unroll 1
            for (int kb = QKB; kb < 32 - SKEW2; ++kb) kblock(kb, std::integral_constant<int, QD2>());
            static_assert(SKEW2 <= (SLOT5 < 32 ? 6 : 4), "slot release");
            const uint32_t alo = desc_lo(sbase, 4096), blo = desc_lo(sbase + 16384, 16);
#pragma unroll
            for (int kb = 32 - SKEW2; kb < 32; ++kb) {
                mbar_wait(bar_full2 + 8 * ring_slot(kb), ring_par(kb));
                wgmma_fence();
#pragma unroll
                for (int k = 0; k < 4; ++k) wgmma_n128<1>(c0, alo + ring_slot(kb) * 2048 + 64 * k, blo + ring_slot(kb) * 2048 + 2 * k, 1);
                wgmma_commit();
                if (SLOT5 < 32 && SKEW2 < 6 && kb == 33 - SKEW2) {
                    wgmma_wait<2>();
                    if ((fresh_tid() & 127) == 0) mbar_arrive(bar_o1);
                }
                if (SKEW2 == 6 && kb == 26) {
                    wgmma_wait<1>();
                    if ((fresh_tid() & 127) == 0) mbar_arrive(bar_empty2 + 8 * ring_slot(25));
                }
            }
            auto late = [&](int kb) {
                wgmma_fence();
#pragma unroll
                for (int k = 0; k < 4; ++k) wgmma_n128<1>(c1, alo + 512 + ring_slot(kb) * 2048 + 64 * k, blo + ring_slot(kb) * 2048 + 2 * k, 1);
                wgmma_commit();
            };
            late(32 - SKEW2);
            const int t = fresh_tid() & 127, lane = t & 31, w4 = t >> 5, g = lane >> 2, t4 = lane & 3;
            auto epilogue = [&](const float (&a)[64], int b) {
                const uint32_t ad0 = sbase + (b ? OFF_O1 : OFF_CU) + (w4 * 16 + g) * 128 + (((2 * t4) ^ g) << 4);
                float gt[2];
                uint32_t bv[4][4];
#pragma unroll
                for (int h = 0; h < 2; ++h) gt[h] = __uint_as_float(lds32(sbase + OFF_PAR + (64 * b + 16 * w4 + 8 * h + g) * 4));
#pragma unroll
                for (int i = 0; i < 4; ++i)
                    asm volatile("ld.shared.v4.b32 {%0,%1,%2,%3}, [%4];" : "=r"(bv[i][0]), "=r"(bv[i][1]), "=r"(bv[i][2]), "=r"(bv[i][3])
                                 : "r"(ad0 + (i & 1) * 1024 + (i >> 1) * 8192) : "memory");
                if (b == 0) wgmma_wait<1>(); else wgmma_wait<0>();
                if (b == 0) fence_regs(c0); else fence_regs(c1);
                if (t == 0) STAMP(2, b ? 2 : 5);
#pragma unroll
                for (int jq = 0; jq < 4; ++jq) {
#pragma unroll
                    for (int h = 0; h < 2; ++h) {
                        const uint32_t ad = ad0 + h * 1024 + jq * 8192;
                        uint32_t (&w)[4] = bv[2 * (jq & 1) + h];
                        const int r = 16 * jq + 2 * h;
                        sts128(ad, __float_as_uint(fmaf(gt[h], a[r], bf_lo(w[0]))), __float_as_uint(fmaf(gt[h], a[r + 1], bf_hi(w[0]))),
                               __float_as_uint(fmaf(gt[h], a[r + 4], bf_lo(w[1]))), __float_as_uint(fmaf(gt[h], a[r + 5], bf_hi(w[1]))));
                        sts128(ad ^ 16, __float_as_uint(fmaf(gt[h], a[r + 8], bf_lo(w[2]))), __float_as_uint(fmaf(gt[h], a[r + 9], bf_hi(w[2]))),
                               __float_as_uint(fmaf(gt[h], a[r + 12], bf_lo(w[3]))), __float_as_uint(fmaf(gt[h], a[r + 13], bf_hi(w[3]))));
                        if (jq < 2) asm volatile("ld.shared.v4.b32 {%0,%1,%2,%3}, [%4];" : "=r"(w[0]), "=r"(w[1]), "=r"(w[2]), "=r"(w[3]) : "r"(ad + 16384) : "memory");
                    }
                    fence_async_smem();
                    __syncwarp();
                    if (lane == 0) mbar_arrive(bar_stg + 48 + 32 * b + 8 * jq);
                    if (b == 0 && jq < SKEW2 - 1) late(33 - SKEW2 + jq);
                    if (SKEW2 == 6 && b == 0 && jq == 0) {
                        wgmma_wait<1>();
                        if (t == 0) mbar_arrive(bar_o1);
                    }
                    if (SKEW2 == 6 && b == 0 && jq == 3) late(31);
                }
            };
            mbar_wait(bar_bias, 0);
            if (t == 0) STAMP(2, 4);
            epilogue(c0, 0);
            mbar_wait(bar_bias + 8, 0);
            epilogue(c1, 1);
            if (t == 0) STAMP(2, 7);
            return;
        }
        asm volatile("setmaxnreg.dec.sync.aligned.u32 %0;" ::"n"(REG_C));
    }
    {
        {
            const int t = fresh_tid() & 127, lane = t & 31, w4 = t >> 5;
            Twiddle tw;
            load_twiddle(tw, reinterpret_cast<const uint4*>(g_tw_tab.w) + t);
            const uint32_t lo = (uint32_t)((16 * w4 + (lane & 7)) * 64 + (((lane >> 3) ^ ((lane >> 1) & 3)) << 4));
            const uint32_t tlo = desc_lo(sbase + OFF_CT, 16);
            float dE[32], dO[32];
            int p = wg == 2 ? 2 : 0;
            mbar_wait(bar_stg, 0);
            mbar_wait(bar_tab, 0);
            mbar_wait(bar_k + 8 * p, 0);
            if (t == 0) STAMP(0, wg == 2 ? 50 : 1);
            wgmma_fence();
            conv_s1(dE, dO, tlo, desc_lo(sbase + conv_buf(0) + p * 16384, 8192));
            wgmma_commit();
            wgmma_wait<0>();
            fence_regs(dE); fence_regs(dO);
            named_bar(wg, 128);
#pragma unroll 1
            for (; p < 4; p = 2 * p + 1) {
                const int pn = p < 2 ? 2 * p + 1 : p;
                if (t == 0) STAMP(0, 40 + 2 * p);
                conv_pair(dE, dO, tw, lds32(w_dsk + ((lane & 3) ? 16 : 4 * p)), tlo, sbase + conv_buf(p), sbase + conv_buf(pn), lo, wg,
                                [&]() { mbar_wait(bar_k + 8 * pn, 0); });
                if (lane == 0) mbar_arrive(bar_stg + 16 + 8 * p);
            }
            if (t == 0) STAMP(0, 57 + wg);
            __syncwarp();
        }
        if (wg == 2) {
            {
            const int t = fresh_tid() & 127, lane = t & 31, w4 = t >> 5, g = lane >> 2, t4 = lane & 3;
            const int bid = lds32(w_bid), dt = bid & 7;
            const int trow = (bid >> 4) * 256 + 4 * (bid & 8) + 128 * (w4 & 1) + 8 * (w4 >> 1) + g;
            uint4 xv[16], dk[4];
            const __nv_bfloat16* xp = x + (size_t)trow * D_DIM + dt * 128 + 8 * t4;
#pragma unroll
            for (int i = 0; i < 16; ++i) {
                xv[i] = ldg128(xp + (size_t)(16 * (i >> 3) + 64 * ((i >> 2) & 1)) * D_DIM + 32 * (i & 3));
                if (i & 1) __nanosleep(GAP_X);
            }
#pragma unroll
            for (int jq = 0; jq < 4; ++jq) dk[jq] = ldg128(dskip + dt * 128 + 32 * jq + 8 * t4);
            mbar_wait(bar_fh, 0);
            uint32_t omg[4], g2[4];
#pragma unroll
            for (int i = 0; i < 4; ++i) {
                const float gt = __ldcg(g_gate + trow + 16 * (i >> 1) + 64 * (i & 1));
                if (t4 == 0) asm volatile("st.shared.f32 [%0], %1;" ::"r"(sbase + OFF_PAR + (64 * (i >> 1) + 16 * w4 + 8 * (i & 1) + g) * 4), "f"(gt) : "memory");
                omg[i] = pack_bf16(2.f - 2.f * gt, 2.f - 2.f * gt); g2[i] = pack_bf16(gt, gt);
            }
            if (t == 0) {
                mbar_wait(bar_yrel, 0);
                wait_counter(&g_cnt[(48 + dt) * 32], lds32(w_bid + 4));
                STAMP(0, 16);
                mbar_expect_tx(bar_y1, 24576);
                tma_load_5d(sbase + OFF_CU, &maps.yt3, bar_y1, (bid & 8) * 128 + (bid >> 4) * 128, 0, 0, 0, dt * 4);
                tma_load_5d(sbase + OFF_CU + 12288, &maps.yt3, bar_y1, (bid & 8) * 128 + (bid >> 4) * 128 + 64, 0, 0, 0, dt * 4);
            }
            __syncwarp();
            uint32_t ya = sbase + OFF_CU + (w4 & 1) * 12288 + (lane >> 3) * 3072 + (lane & 7) * 128 + ((((w4 >> 1) ^ ((bid >> 3 & 2) + (w4 & 1))) ^ (lane & 7)) << 4);
            mbar_wait(bar_y1, 0);
            if (t == 0) STAMP(0, 18);
#pragma unroll
            for (int p = 0; p < 3; ++p)
#pragma unroll
                for (int i = 0; i < 4; ++i) {
                    uint32_t yw[4];
                    ldsm_x4_t(yw[0], yw[1], yw[2], yw[3], (ya ^ ((i & 1) << 6) ^ ((i & 2) << 4)) + p * 1024);
#pragma unroll
                    for (int jq = 0; jq < 4; ++jq) {
                        uint32_t& w = (&xv[4 * i + jq].x)[p];
                        w = hfma(g2[i], hmul(w, (&dk[jq].x)[p]), hmul(omg[i], hmul(w, yw[jq])));
                    }
                }
            uint32_t xd[16], yw[16];
#pragma unroll
            for (int i = 0; i < 16; ++i) { xd[i] = hmul(xv[i].w, dk[i & 3].w); asm volatile("" : "+r"(xd[i]), "+r"(xv[i].x), "+r"(xv[i].y), "+r"(xv[i].z)); }
            if (t == 0) STAMP(0, 17);
            ya += 24576 - (w4 & 1) * 8192 - (lane >> 3) * 2048;
            mbar_wait(bar_y, 0);
            if (t == 0) STAMP(0, 6);
#pragma unroll
            for (int i = 0; i < 4; ++i) ldsm_x4_t(yw[4 * i], yw[4 * i + 1], yw[4 * i + 2], yw[4 * i + 3], ya ^ ((i & 1) << 6) ^ ((i & 2) << 4));
            named_bar(2, 128);
#pragma unroll
            for (int i = 0; i < 16; ++i) {
                if (SLOT5 < 32 && i == 8) mbar_wait(bar_o1, 0);
                sts128(sbase + (i & 8 ? OFF_O1 : OFF_CU) + (i & 3) * 8192 + (w4 * 16 + g + (i & 4) * 2) * 128 + (((2 * t4) ^ g) << 4), xv[i].x, xv[i].y, xv[i].z,
                       hfma(g2[i >> 2], xd[i], hmul(omg[i >> 2], hmul(xv[i].w, yw[i]))));
                if ((i & 7) == 7) {
                    __syncwarp();
                    if (lane == 0) mbar_arrive(bar_bias + (i & 8));
                }
            }
            if (t == 0) STAMP(0, 7);
            }
        }
    }
    }
}

void make_map(CUtensorMap* m, const void* ptr, int rank, const cuuint64_t* dims, const cuuint64_t* strides, const cuuint32_t* box,
              CUtensorMapSwizzle swz, bool f32 = false) {
    cuuint32_t es[5] = {1, 1, 1, 1, 1};
    get_encode()(m, f32 ? CU_TENSOR_MAP_DATA_TYPE_FLOAT32 : CU_TENSOR_MAP_DATA_TYPE_BFLOAT16, rank, const_cast<void*>(ptr), dims, strides, box, es,
                 CU_TENSOR_MAP_INTERLEAVE_NONE, swz, CU_TENSOR_MAP_L2_PROMOTION_L2_256B, CU_TENSOR_MAP_FLOAT_OOB_FILL_NONE);
}
void make_map_2d(CUtensorMap* m, const void* ptr, uint64_t inner, uint64_t outer, uint32_t box_in, uint32_t box_out) {
    cuuint64_t dims[2] = {inner, outer};
    cuuint64_t strides[1] = {inner * 2};
    cuuint32_t box[2] = {box_in, box_out};
    make_map(m, ptr, 2, dims, strides, box, CU_TENSOR_MAP_SWIZZLE_128B);
}
void make_map_conv(CUtensorMap* m, const void* p, uint32_t nch = 2) {
    cuuint64_t dims[4] = {32, 32, 2, 1024};
    cuuint64_t strides[3] = {128, 64, 4096};
    cuuint32_t box[4] = {32, 32, 2, nch};
    make_map(m, p, 4, dims, strides, box, CU_TENSOR_MAP_SWIZZLE_64B);
}

}

extern "C" void kernel_launch(void* const* d_in, const int* in_sizes, int n_in, void* d_out, int out_size) {
    const __nv_bfloat16* x = (const __nv_bfloat16*)d_in[0];
    const __nv_bfloat16* lam_re = (const __nv_bfloat16*)d_in[1];
    const __nv_bfloat16* lam_im = (const __nv_bfloat16*)d_in[2];
    const __nv_bfloat16* b_re = (const __nv_bfloat16*)d_in[3];
    const __nv_bfloat16* b_im = (const __nv_bfloat16*)d_in[4];
    const __nv_bfloat16* c_re = (const __nv_bfloat16*)d_in[5];
    const __nv_bfloat16* c_im = (const __nv_bfloat16*)d_in[6];
    const __nv_bfloat16* log_dt = (const __nv_bfloat16*)d_in[7];
    const __nv_bfloat16* dskip = (const __nv_bfloat16*)d_in[8];
    const __nv_bfloat16* kin = (const __nv_bfloat16*)d_in[10];
    const __nv_bfloat16* vin = (const __nv_bfloat16*)d_in[11];
    const __nv_bfloat16* shift_k = (const __nv_bfloat16*)d_in[12];
    const __nv_bfloat16* ssm_k = (const __nv_bfloat16*)d_in[13];
    const __nv_bfloat16* ssm_D = (const __nv_bfloat16*)d_in[14];
    const __nv_bfloat16* gate_w = (const __nv_bfloat16*)d_in[15];
    float* out = (float*)d_out;

    void *yptr = nullptr, *kvtptr = nullptr;
    cudaGetSymbolAddress(&yptr, g_y2);
    cudaGetSymbolAddress(&kvtptr, g_kvT);

    Maps maps;
    {
        cuuint64_t dims[5] = {1024, 2, 4, 32, 8};
        cuuint64_t strides[4] = {2048, 64 * 2048, 2 * 2048, 256 * 2048};
        cuuint32_t box[5] = {64, 2, 4, 32, 1};
        make_map(&maps.x5, x, 5, dims, strides, box, CU_TENSOR_MAP_SWIZZLE_128B);
    }
    int bmode = 0;
    {
        const uint64_t a = (uint64_t)b_re, b = (uint64_t)b_im;
        const uint64_t delta = a < b ? b - a : a - b;
        if (delta != 0 && (delta & 15) == 0 && delta < (1ull << 40)) bmode = a < b ? 1 : 2;
        cuuint64_t dims[4] = {1024, 8, 2, 128};
        cuuint64_t strides[3] = {2048, bmode ? delta : 16, 16384};
        cuuint32_t box[4] = {64, 8, 2, 4};
        make_map(&maps.b4, a < b ? b_re : b_im, 4, dims, strides, box, CU_TENSOR_MAP_SWIZZLE_128B);
    }
    make_map_2d(&maps.bre, b_re, 1024, 1024, 64, 8);
    make_map_2d(&maps.bim, b_im, 1024, 1024, 64, 8);
    {
        cuuint64_t dims[3] = {S_LEN, 128, 8};
        cuuint64_t strides[2] = {8 * 4096, 4096};
        cuuint32_t box[3] = {64, 16, 2};
        make_map(&maps.kvst, kvtptr, 3, dims, strides, box, CU_TENSOR_MAP_SWIZZLE_128B);
    }
    make_map_conv(&maps.sk, ssm_k, 1);
    for (int i = 0; i < 2; ++i) {
        cuuint64_t dims[5] = {1024, 2, 4, 4, 32};
        cuuint64_t strides[4] = {2048, 8 * 2048, 2 * 2048, 32 * 2048};
        cuuint32_t box[5] = {64, 2, 4, 4, 4};
        make_map(i ? &maps.cim : &maps.cre, i ? c_im : c_re, 5, dims, strides, box, CU_TENSOR_MAP_SWIZZLE_128B);
    }
    {
        cuuint64_t dims[5] = {S_LEN, 2, 4, 4, 32};
        cuuint64_t strides[4] = {4096, 8 * 4096, 2 * 4096, 32 * 4096};
        cuuint32_t box[5] = {64, 2, 4, 1, 4};
        make_map(&maps.yt, yptr, 5, dims, strides, box, CU_TENSOR_MAP_SWIZZLE_128B);
        box[3] = 3;
        make_map(&maps.yt3, yptr, 5, dims, strides, box, CU_TENSOR_MAP_SWIZZLE_128B);
    }
    {
        cuuint64_t dims[5] = {D_DIM, 8, 4, 8, 8};
        cuuint64_t strides[4] = {4096, 64 * 4096, 8 * 4096, 256 * 4096};
        cuuint32_t box[5] = {32, 8, 4, 2, 1};
        make_map(&maps.out, out, 5, dims, strides, box, CU_TENSOR_MAP_SWIZZLE_128B, true);
    }

    auto kern = bmode == 1 ? fused_kernel<1> : bmode == 2 ? fused_kernel<2> : fused_kernel<0>;
    cudaFuncSetAttribute(kern, cudaFuncAttributeMaxDynamicSharedMemorySize, SMEM_BYTES);
    static int grid = 0;
    if (!grid) {
        int dev = 0, sms = 0;
        cudaGetDevice(&dev);
        cudaDeviceGetAttribute(&sms, cudaDevAttrMultiProcessorCount, dev);
        grid = sms == 132 ? 132 : 128;
    }
    kern<<<grid, 512, SMEM_BYTES>>>(x, b_re, b_im, kin, vin, ssm_k, shift_k, ssm_D, lam_re, lam_im, log_dt, gate_w, dskip, c_re, c_im, maps);
}
```
